```python
import torch

def _softmax(x, axis=-1):
    return torch.softmax(x, dim=axis)

def _gelu(x):
    return torch.nn.functional.gelu(x, approximate='tanh')

def _silu(x):
    return torch.nn.functional.silu(x)

def _sigmoid(x):
    return torch.sigmoid(x)

def _layernorm(x, axis=-1, eps=1e-05):
    m = x.mean(dim=axis, keepdim=True)
    v = x.var(dim=axis, keepdim=True, unbiased=False)
    return (x - m) / torch.sqrt(v + eps)

def _scatter_add(tgt, idx, src, axis=0):
    return tgt.clone().index_add_(axis, idx, src)

def _segment_sum(src, seg, n):
    out = torch.zeros((n,) + src.shape[1:], dtype=src.dtype)
    return out.index_add_(0, seg, src)

def _pad(x, pw):
    flat = tuple((v for pair in reversed(pw) for v in pair))
    return torch.nn.functional.pad(x, flat)
kernel_name = 'standalone__window_attn_davit__vision'

def setup_inputs():

    _w = lambda a: (lambda t: t.to(torch.bfloat16) if t.is_floating_point() else t)(torch.as_tensor(a))
    HW = 512
    C0 = 192
    ws = 7
    nh = 4
    H = W = max(HW // ws * ws, ws)
    C = max(C0 // nh * nh, nh)
    k = 3
    return {'x': _w((lambda *s: torch.randn(*s, dtype=torch.bfloat16) * 1.6)(1, H, W, C)), 'dw_pe': _w((lambda *s: torch.randn(*s, dtype=torch.bfloat16) * 1.6)(k, k, C) * 0.1), 'w_qkv': _w((lambda *s: torch.randn(*s, dtype=torch.bfloat16) * 1.6)(C, 3 * C) * C ** (-0.5)), 'w_o': _w((lambda *s: torch.randn(*s, dtype=torch.bfloat16) * 0.4)(C, C) * C ** (-0.5))}

def reference(x, dw_pe, w_qkv, w_o):
    B, H, W, C = x.shape
    ws = 7
    nh = 4
    dh = C // nh
    kk = dw_pe.shape[0]
    pad = kk // 2
    xp = _pad(x, ((0, 0), (pad, pad), (pad, pad), (0, 0)))
    pe = torch.zeros_like(x)
    for i in range(kk):
        for j in range(kk):
            pe = pe + xp[:, i:i + H, j:j + W, :] * dw_pe[i, j][None, None, None, :]
    x0 = x + pe
    h = _layernorm(x0, axis=-1)
    hw = h.reshape(B, H // ws, ws, W // ws, ws, C)
    hw = (lambda x, *d: x.permute(*d))(hw, 0, 1, 3, 2, 4, 5)
    hw = hw.reshape(-1, ws * ws, C)
    qkv = (hw @ w_qkv).reshape(-1, ws * ws, 3, nh, dh)
    q = qkv[:, :, 0].clone()
    k = qkv[:, :, 1].clone()
    v = qkv[:, :, 2].clone()
    scale = dh ** (-0.5)
    attn = torch.einsum('wnhd,wmhd->whnm', q, k) * scale
    attn = _softmax(attn, axis=-1)
    out = torch.einsum('whnm,wmhd->wnhd', attn, v)
    out = out.reshape(-1, ws * ws, C) @ w_o
    out = out.reshape(B, H // ws, W // ws, ws, ws, C)
    out = (lambda x, *d: x.permute(*d))(out, 0, 1, 3, 2, 4, 5)
    out = out.reshape(B, H, W, C)
    return x0 + out
```

```cpp
#include <cuda.h>
#include <cuda_bf16.h>
#include <cuda_runtime.h>
#include <stdint.h>

namespace {

constexpr int kImg = 511;
constexpr int kCh = 192;
constexpr int kWinPerCol = 73;
constexpr int kNumWin = 73 * 73;

constexpr uint32_t W_PART = 36864;
constexpr uint32_t W_STEP = 3072;
constexpr uint32_t WO_STEP = 6144;
constexpr uint32_t W_BYTES = 8 * W_PART;

struct Scratch {
  uint8_t weights[W_BYTES];
  uint32_t ready;
  uint32_t passed;
  uint8_t redo[kNumWin];
};
__device__ __align__(128) Scratch g_scratch;

constexpr uint32_t OFF_RING = 0;
constexpr uint32_t OFF_X0 = 3 * W_PART;
constexpr uint32_t X0_CHUNK = 49 * 128;
constexpr uint32_t X0_SIZE = 3 * X0_CHUNK;
constexpr uint32_t OFF_HALO = OFF_X0 + 2 * X0_SIZE;
constexpr uint32_t HALO_ROW = 9 * 128;
constexpr uint32_t HALO_SLOT = 3 * HALO_ROW;
constexpr uint32_t OFF_KV = OFF_HALO + 6 * HALO_SLOT;
constexpr uint32_t K_CHUNK = 784;
constexpr uint32_t A_K0 = 0;
constexpr uint32_t A_V0 = 6 * K_CHUNK;
constexpr uint32_t A_ONES = A_V0 + 5376;
constexpr uint32_t A_V1 = A_ONES + 896;
constexpr uint32_t A_K1 = A_V1 + 5376;
constexpr uint32_t KV_SIZE = A_K1 + 6 * K_CHUNK;
constexpr uint32_t OUT_GROUP = 3328;
constexpr uint32_t OUT_HALF = 11008;
__host__ __device__ constexpr uint32_t out_group(uint32_t g) { return (g / 3) * OUT_HALF + (g % 3) * OUT_GROUP; }
__host__ __device__ constexpr uint32_t out_flip(uint32_t g) { return (out_group(g) >> 8) & 1; }
static_assert(64 + out_group(2) + 3136 <= A_ONES && out_group(3) >= A_V1 && 64 + out_group(5) + 3136 <= KV_SIZE, "output staging");
constexpr uint32_t OFF_TAIL = OFF_KV + 3 * KV_SIZE;
constexpr uint32_t SMEM_BYTES = OFF_TAIL + 320;
static_assert(SMEM_BYTES <= 232448, "shared memory");

constexpr uint32_t T_FULL = 0;
constexpr uint32_t T_EMPTY = 24;
constexpr uint32_t T_X0FULL = 48;
constexpr uint32_t T_X0FREE = 72;
constexpr uint32_t T_HALO = 88;
constexpr uint32_t T_WG = 136;
constexpr uint32_t B_KVRDY = 0;
constexpr uint32_t B_KVFREE = 8;
constexpr uint32_t B_OUTRDY = 16;
constexpr uint32_t B_OUTFREE = 24;
constexpr uint32_t T_RAW = 232;
constexpr uint32_t T_ZERO = 240;
constexpr uint32_t T_SCALE = 256;
constexpr uint32_t T_ALL = 260;
constexpr uint32_t T_ANY = 264;
constexpr uint32_t T_DUMP = 268;

__device__ __forceinline__ void hmma_n96_first(uint32_t (&d)[24], uint32_t a0, uint32_t a1, uint32_t a2, uint32_t a3, uint64_t desc) {
  asm volatile("wgmma.mma_async.sync.aligned.m64n96k16.f16.f16.f16 "
               "{%0, %1, %2, %3, %4, %5, %6, %7, %8, %9, %10, %11, %12, %13, %14, %15, "
               "%16, %17, %18, %19, %20, %21, %22, %23}, "
               "{%24, %25, %26, %27}, %28, 0, 1, 1, 0;\n"
               : "=r"(d[0]), "=r"(d[1]), "=r"(d[2]), "=r"(d[3]), "=r"(d[4]), "=r"(d[5]), "=r"(d[6]), "=r"(d[7]),
                 "=r"(d[8]), "=r"(d[9]), "=r"(d[10]), "=r"(d[11]), "=r"(d[12]), "=r"(d[13]), "=r"(d[14]), "=r"(d[15]),
                 "=r"(d[16]), "=r"(d[17]), "=r"(d[18]), "=r"(d[19]), "=r"(d[20]), "=r"(d[21]), "=r"(d[22]), "=r"(d[23])
               : "r"(a0), "r"(a1), "r"(a2), "r"(a3), "l"(desc));
}
__device__ __forceinline__ void hmma_n96(uint32_t (&d)[24], uint32_t a0, uint32_t a1, uint32_t a2, uint32_t a3, uint64_t desc) {
  asm volatile("wgmma.mma_async.sync.aligned.m64n96k16.f16.f16.f16 "
               "{%0, %1, %2, %3, %4, %5, %6, %7, %8, %9, %10, %11, %12, %13, %14, %15, "
               "%16, %17, %18, %19, %20, %21, %22, %23}, "
               "{%24, %25, %26, %27}, %28, 1, 1, 1, 0;\n"
               : "+r"(d[0]), "+r"(d[1]), "+r"(d[2]), "+r"(d[3]), "+r"(d[4]), "+r"(d[5]), "+r"(d[6]), "+r"(d[7]),
                 "+r"(d[8]), "+r"(d[9]), "+r"(d[10]), "+r"(d[11]), "+r"(d[12]), "+r"(d[13]), "+r"(d[14]), "+r"(d[15]),
                 "+r"(d[16]), "+r"(d[17]), "+r"(d[18]), "+r"(d[19]), "+r"(d[20]), "+r"(d[21]), "+r"(d[22]), "+r"(d[23])
               : "r"(a0), "r"(a1), "r"(a2), "r"(a3), "l"(desc));
}
__device__ __forceinline__ void hmma_n96_over(uint32_t (&d)[24], uint32_t a0, uint32_t a1, uint32_t a2, uint32_t a3, uint64_t desc) {
  asm volatile("wgmma.mma_async.sync.aligned.m64n96k16.f16.f16.f16 "
               "{%0, %1, %2, %3, %4, %5, %6, %7, %8, %9, %10, %11, %12, %13, %14, %15, "
               "%16, %17, %18, %19, %20, %21, %22, %23}, "
               "{%24, %25, %26, %27}, %28, 0, 1, 1, 0;\n"
               : "+r"(d[0]), "+r"(d[1]), "+r"(d[2]), "+r"(d[3]), "+r"(d[4]), "+r"(d[5]), "+r"(d[6]), "+r"(d[7]),
                 "+r"(d[8]), "+r"(d[9]), "+r"(d[10]), "+r"(d[11]), "+r"(d[12]), "+r"(d[13]), "+r"(d[14]), "+r"(d[15]),
                 "+r"(d[16]), "+r"(d[17]), "+r"(d[18]), "+r"(d[19]), "+r"(d[20]), "+r"(d[21]), "+r"(d[22]), "+r"(d[23])
               : "r"(a0), "r"(a1), "r"(a2), "r"(a3), "l"(desc));
}
__device__ __forceinline__ void hmma_n56_first(uint32_t (&d)[14], uint32_t a0, uint32_t a1, uint32_t a2, uint32_t a3, uint64_t desc) {
  asm volatile("wgmma.mma_async.sync.aligned.m64n56k16.f16.f16.f16 "
               "{%0, %1, %2, %3, %4, %5, %6, %7, %8, %9, %10, %11, %12, %13}, "
               "{%14, %15, %16, %17}, %18, 0, 1, 1, 0;\n"
               : "=r"(d[0]), "=r"(d[1]), "=r"(d[2]), "=r"(d[3]), "=r"(d[4]), "=r"(d[5]), "=r"(d[6]), "=r"(d[7]),
                 "=r"(d[8]), "=r"(d[9]), "=r"(d[10]), "=r"(d[11]), "=r"(d[12]), "=r"(d[13])
               : "r"(a0), "r"(a1), "r"(a2), "r"(a3), "l"(desc));
}
__device__ __forceinline__ void hmma_n56(uint32_t (&d)[14], uint32_t a0, uint32_t a1, uint32_t a2, uint32_t a3, uint64_t desc) {
  asm volatile("wgmma.mma_async.sync.aligned.m64n56k16.f16.f16.f16 "
               "{%0, %1, %2, %3, %4, %5, %6, %7, %8, %9, %10, %11, %12, %13}, "
               "{%14, %15, %16, %17}, %18, 1, 1, 1, 0;\n"
               : "+r"(d[0]), "+r"(d[1]), "+r"(d[2]), "+r"(d[3]), "+r"(d[4]), "+r"(d[5]), "+r"(d[6]), "+r"(d[7]),
                 "+r"(d[8]), "+r"(d[9]), "+r"(d[10]), "+r"(d[11]), "+r"(d[12]), "+r"(d[13])
               : "r"(a0), "r"(a1), "r"(a2), "r"(a3), "l"(desc));
}
__device__ __forceinline__ void hmma_n192(uint32_t (&d)[48], uint32_t a0, uint32_t a1, uint32_t a2, uint32_t a3, uint64_t desc) {
  asm volatile("wgmma.mma_async.sync.aligned.m64n192k16.f16.f16.f16 "
               "{%0, %1, %2, %3, %4, %5, %6, %7, %8, %9, %10, %11, %12, %13, %14, %15, "
               "%16, %17, %18, %19, %20, %21, %22, %23, %24, %25, %26, %27, %28, %29, %30, %31, "
               "%32, %33, %34, %35, %36, %37, %38, %39, %40, %41, %42, %43, %44, %45, %46, %47}, "
               "{%48, %49, %50, %51}, %52, 1, 1, 1, 0;\n"
               : "+r"(d[0]), "+r"(d[1]), "+r"(d[2]), "+r"(d[3]), "+r"(d[4]), "+r"(d[5]), "+r"(d[6]), "+r"(d[7]),
                 "+r"(d[8]), "+r"(d[9]), "+r"(d[10]), "+r"(d[11]), "+r"(d[12]), "+r"(d[13]), "+r"(d[14]), "+r"(d[15]),
                 "+r"(d[16]), "+r"(d[17]), "+r"(d[18]), "+r"(d[19]), "+r"(d[20]), "+r"(d[21]), "+r"(d[22]), "+r"(d[23]),
                 "+r"(d[24]), "+r"(d[25]), "+r"(d[26]), "+r"(d[27]), "+r"(d[28]), "+r"(d[29]), "+r"(d[30]), "+r"(d[31]),
                 "+r"(d[32]), "+r"(d[33]), "+r"(d[34]), "+r"(d[35]), "+r"(d[36]), "+r"(d[37]), "+r"(d[38]), "+r"(d[39]),
                 "+r"(d[40]), "+r"(d[41]), "+r"(d[42]), "+r"(d[43]), "+r"(d[44]), "+r"(d[45]), "+r"(d[46]), "+r"(d[47])
               : "r"(a0), "r"(a1), "r"(a2), "r"(a3), "l"(desc));
}

__device__ __forceinline__ void wg_fence() { asm volatile("wgmma.fence.sync.aligned;\n" ::: "memory"); }
__device__ __forceinline__ void wg_commit() { asm volatile("wgmma.commit_group.sync.aligned;\n" ::: "memory"); }
template <int N> __device__ __forceinline__ void wg_wait() { asm volatile("wgmma.wait_group.sync.aligned %0;\n" ::"n"(N) : "memory"); }
__device__ __forceinline__ uint64_t make_desc(uint32_t addr, uint32_t lbo, uint32_t sbo) {
  return (uint64_t)((addr & 0x3FFFF) >> 4) | ((uint64_t)(lbo >> 4) << 16) | ((uint64_t)(sbo >> 4) << 32);
}
__device__ __forceinline__ uint64_t desc_add(uint64_t d, uint32_t bytes) { return d + (bytes >> 4); }
__device__ __forceinline__ uint64_t desc_at(uint64_t d, uint32_t bytes) {
  uint64_t r;
  asm volatile("mov.b64 %0, %1;" : "=l"(r) : "l"(d));
  return desc_add(r, bytes);
}

__device__ __forceinline__ void mbar_init(uint32_t bar, uint32_t count) {
  asm volatile("mbarrier.init.shared::cta.b64 [%0], %1;" ::"r"(bar), "r"(count) : "memory");
}
__device__ __forceinline__ void mbar_expect_tx(uint32_t bar, uint32_t bytes) {
  asm volatile("mbarrier.arrive.expect_tx.shared::cta.b64 _, [%0], %1;" ::"r"(bar), "r"(bytes) : "memory");
}
__device__ __forceinline__ void mbar_wait(uint32_t bar, uint32_t parity) {
  asm volatile("{\n.reg .pred p;\n.reg .u32 c;\n"
               "mbarrier.try_wait.parity.shared::cta.b64 p, [%0], %1;\n"
               "@p bra DONE;\n"
               "mov.u32 c, 0;\n"
               "SPIN:\n"
               "mbarrier.try_wait.parity.shared::cta.b64 p, [%0], %1, 4000;\n"
               "@p bra DONE;\n"
               "add.u32 c, c, 1;\n"
               "setp.lt.u32 p, c, 1048576;\n"
               "@!p trap;\n"
               "bra SPIN;\n"
               "DONE:\n}" ::"r"(bar), "r"(parity) : "memory");
}
__device__ __forceinline__ void bar_sync(uint32_t id) { asm volatile("bar.sync %0, 128;" ::"r"(id) : "memory"); }
__device__ __forceinline__ void mbar_arrive(uint32_t bar) { asm volatile("mbarrier.arrive.shared::cta.b64 _, [%0];" ::"r"(bar) : "memory"); }
__device__ __forceinline__ void warp_arrive(uint32_t bar, bool first) {
  __syncwarp();
  if (first) mbar_arrive(bar);
}
__device__ __forceinline__ void arrive_elected(uint32_t bar) {
  asm volatile("{\n.reg .pred p;\nelect.sync _|p, 0xffffffff;\n@p mbarrier.arrive.shared::cta.b64 _, [%0];\n}" ::"r"(bar) : "memory");
}
__device__ __forceinline__ void fence_async() { asm volatile("fence.proxy.async.shared::cta;" ::: "memory"); }
__device__ __forceinline__ uint32_t lds32(uint32_t a) {
  uint32_t v;
  asm volatile("ld.shared.b32 %0, [%1];" : "=r"(v) : "r"(a) : "memory");
  return v;
}
__device__ __forceinline__ void lds64(uint32_t a, uint32_t& v0, uint32_t& v1) {
  asm volatile("ld.shared.v2.b32 {%0, %1}, [%2];" : "=r"(v0), "=r"(v1) : "r"(a) : "memory");
}
__device__ __forceinline__ void sts32(uint32_t a, uint32_t v) { asm volatile("st.shared.b32 [%0], %1;" ::"r"(a), "r"(v) : "memory"); }
__device__ __forceinline__ void sts64(uint32_t a, uint32_t v0, uint32_t v1) {
  asm volatile("st.shared.v2.b32 [%0], {%1, %2};" ::"r"(a), "r"(v0), "r"(v1) : "memory");
}
__device__ __forceinline__ void sts32_if(bool on, uint32_t a, uint32_t v) {
  asm volatile("{\n.reg .pred p;\nsetp.ne.u32 p, %2, 0;\n@p st.shared.b32 [%0], %1;\n}" ::"r"(a), "r"(v), "r"((uint32_t)on) : "memory");
}
__device__ __forceinline__ void ldsm4(uint32_t a, uint32_t& r0, uint32_t& r1, uint32_t& r2, uint32_t& r3) {
  asm volatile("ldmatrix.sync.aligned.m8n8.x4.shared.b16 {%0, %1, %2, %3}, [%4];" : "=r"(r0), "=r"(r1), "=r"(r2), "=r"(r3) : "r"(a) : "memory");
}
__device__ __forceinline__ void stsm4(uint32_t a, uint32_t r0, uint32_t r1, uint32_t r2, uint32_t r3) {
  asm volatile("stmatrix.sync.aligned.m8n8.x4.shared.b16 [%0], {%1, %2, %3, %4};" ::"r"(a), "r"(r0), "r"(r1), "r"(r2), "r"(r3) : "memory");
}
__device__ __forceinline__ void stsm2_t(uint32_t a, uint32_t r0, uint32_t r1) {
  asm volatile("stmatrix.sync.aligned.m8n8.x2.trans.shared.b16 [%0], {%1, %2};" ::"r"(a), "r"(r0), "r"(r1) : "memory");
}
__device__ __forceinline__ void stsm4_t(uint32_t a, uint32_t r0, uint32_t r1, uint32_t r2, uint32_t r3) {
  asm volatile("stmatrix.sync.aligned.m8n8.x4.trans.shared.b16 [%0], {%1, %2, %3, %4};" ::"r"(a), "r"(r0), "r"(r1), "r"(r2), "r"(r3) : "memory");
}
__device__ __forceinline__ uint32_t pack_bf16(float lo, float hi) {
  uint32_t r;
  asm("cvt.rn.bf16x2.f32 %0, %1, %2;" : "=r"(r) : "f"(hi), "f"(lo));
  return r;
}
__device__ __forceinline__ uint32_t pack_f16(float lo, float hi) {
  uint32_t r;
  asm("cvt.rn.f16x2.f32 %0, %1, %2;" : "=r"(r) : "f"(hi), "f"(lo));
  return r;
}
__device__ __forceinline__ float bf_lo(uint32_t v) { return __uint_as_float(v << 16); }
__device__ __forceinline__ float bf_hi(uint32_t v) { return __uint_as_float(v & 0xffff0000u); }
__device__ __forceinline__ float h_lo(uint32_t v) {
  float r;
  asm("{\n.reg .b16 l, h;\nmov.b32 {l, h}, %1;\ncvt.f32.f16 %0, l;\n}" : "=f"(r) : "r"(v));
  return r;
}
__device__ __forceinline__ float h_hi(uint32_t v) {
  float r;
  asm("{\n.reg .b16 l, h;\nmov.b32 {l, h}, %1;\ncvt.f32.f16 %0, h;\n}" : "=f"(r) : "r"(v));
  return r;
}
__device__ __forceinline__ uint32_t bf16x2_to_f16x2(uint32_t v) { return pack_f16(bf_lo(v), bf_hi(v)); }
__device__ __forceinline__ uint32_t f16x2_to_bf16x2(uint32_t v) { return pack_bf16(h_lo(v), h_hi(v)); }
__device__ __forceinline__ uint32_t bmul2(uint32_t a, uint32_t b) {
  uint32_t r;
  asm("mul.rn.bf16x2 %0, %1, %2;" : "=r"(r) : "r"(a), "r"(b));
  return r;
}
__device__ __forceinline__ uint32_t badd2(uint32_t a, uint32_t b) {
  uint32_t r;
  asm("add.rn.bf16x2 %0, %1, %2;" : "=r"(r) : "r"(a), "r"(b));
  return r;
}
__device__ __forceinline__ uint32_t bfma2(uint32_t a, uint32_t b, uint32_t c) {
  uint32_t r;
  asm("fma.rn.bf16x2 %0, %1, %2, %3;" : "=r"(r) : "r"(a), "r"(b), "r"(c));
  return r;
}
__device__ __forceinline__ uint32_t hadd2(uint32_t a, uint32_t b) {
  uint32_t d;
  asm("add.rn.f16x2 %0, %1, %2;" : "=r"(d) : "r"(a), "r"(b));
  return d;
}
__device__ __forceinline__ uint32_t hmax2(uint32_t a, uint32_t b) {
  uint32_t d;
  asm("max.f16x2 %0, %1, %2;" : "=r"(d) : "r"(a), "r"(b));
  return d;
}
__device__ __forceinline__ uint32_t hmul2(uint32_t a, uint32_t b) {
  uint32_t d;
  asm("mul.rn.f16x2 %0, %1, %2;" : "=r"(d) : "r"(a), "r"(b));
  return d;
}
__device__ __forceinline__ uint32_t hmul2_lo(uint32_t a, uint32_t r) {
  uint32_t d;
  asm("{\n.reg .b16 l, h;\n.reg .b32 t;\nmov.b32 {l, h}, %2;\nmov.b32 t, {l, l};\nmul.rn.f16x2 %0, %1, t;\n}" : "=r"(d) : "r"(a), "r"(r));
  return d;
}
__device__ __forceinline__ uint32_t hmul2_hi(uint32_t a, uint32_t r) {
  uint32_t d;
  asm("{\n.reg .b16 l, h;\n.reg .b32 t;\nmov.b32 {l, h}, %2;\nmov.b32 t, {h, h};\nmul.rn.f16x2 %0, %1, t;\n}" : "=r"(d) : "r"(a), "r"(r));
  return d;
}
__device__ __forceinline__ float rcp(float x) {
  float r;
  asm("rcp.approx.ftz.f32 %0, %1;" : "=f"(r) : "f"(x));
  return r;
}
__device__ __forceinline__ float rsqrt_fast(float x) {
  float r;
  asm("rsqrt.approx.ftz.f32 %0, %1;" : "=f"(r) : "f"(x));
  return r;
}
template <int N> __device__ __forceinline__ void fence_regs(uint32_t (&d)[N]) {
#pragma unroll
  for (int i = 0; i < N; i++) asm volatile("" : "+r"(d[i])::"memory");
}

__device__ __forceinline__ void row_stats(const uint32_t (&x)[48], bool odd, float& sum, float& squares) {
  float s0 = 0.f, q0 = 0.f, s1 = 0.f, q1 = 0.f;
#pragma unroll
  for (int i = 0; i < 48; i++) {
    const float lo = h_lo(x[i]), hi = h_hi(x[i]);
    if (i & 1) {
      s1 += lo; q1 = fmaf(lo, lo, q1);
      s1 += hi; q1 = fmaf(hi, hi, q1);
    } else {
      s0 += lo; q0 = fmaf(lo, lo, q0);
      s0 += hi; q0 = fmaf(hi, hi, q0);
    }
  }
  sum = (odd ? s1 : s0) + __shfl_xor_sync(0xffffffffu, odd ? s0 : s1, 1);
  squares = (odd ? q1 : q0) + __shfl_xor_sync(0xffffffffu, odd ? q0 : q1, 1);
  sum += __shfl_xor_sync(0xffffffffu, sum, 2);
  squares += __shfl_xor_sync(0xffffffffu, squares, 2);
}
__device__ __forceinline__ void lane_stats_packed(const uint32_t (&x)[48], uint32_t (&t)[2]) {
  uint32_t s[4] = {x[0], x[1], x[2], x[3]}, q[4];
#pragma unroll
  for (int r = 0; r < 4; r++) q[r] = hmul2(x[r], x[r]);
#pragma unroll
  for (int i = 4; i < 48; i++) {
    asm("add.rn.f16x2 %0, %0, %1;" : "+r"(s[i & 3]) : "r"(x[i]));
    asm("fma.rn.f16x2 %0, %1, %1, %0;" : "+r"(q[i & 3]) : "r"(x[i]));
  }
#pragma unroll
  for (int r = 0; r < 2; r++) {
    const uint32_t a = hadd2(s[r], s[r + 2]), b = hadd2(q[r], q[r + 2]);
    t[r] = hadd2(__byte_perm(a, b, 0x5410), __byte_perm(a, b, 0x7632));
  }
}
__device__ __forceinline__ uint32_t quad_stats_packed(const uint32_t (&t)[2], bool odd) {
  const uint32_t u = hadd2(__shfl_xor_sync(0xffffffffu, odd ? t[0] : t[1], 1), odd ? t[1] : t[0]);
  return hadd2(u, __shfl_xor_sync(0xffffffffu, u, 2));
}

__device__ __forceinline__ void store_k(const uint32_t (&k)[24], uint32_t k_st, bool full, bool first_row, uint32_t r) {
  if (full) {
#pragma unroll
    for (int j = 0; j < 12; j += 2)
      stsm4(k_st + (j / 6) * A_K1 + (j % 6) * K_CHUNK, hmul2_lo(k[2 * j], r), hmul2_hi(k[2 * j + 1], r), hmul2_lo(k[2 * j + 2], r),
            hmul2_hi(k[2 * j + 3], r));
  } else {
#pragma unroll
    for (int j = 0; j < 12; j++) sts32_if(first_row, k_st + (j / 6) * A_K1 + (j % 6) * K_CHUNK, hmul2_lo(k[2 * j], r));
    __syncwarp();
  }
}
__device__ __forceinline__ void store_v(const uint32_t (&v)[24], uint32_t v_st, bool full, uint32_t r) {
  if (full) {
#pragma unroll
    for (int j = 0; j < 12; j += 2)
      stsm4_t(v_st + (j / 6) * (A_V1 - A_V0) + (j % 6) * 896, hmul2_lo(v[2 * j], r), hmul2_hi(v[2 * j + 1], r), hmul2_lo(v[2 * j + 2], r),
              hmul2_hi(v[2 * j + 3], r));
  } else {
#pragma unroll
    for (int j = 0; j < 12; j += 2) stsm2_t(v_st + (j / 6) * (A_V1 - A_V0) + (j % 6) * 896, hmul2_lo(v[2 * j], r), hmul2_lo(v[2 * j + 2], r));
  }
}
template <int HALF> __device__ __forceinline__ uint32_t both(uint32_t v) {
  uint32_t d;
  if (HALF == 0) asm("{\n.reg .b16 l, h;\nmov.b32 {l, h}, %1;\nmov.b32 %0, {l, l};\n}" : "=r"(d) : "r"(v));
  else asm("{\n.reg .b16 l, h;\nmov.b32 {l, h}, %1;\nmov.b32 %0, {h, h};\n}" : "=r"(d) : "r"(v));
  return d;
}
__device__ __forceinline__ uint32_t exp2_scaled(uint32_t s, uint32_t c, uint32_t off) {
  uint32_t d;
  asm("{\n.reg .b32 t;\nfma.rn.f16x2 t, %1, %2, %3;\nex2.approx.f16x2 %0, t;\n}" : "=r"(d) : "r"(s), "r"(c), "r"(off));
  return d;
}
__device__ __forceinline__ uint32_t exp2_scaled_low(uint32_t s, uint32_t c, uint32_t off) {
  uint32_t d;
  asm("{\n.reg .b16 l, h, z;\nmov.b32 {l, _}, %1;\nmov.b32 {z, _}, %2;\nmov.b32 {h, _}, %3;\nfma.rn.f16 l, l, z, h;\n"
      "ex2.approx.f16 l, l;\nmov.b16 z, 0;\nmov.b32 %0, {l, z};\n}" : "=r"(d) : "r"(s), "r"(c), "r"(off));
  return d;
}
template <int PAIR>
__device__ __forceinline__ uint32_t softmax_max(uint32_t (&s)[14], uint32_t keep, uint32_t scales) {
  const uint32_t fill = 0xFC00FC00u & ~keep;
  asm("lop3.b32 %0, %0, %1, %2, 0xEA;" : "+r"(s[12]) : "r"(keep), "r"(fill));
  asm("lop3.b32 %0, %0, %1, %2, 0xEA;" : "+r"(s[13]) : "r"(keep), "r"(fill));
  const uint32_t a = hmax2(hmax2(hmax2(s[0], s[2]), hmax2(s[4], s[6])), hmax2(hmax2(s[8], s[10]), s[12]));
  const uint32_t b = hmax2(hmax2(hmax2(s[1], s[3]), hmax2(s[5], s[7])), hmax2(hmax2(s[9], s[11]), s[13]));
  uint32_t m = hmax2(__byte_perm(a, b, 0x5410), __byte_perm(a, b, 0x7632));
  m = hmax2(m, __shfl_xor_sync(0xffffffffu, m, 1));
  m = hmax2(m, __shfl_xor_sync(0xffffffffu, m, 2));
  return hmul2(m, both<PAIR>(scales));
}
template <int PAIR>
__device__ __forceinline__ void softmax_exp(const uint32_t (&s)[14], uint32_t top, uint32_t scales, uint32_t pad, uint32_t (&pa)[14]) {
  uint32_t off;
  asm("sub.rn.f16x2 %0, %1, %2;" : "=r"(off) : "r"(pad), "r"(top));
#pragma unroll
  for (int j = 0; j < 6; j++) {
    pa[2 * j] = exp2_scaled(s[2 * j], both<PAIR>(scales), both<0>(off));
    pa[2 * j + 1] = exp2_scaled(s[2 * j + 1], both<PAIR>(scales), both<1>(off));
  }
  pa[12] = exp2_scaled_low(s[12], both<PAIR>(scales), both<0>(off));
  pa[13] = exp2_scaled_low(s[13], both<PAIR>(scales), both<1>(off));
}
__device__ __forceinline__ void issue_s(uint32_t (&s)[14], const uint32_t* qa, uint64_t k_desc) {
  hmma_n56_first(s, qa[0], qa[1], qa[2], qa[3], k_desc);
#pragma unroll
  for (int k = 1; k < 3; k++) hmma_n56(s, qa[4 * k], qa[4 * k + 1], qa[4 * k + 2], qa[4 * k + 3], desc_add(k_desc, k * 2 * K_CHUNK));
}
__device__ __forceinline__ void issue_pv(uint32_t (&ov)[14], const uint32_t (&pa)[14], uint64_t v_desc) {
  hmma_n56_first(ov, pa[0], pa[1], pa[2], pa[3], v_desc);
#pragma unroll
  for (int k = 1; k < 3; k++) hmma_n56(ov, pa[4 * k], pa[4 * k + 1], pa[4 * k + 2], pa[4 * k + 3], desc_add(v_desc, k * 256));
  hmma_n56(ov, pa[12], pa[13], 0u, 0u, v_desc + (uint64_t)(int64_t)(768 / 16 - ((128 / 16) << 16)));
}
template <int SUM, int VAL>
__device__ __forceinline__ void pack_o(const uint32_t (&ov)[14], uint32_t* o) {
  const uint32_t p = pack_f16(rcp(fmaxf(h_lo(ov[SUM]), 0.5f)), rcp(fmaxf(h_lo(ov[SUM + 1]), 0.5f)));
#pragma unroll
  for (int j = 0; j < 6; j++) {
    o[2 * j] = hmul2_lo(ov[VAL + 2 * j], p);
    o[2 * j + 1] = hmul2_hi(ov[VAL + 2 * j + 1], p);
  }
}
template <bool OVER>
__device__ __forceinline__ void issue_proj(uint32_t (&d)[24], const uint32_t (&x)[48], uint64_t desc) {
  if (OVER) hmma_n96_over(d, x[0], x[1], x[2], x[3], desc);
  else hmma_n96_first(d, x[0], x[1], x[2], x[3], desc);
#pragma unroll
  for (int s = 1; s < 12; s++) hmma_n96(d, x[4 * s], x[4 * s + 1], x[4 * s + 2], x[4 * s + 3], desc_add(desc, s * W_STEP));
}
template <int N>
__device__ __forceinline__ void issue_out(uint32_t (&d)[48], const uint32_t* o, uint64_t desc) {
#pragma unroll
  for (int s = 0; s < N; s++) hmma_n192(d, o[4 * s], o[4 * s + 1], o[4 * s + 2], o[4 * s + 3], desc_add(desc, s * WO_STEP));
}

__device__ __forceinline__ void mma_bf16(float (&c)[4], uint32_t a0, uint32_t a1, uint32_t a2, uint32_t a3, uint32_t b0, uint32_t b1) {
  asm("mma.sync.aligned.m16n8k16.row.col.f32.bf16.bf16.f32 {%0, %1, %2, %3}, {%4, %5, %6, %7}, {%8, %9}, {%0, %1, %2, %3};"
      : "+f"(c[0]), "+f"(c[1]), "+f"(c[2]), "+f"(c[3]) : "r"(a0), "r"(a1), "r"(a2), "r"(a3), "r"(b0), "r"(b1));
}
__device__ __forceinline__ void mma_bf16_k8(float (&d)[4], uint32_t a0, uint32_t a1, uint32_t b, const float (&c)[4]) {
  asm("mma.sync.aligned.m16n8k8.row.col.f32.bf16.bf16.f32 {%0, %1, %2, %3}, {%4, %5}, {%6}, {%7, %8, %9, %10};"
      : "=f"(d[0]), "=f"(d[1]), "=f"(d[2]), "=f"(d[3]) : "r"(a0), "r"(a1), "r"(b), "f"(c[0]), "f"(c[1]), "f"(c[2]), "f"(c[3]));
}
__device__ __forceinline__ bool on_diagonal(uint32_t lane) { return (lane & 3) == (lane >> 3); }
__device__ __forceinline__ float column_stats(const uint32_t (&v)[24], uint32_t lane, uint32_t& hi, uint32_t& lo) {
  float sum[2][4] = {}, sq[2][4] = {}, sr[2][4] = {};
#pragma unroll
  for (int c = 0; c < 24; c += 4) mma_bf16(sum[(c >> 2) & 1], v[c], v[c + 1], v[c + 2], v[c + 3], 0x3F803F80u, 0x3F803F80u);
#pragma unroll
  for (int c = 0; c < 24; c += 2) {
    mma_bf16_k8(sq[(c >> 1) & 1], v[c], v[c + 1], v[c], sq[(c >> 1) & 1]);
    mma_bf16_k8(sr[(c >> 1) & 1], v[c], v[c + 1], v[c + 1], sr[(c >> 1) & 1]);
  }
  const float total = (sum[0][0] + sum[0][2]) + (sum[1][0] + sum[1][2]), mean = total * (1.f / 192.f);
  const bool diag = on_diagonal(lane);
  const float n2 = (lane & 4) ? (sq[0][1] + sq[1][1]) + (sr[0][3] + sr[1][3]) : (sq[0][0] + sq[1][0]) + (sr[0][2] + sr[1][2]);
  hi = diag ? __float_as_uint(n2) : 0u;
  lo = __float_as_uint((diag && n2 > 0.f) ? fmaxf(fmaf(-total, mean, n2), 0.f) : INFINITY);
  return mean;
}
__device__ __forceinline__ uint32_t warp_max_abs(const uint32_t (&v)[8]) {
  uint32_t m = v[0];
#pragma unroll
  for (int c = 1; c < 8; c++) asm("max.NaN.xorsign.abs.bf16x2 %0, %0, %1;" : "+r"(m) : "r"(v[c]));
  return __reduce_max_sync(0xffffffffu, max(m & 0x7fffu, (m >> 16) & 0x7fffu));
}
__device__ __forceinline__ bool norms_in_range(uint32_t hi, uint32_t lo) {
  return hi - 0x08800000u <= 0x7B000000u - 0x08800000u && lo >= hi - (12u << 23);
}
__device__ __forceinline__ int norm_exponent(uint32_t n2) { return (int)(0x453B8000u - n2) >> 24; }
__device__ __forceinline__ void scale_to_f16(uint32_t (&v)[8], uint32_t lane, int e, float mean) {
  const uint32_t ident = on_diagonal(lane) ? (uint32_t)(e + 127) << ((lane & 4) ? 23 : 7) : 0u;
  const float c0 = -mean * __uint_as_float((uint32_t)(e + 127) << 23), c[4] = {c0, c0, c0, c0};
#pragma unroll
  for (int i = 0; i < 8; i += 2) {
    float d[4];
    mma_bf16_k8(d, v[i], v[i + 1], ident, c);
    v[i] = pack_f16(d[0], d[1]);
    v[i + 1] = pack_f16(d[2], d[3]);
  }
}
__device__ __forceinline__ float pow2(int e) { return __uint_as_float((uint32_t)(min(max(e, -126), 127) + 127) << 23); }

constexpr uint32_t kUnits = 24;
constexpr uint32_t RAW_O = W_PART, RAW_RED = RAW_O + 32 * 384;
__device__ __forceinline__ void bulk_load(uint32_t dst, const void* src, uint32_t bytes, uint32_t bar) {
  asm volatile("cp.async.bulk.shared::cluster.global.mbarrier::complete_tx::bytes [%0], [%1], %2, [%3];"
               ::"r"(dst), "l"(src), "r"(bytes), "r"(bar) : "memory");
}
__device__ __forceinline__ void tile_load(uint32_t dst, const CUtensorMap* tm, uint32_t c0, uint32_t c1, uint32_t bar) {
  asm volatile("cp.async.bulk.tensor.2d.shared::cluster.global.tile.mbarrier::complete_tx::bytes [%0], [%1, {%2, %3}], [%4];"
               ::"r"(dst), "l"(tm), "r"(c0), "r"(c1), "r"(bar) : "memory");
}
__device__ __forceinline__ void request_unit(uint32_t u, uint32_t raw, uint32_t bar, const CUtensorMap* tmw, const CUtensorMap* tmwo) {
  const bool is_o = (u & 7) >= 6;
  const uint32_t pair = is_o ? u & 1 : (u & 7) / 3, part = is_o ? 1 : (u & 7) % 3;
  mbar_expect_tx(bar, is_o ? W_PART + 32 * 384 : W_PART);
#pragma unroll
  for (uint32_t i = 0; i < 3; i++) tile_load(raw + i * (192 * 64), tmw, ((part + 1) % 3) * 192 + pair * 96 + 32 * i, 0, bar);
  if (is_o) {
#pragma unroll
    for (uint32_t i = 0; i < 6; i++) tile_load(raw + RAW_O + i * (32 * 64), tmwo, 32 * i, pair * 96 + (u >> 3) * 32, bar);
  }
}
__device__ __forceinline__ void ldsm4_t(uint32_t a, uint32_t* v) {
  asm volatile("ldmatrix.sync.aligned.m8n8.x4.trans.shared.b16 {%0, %1, %2, %3}, [%4];" : "=r"(v[0]), "=r"(v[1]), "=r"(v[2]), "=r"(v[3]) : "r"(a) : "memory");
}
__device__ __forceinline__ void prepare_unit(uint32_t u, uint32_t wid, uint32_t lane, uint32_t raw, Scratch* scr) {
  const bool is_o = (u & 7) >= 6;
  const uint32_t third = u >> 3;
  uint32_t v[24], w[8];
  const uint32_t src = raw + (wid >> 2) * (192 * 64) + lane * 64 + (((wid ^ (lane >> 1)) & 3) << 4);
#pragma unroll
  for (int m = 0; m < 6; m++) ldsm4_t(src + m * (32 * 64), &v[4 * m]);
  uint32_t hi, lo, top = 0;
  const float mean = column_stats(v, lane, hi, lo);
  if (is_o) {
#pragma unroll
    for (int m = 0; m < 2; m++)
      ldsm4_t(raw + RAW_O + (wid >> 1) * (32 * 64) + lane * 64 + ((((2 * wid + m) ^ (lane >> 1)) & 3) << 4), &w[4 * m]);
    top = warp_max_abs(w);
  } else {
#pragma unroll
    for (int m = 0; m < 2; m++) ldsm4_t(src + (2 * third + m) * (32 * 64), &w[4 * m]);
  }
  hi = __reduce_max_sync(0xffffffffu, hi);
  lo = __reduce_min_sync(0xffffffffu, lo);
  if (lane == 0) {
    sts64(raw + RAW_RED + wid * 16, hi, lo);
    sts32(raw + RAW_RED + wid * 16 + 8, top);
  }
  asm volatile("bar.sync 4, 384;" ::: "memory");
  lds64(raw + RAW_RED + (lane % 12) * 16, hi, lo);
  top = lds32(raw + RAW_RED + (lane % 12) * 16 + 8);
  hi = __reduce_max_sync(0xffffffffu, hi);
  lo = __reduce_min_sync(0xffffffffu, lo);
  top = __reduce_max_sync(0xffffffffu, top);
  const int e = norm_exponent(hi);
  scale_to_f16(w, lane, is_o ? -e : e - 4, is_o ? 0.f : mean);
  const uint32_t mat = lane >> 3, at = (mat & 1) * 128 + (lane & 7) * 16;
#pragma unroll
  for (int m = 0; m < 2; m++)
    stsm4(raw + at + (is_o ? (mat >> 1) * WO_STEP + (2 * wid + m) * 256 : (2 * m + (mat >> 1)) * W_STEP + wid * 256), w[4 * m], w[4 * m + 1],
          w[4 * m + 2], w[4 * m + 3]);
  fence_async();
  asm volatile("bar.sync 4, 384;" ::: "memory");
  if (wid == 0 && lane == 0) {
    asm volatile("cp.async.bulk.global.shared::cta.bulk_group [%0], [%1], %2;\ncp.async.bulk.commit_group;"
                 ::"l"(scr->weights + (u & 7) * W_PART + third * (W_PART / 3)), "r"(raw), "n"(W_PART / 3) : "memory");
    const bool bad = is_o ? !(__uint_as_float(top << 16) * pow2(-e) <= 0.25f) : !norms_in_range(hi, lo);
    const uint32_t exponent = (!is_o && third == 0 && u % 3 != 1) ? (uint32_t)(e + 64) << (u < 3 ? 10 : 19) : 0u;
    asm volatile("cp.async.bulk.wait_group 0;" ::: "memory");
    asm volatile("red.relaxed.gpu.global.add.u32 [%0], %1;" ::"l"(&scr->ready), "r"(bad ? 33u : 1u + exponent) : "memory");
  }
  __syncwarp();
}

constexpr uint32_t REDO_BYTES = 75776;
static_assert(3 * REDO_BYTES <= OFF_TAIL && (3 * 49 * 192 + 49 * 144) * 2 <= REDO_BYTES, "redo scratch");
__device__ __forceinline__ float round_bf16(float x) { return __bfloat162float(__float2bfloat16(x)); }
__device__ __forceinline__ void redo_window(int w, int t, uint32_t bar, uint8_t* scratch, const __nv_bfloat16* x,
                                            const __nv_bfloat16* dw, const __nv_bfloat16* wqkv, const __nv_bfloat16* wo,
                                            __nv_bfloat16* out) {
  __nv_bfloat16* x0 = reinterpret_cast<__nv_bfloat16*>(scratch);
  __nv_bfloat16* h = x0 + 49 * 192;
  __nv_bfloat16* o = h + 49 * 192;
  __nv_bfloat16* qkv = o + 49 * 192;
  const int y0 = (w % kWinPerCol) * 7, c0 = (w / kWinPerCol) * 7;
  bar_sync(bar);
#pragma unroll 1
  for (int i = t; i < 49 * 192; i += 128) {
    const int tok = i / 192, c = i % 192, y = y0 + tok / 7, xx = c0 + tok % 7;
    float pe = 0.f;
#pragma unroll 1
    for (int k = 0; k < 9; k++) {
      const int yy = y + k / 3 - 1, xj = xx + k % 3 - 1;
      const bool in = (uint32_t)yy < kImg && (uint32_t)xj < kImg;
      const float v = in ? __bfloat162float(x[((size_t)yy * kImg + xj) * kCh + c]) : 0.f;
      pe = round_bf16(pe + round_bf16(v * __bfloat162float(dw[k * kCh + c])));
    }
    x0[i] = __float2bfloat16(__bfloat162float(x[((size_t)y * kImg + xx) * kCh + c]) + pe);
  }
  bar_sync(bar);
  if (t < 49) {
    float s = 0.f, v = 0.f;
#pragma unroll 1
    for (int c = 0; c < 192; c++) s += __bfloat162float(x0[t * 192 + c]);
    const float mean = s * (1.f / 192.f);
#pragma unroll 1
    for (int c = 0; c < 192; c++) {
      const float d = __bfloat162float(x0[t * 192 + c]) - mean;
      v = fmaf(d, d, v);
    }
    const float m = round_bf16(mean), sd = round_bf16(sqrtf(round_bf16(round_bf16(v * (1.f / 192.f)) + 1e-5f)));
#pragma unroll 1
    for (int c = 0; c < 192; c++) h[t * 192 + c] = __float2bfloat16(round_bf16(__bfloat162float(x0[t * 192 + c]) - m) / sd);
  }
#pragma unroll 1
  for (int head = 0; head < 4; head++) {
    bar_sync(bar);
#pragma unroll 1
    for (int i = t; i < 49 * 144; i += 128) {
      const int tok = i / 144, n = i % 144, col = (n / 48) * 192 + head * 48 + n % 48;
      float a = 0.f;
#pragma unroll 4
      for (int c = 0; c < 192; c++) a = fmaf(__bfloat162float(h[tok * 192 + c]), __bfloat162float(wqkv[c * 576 + col]), a);
      qkv[i] = __float2bfloat16(a);
    }
    bar_sync(bar);
    if (t < 49) {
      float p[49], m = -INFINITY, s = 0.f;
#pragma unroll
      for (int b = 0; b < 49; b++) {
        float a = 0.f;
#pragma unroll 4
        for (int d = 0; d < 48; d++) a = fmaf(__bfloat162float(qkv[t * 144 + d]), __bfloat162float(qkv[b * 144 + 48 + d]), a);
        p[b] = round_bf16(round_bf16(a) * 0.14433757f);
        m = fmaxf(m, p[b]);
      }
#pragma unroll
      for (int b = 0; b < 49; b++) {
        p[b] = expf(p[b] - m);
        s += p[b];
      }
#pragma unroll
      for (int b = 0; b < 49; b++) p[b] = round_bf16(p[b] / s);
#pragma unroll 1
      for (int d = 0; d < 48; d++) {
        float a = 0.f;
#pragma unroll
        for (int b = 0; b < 49; b++) a = fmaf(p[b], __bfloat162float(qkv[b * 144 + 96 + d]), a);
        o[t * 192 + head * 48 + d] = __float2bfloat16(a);
      }
    }
  }
  bar_sync(bar);
#pragma unroll 1
  for (int i = t; i < 49 * 192; i += 128) {
    const int tok = i / 192, n = i % 192;
    float a = 0.f;
#pragma unroll 4
    for (int c = 0; c < 192; c++) a = fmaf(__bfloat162float(o[tok * 192 + c]), __bfloat162float(wo[c * kCh + n]), a);
    out[((size_t)(y0 + tok / 7) * kImg + c0 + tok % 7) * kCh + n] = __float2bfloat16(__bfloat162float(x0[tok * 192 + n]) + round_bf16(a));
  }
}

__device__ __forceinline__ uint32_t fresh_tid() {
  uint32_t t;
  asm volatile("mov.u32 %0, %%tid.x;" : "=r"(t));
  return t;
}
__device__ __forceinline__ void cta_windows(uint32_t n, uint32_t fewer, uint32_t& first, uint32_t& count) {
  first = blockIdx.x * n + (blockIdx.x > fewer ? blockIdx.x - fewer : 0);
  count = n + (blockIdx.x >= fewer ? 1 : 0);
}
template <uint32_t BYTES>
__device__ __forceinline__ void load_rows(uint32_t dst, const CUtensorMap* tm, uint32_t ch, int x, int y, uint32_t bar) {
  asm volatile("{\n.reg .pred p;\nelect.sync _|p, 0xffffffff;\n"
               "@p mbarrier.arrive.expect_tx.shared::cta.b64 _, [%5], %6;\n"
               "@p cp.async.bulk.tensor.3d.shared::cluster.global.tile.mbarrier::complete_tx::bytes [%0], [%1, {%2, %3, %4}], [%5];\n}"
               ::"r"(dst), "l"(tm), "r"(ch), "r"(x), "r"(y), "r"(bar), "n"(BYTES) : "memory");
}
__device__ __forceinline__ void prefetch_rows(const CUtensorMap* tm, int x, int y) {
  asm volatile("{\n.reg .pred p;\nelect.sync _|p, 0xffffffff;\n"
               "@p cp.async.bulk.prefetch.tensor.3d.L2.global.tile [%0, {%1, %2, %3}];\n}" ::"l"(tm), "r"(0), "r"(x), "r"(y) : "memory");
}
__device__ __forceinline__ void store_group(const CUtensorMap* tm, uint32_t src, uint32_t ch, uint32_t x, uint32_t y) {
  asm volatile("cp.async.bulk.tensor.3d.global.shared::cta.tile.bulk_group [%0, {%2, %3, %4}], [%1];"
               ::"l"(tm), "r"(src), "r"(ch), "r"(x), "r"(y) : "memory");
}

struct Conv {
  uint32_t wt[9], prev[9], acc[7];
  __device__ __forceinline__ void begin(const uint32_t (&cur)[9]) {
#pragma unroll
    for (int x = 0; x < 7; x++) {
      uint32_t a = bmul2(prev[x], wt[0]);
      a = bfma2(prev[x + 1], wt[1], a);
      a = bfma2(prev[x + 2], wt[2], a);
#pragma unroll
      for (int t = 0; t < 3; t++) a = bfma2(cur[x + t], wt[3 + t], a);
      acc[x] = a;
    }
#pragma unroll
    for (int x = 0; x < 9; x++) prev[x] = cur[x];
  }
  template <int R0, int N>
  __device__ __forceinline__ void rows(uint32_t src, uint32_t dst) {
#pragma unroll
    for (int r = 0; r < N; r++) {
      uint32_t cur[9];
#pragma unroll
      for (int x = 0; x < 9; x++) cur[x] = lds32(src + (r * 9 + x) * 128);
#pragma unroll
      for (int x = 0; x < 7; x++) {
        uint32_t a = acc[x];
#pragma unroll
        for (int t = 0; t < 3; t++) a = bfma2(cur[x + t], wt[6 + t], a);
        a = badd2(prev[x + 1], a);
        const int t = (R0 + r) * 7 + x;
        sts32((dst ^ ((t & 7) << 4)) + t * 128, bf16x2_to_f16x2(a));
      }
      begin(cur);
    }
  }
};

__global__ void __launch_bounds__(512, 1)
davit_window_attn_kernel(const __grid_constant__ CUtensorMap tm2, const __grid_constant__ CUtensorMap tm3,
                         const __grid_constant__ CUtensorMap tm7, const __grid_constant__ CUtensorMap tmo,
                         const __grid_constant__ CUtensorMap tmw, const __grid_constant__ CUtensorMap tmwo,
                         const __nv_bfloat16* __restrict__ dw, const __nv_bfloat16* __restrict__ x_raw,
                         const __nv_bfloat16* __restrict__ wqkv_raw, const __nv_bfloat16* __restrict__ wo_raw,
                         __nv_bfloat16* __restrict__ out, Scratch* __restrict__ scr, uint32_t per_cta, uint32_t fewer) {
  extern __shared__ __align__(1024) uint8_t smem_raw[];
  const uint32_t sb = (uint32_t)__cvta_generic_to_shared(smem_raw);
  const uint32_t tail = sb + OFF_TAIL;
  uint32_t wt[9];
  {
    const uint32_t tid = threadIdx.x;
    const uint32_t wid = __shfl_sync(0xffffffffu, tid >> 5, 0), lane = tid & 31;
    if (wid > 12) {
      const uint32_t chunk = wid - 13, hbar = tail + T_HALO + 16 * chunk;
      if (lane == 0) {
        mbar_init(hbar, 1);
        mbar_init(hbar + 8, 1);
        fence_async();
      }
      __syncwarp();
      uint32_t first, count;
      cta_windows(per_cta, fewer, first, count);
      const int x = (int)(first / kWinPerCol) * 7 - 1, y = (int)(first % kWinPerCol) * 7 - 1;
      const uint32_t halo = sb + OFF_HALO + chunk * 2 * HALO_SLOT;
      load_rows<2 * HALO_ROW>(halo, &tm2, chunk * 64, x, y, hbar);
      load_rows<2 * HALO_ROW>(halo + HALO_SLOT, &tm2, chunk * 64, x, y + 2, hbar + 8);
#pragma unroll
      for (int i = 0; i < 9; i++) wt[i] = __ldg(reinterpret_cast<const uint32_t*>(dw) + i * (kCh / 2) + chunk * 32 + lane);
    } else {
      if (lane == 0) {
        if (wid < 12) {
          const uint32_t i = 2 * wid, counts = (uint32_t)((wid < 8 ? 0x4144444333CCC111ull >> (8 * wid) : 0x11444144u >> (8 * wid - 64)));
          mbar_init(tail + 8 * (i < 11 ? i : i + 6), counts & 15);
          mbar_init(tail + 8 * (i < 10 ? i + 1 : i + 7), (counts >> 4) & 15);
          fence_async();
          if (wid == 11 && blockIdx.x < kUnits) request_unit(blockIdx.x, sb + OFF_RING, tail + T_RAW, &tmw, &tmwo);
        }
      }
      if (wid == 12) {
        for (uint32_t line = blockIdx.x + gridDim.x * lane; line < 2304; line += gridDim.x * 32) {
          const uint8_t* p = (line < 1728) ? reinterpret_cast<const uint8_t*>(wqkv_raw) + line * 128
                                           : reinterpret_cast<const uint8_t*>(wo_raw) + (line - 1728) * 128;
          asm volatile("prefetch.global.L2 [%0];" ::"l"(p));
        }
        if (lane < 7) sts32(tail + T_ZERO + 4 * lane, 0u);
      } else if ((tid & 127) < 56) {
        const uint32_t a = sb + OFF_KV + (wid >> 2) * KV_SIZE + A_ONES + (tid & 127) * 16;
        sts64(a, 0x3C003C00u, 0x3C003C00u);
        sts64(a + 8, 0x3C003C00u, 0x3C003C00u);
      }
    }
    __syncthreads();
  }

  if (threadIdx.x >= 384) {
    asm volatile("setmaxnreg.dec.sync.aligned.u32 %0;" ::"n"(56));
    const uint32_t tid = fresh_tid();
    const uint32_t warp = __shfl_sync(0xffffffffu, (tid >> 5) & 3, 0), lane = tid & 31;
    uint32_t first, count;
    cta_windows(per_cta, fewer, first, count);
    if (warp == 0) {
      {
        const int x = (int)(first / kWinPerCol) * 7 - 1, y = (int)(first % kWinPerCol) * 7 - 1;
        const bool wrap = y == kImg - 8;
#pragma unroll 1
        for (int r = 3; r < 18; r++) {
          const int yy = (wrap && r >= 9) ? r - 10 : y + r, xx = ((wrap && r >= 9) ? x + 7 : x) * 3 + (int)lane;
          if (lane < 27 && (uint32_t)yy < kImg && (uint32_t)xx < 3 * kImg && (wrap || r < 16))
            asm volatile("prefetch.global.L2 [%0];" ::"l"(reinterpret_cast<const uint8_t*>(x_raw) + ((size_t)yy * (3 * kImg) + xx) * 128));
        }
      }
      if (lane == 0) {
        uint32_t spins = 0, seen;
        while (true) {
          asm volatile("ld.acquire.gpu.global.u32 %0, [%1];" : "=r"(seen) : "l"(&scr->ready) : "memory");
          if ((seen & 31) == kUnits) break;
          if (++spins > (1u << 22)) __trap();
        }
        asm volatile("fence.proxy.async.global;" ::: "memory");
        const uint8_t* w = scr->weights;
        {
          const int e0 = (int)((seen >> 10) & 511) - 128, e1 = (int)(seen >> 19) - 128;
          sts32(tail + T_SCALE, pack_f16(fmaxf(0.20823509f * pow2(9 - e0), 0x1p-24f), fmaxf(0.20823509f * pow2(9 - e1), 0x1p-24f)));
          if ((seen & 0x3E0u) || e0 < 1 || e1 < 1) sts32(tail + T_ALL, 1u);
        }
#pragma unroll
        for (uint32_t s = 0; s < 3; s++) {
          mbar_expect_tx(tail + T_FULL + 8 * s, W_PART);
          bulk_load(sb + OFF_RING + s * W_PART, w + s * W_PART, W_PART, tail + T_FULL + 8 * s);
        }
        if (atomicInc(&scr->passed, gridDim.x - 1) == gridDim.x - 1) scr->ready = 0;
        const uint32_t uses = 3 * ((count + 2) / 3);
        uint32_t k = 1;
#pragma unroll 1
        for (uint32_t u = 1; u < uses; u++) {
#pragma unroll
          for (uint32_t s = 0; s < 3; s++) {
            const uint32_t bytes = (k == 2 && s > 0) ? W_PART / 2 : W_PART;
            const uint32_t off = (k == 2 && s == 2) ? 7 * W_PART + W_PART / 2 : (3 * k + s) * W_PART;
            mbar_wait(tail + T_EMPTY + 8 * s, (u & 1) ^ 1);
            mbar_expect_tx(tail + T_FULL + 8 * s, bytes);
            bulk_load(sb + OFF_RING + s * W_PART, w + off, bytes, tail + T_FULL + 8 * s);
          }
          k = (k == 2) ? 0 : k + 1;
        }
      }
    } else {
      const uint32_t chunk = warp - 1, ch = chunk * 64;
      const uint32_t halo = sb + OFF_HALO + chunk * 2 * HALO_SLOT, hbar = tail + T_HALO + 16 * chunk;
      const uint32_t src0 = halo + lane * 4, dst0 = sb + OFF_X0 + chunk * X0_CHUNK + lane * 4;
      Conv cv;
#pragma unroll
      for (int i = 0; i < 9; i++) cv.wt[i] = wt[i];
      int x = (int)(first / kWinPerCol) * 7 - 1, y = (int)(first % kWinPerCol) * 7;
      bool fresh = true;
      uint32_t c = 0;
      uint32_t n = 0;
#pragma unroll 1
      for (uint32_t j = 0; j < count; j++) {
        const bool more = j + 1 < count, fresh_n = y == kImg - 7;
        const int xn = fresh_n ? x + 7 : x, yn = fresh_n ? 0 : y + 7;
        if (fresh) {
          const uint32_t s = n & 1;
          mbar_wait(hbar + 8 * s, (n >> 1) & 1);
          uint32_t cur[9];
#pragma unroll
          for (int i = 0; i < 9; i++) {
            cv.prev[i] = lds32(src0 + s * HALO_SLOT + i * 128);
            cur[i] = lds32(src0 + s * HALO_SLOT + HALO_ROW + i * 128);
          }
          cv.begin(cur);
          sts32(tail + T_DUMP, cv.acc[0] ^ cv.acc[3] ^ cv.acc[6]);
          load_rows<2 * HALO_ROW>(halo + s * HALO_SLOT, &tm2, ch, x, y + 3, hbar + 8 * s);
          n++;
        }
        const uint32_t s = n & 1, a = s * HALO_SLOT, b = HALO_SLOT - a, bar_a = hbar + 8 * s, bar_b = hbar + 8 - 8 * s;
        const uint32_t dst = dst0 + (j & 1) * X0_SIZE;
        mbar_wait(tail + T_X0FREE + 8 * (j & 1), ((j >> 1) & 1) ^ 1);
        mbar_wait(bar_a, (n >> 1) & 1);
        cv.rows<0, 2>(src0 + a, dst);
        load_rows<3 * HALO_ROW>(halo + a, &tm3, ch, x, y + 5, bar_a);
        if (chunk == 0 && j + 2 < count) {
          if (yn == kImg - 7) {
            prefetch_rows(&tm7, xn + 7, -1);
            prefetch_rows(&tm7, xn + 7, 1);
          } else {
            prefetch_rows(&tm7, xn, yn + 8);
          }
        }
        mbar_wait(bar_b, ((n + 1) >> 1) & 1);
        cv.rows<2, 2>(src0 + b, dst);
        if (more) load_rows<2 * HALO_ROW>(halo + b, &tm2, ch, xn, fresh_n ? yn - 1 : yn + 1, bar_b);
        mbar_wait(bar_a, ((n + 2) >> 1) & 1);
        cv.rows<4, 3>(src0 + a, dst);
        if (more) load_rows<2 * HALO_ROW>(halo + a, &tm2, ch, xn, fresh_n ? yn + 1 : yn + 3, bar_a);
        __syncwarp();
        arrive_elected(tail + T_X0FULL + 8 * c);
        c = (c == 2) ? 0 : c + 1;
        n += 3;
        x = xn; y = yn; fresh = fresh_n;
      }
    }
    __syncwarp();
    asm volatile("bar.sync 0, 512;" ::: "memory");
  } else {
    asm volatile("setmaxnreg.inc.sync.aligned.u32 %0;" ::"n"(152));
    const uint32_t wid = __shfl_sync(0xffffffffu, fresh_tid() >> 5, 0);
    const uint32_t wg = wid >> 2, warp = wid & 3;
    uint32_t lane;
    asm volatile("mov.u32 %0, %%laneid;" : "=r"(lane));
#pragma unroll 1
    for (uint32_t u = blockIdx.x, i = 0; u < kUnits; u += gridDim.x, i++) {
      if (i) {
        asm volatile("bar.sync 4, 384;" ::: "memory");
        if (wid == 0 && lane == 0) request_unit(u, sb + OFF_RING, tail + T_RAW, &tmw, &tmwo);
      }
      mbar_wait(tail + T_RAW, i & 1);
      prepare_unit(u, wid, lane, sb + OFF_RING, scr);
    }
    uint32_t first, count;
    cta_windows(per_cta, fewer, first, count);
    const uint32_t q = lane & 3, mat = lane >> 3, row = lane & 7;
    const uint32_t area = sb + OFF_KV + wg * KV_SIZE, stage = (area + 127) & ~127u;
    const uint32_t bars = tail + T_WG + 32 * wg;
    const bool full = warp < 3;
    const bool valid = full || lane < 4;
    const bool lead = lane == 0;
    uint32_t k_st, v_st, x_ld, x_mask, o_st;
    {
      const uint32_t rowg = full ? 2 * warp + (mat & 1) : 6, colg = full ? (mat >> 1) : (mat & 1);
      k_st = full ? area + A_K0 + colg * K_CHUNK + rowg * 128 + row * 16 : area + A_K0 + 768 + q * 4;
      v_st = area + A_V0 + colg * 896 + rowg * 128 + row * 16;
      const uint32_t t = 16 * warp + row + 8 * (mat & 1);
      x_ld = (t < 49) ? sb + OFF_X0 + t * 128 + (((mat >> 1) ^ row) << 4) : tail + T_ZERO;
      x_mask = (t < 49) ? ~0u : 0u;
      const uint32_t a = stage + (full ? t : 48) * 64;
      o_st = a + (((full ? (mat >> 1) : 0) ^ ((a >> 7) & 3)) << 4) + (full ? 0 : 4 * q);
    }
    const uint32_t keep = q ? 0u : 0xFFFFu;
    const uint32_t pad = (valid ? 0u : 0xFC00u) | (full ? 0u : 0xFC000000u);
    const uint64_t k_desc = make_desc(area + A_K0, K_CHUNK, 128);
    const uint64_t v_desc = make_desc(area + A_V0, 128, 896);
    const uint64_t w_desc = make_desc(sb + OFF_RING, 128, 256);
    if (wg == 2) asm volatile("bar.arrive 8, 256;" ::: "memory");
    mbar_wait(tail + T_FULL, 0);
    const uint32_t scales = lds32(tail + T_SCALE);
    uint32_t ph = 0, j = wg;
#pragma unroll 1
    for (; j < count; j += 3, ph ^= 1) {
      uint32_t x[48], ka[24], va[24], oa[24], ob[24], rr;
      uint32_t (&qa)[24] = ka;
      uint32_t sc0[14], sc1[14], pa0[14], pa1[14], ov0[14], ov1[14];
      mbar_wait(tail + T_X0FULL + 8 * wg, ph);
      {
        asm volatile("" : "+r"(x_mask));
        const uint32_t a = x_ld + ((j & 1) * X0_SIZE & x_mask);
#pragma unroll
        for (int s = 0; s < 12; s++)
          ldsm4((a ^ (((s & 3) << 5) & x_mask)) + ((s >> 2) * X0_CHUNK & x_mask), x[4 * s], x[4 * s + 1], x[4 * s + 2], x[4 * s + 3]);
      }
      uint32_t lane_sums[2];
      lane_stats_packed(x, lane_sums);
      fence_regs(lane_sums);
      warp_arrive(tail + T_X0FREE + 8 * (j & 1), lead);
#pragma unroll
      for (int p = 0; p < 2; p++) {
        if (3 & (1 << p)) asm volatile("bar.sync %0, 256;" ::"r"(8 + wg) : "memory");
        mbar_wait(tail + T_FULL, ph ^ p);
        wg_fence();
        issue_proj<false>(ka, x, desc_at(w_desc, 0));
        wg_commit();
        mbar_wait(tail + T_FULL + 8, ph ^ p);
        wg_fence();
        issue_proj<false>(va, x, desc_at(w_desc, W_PART));
        wg_commit();
        if (3 & (1 << p)) asm volatile("bar.arrive %0, 256;" ::"r"(wg == 2 ? 8 : 9 + wg) : "memory");
        if (p == 0) {
          const bool odd = q & 1;
          const uint32_t packed = quad_stats_packed(lane_sums, odd);
          float sum = h_lo(packed), squares = h_hi(packed);
          const bool fine = (squares >= 0.1875f || (pad & (odd ? 0xFC000000u : 0xFC00u))) & (squares <= 65504.f) & (sum * sum <= 96.f * squares);
          const bool exact = !__all_sync(0xffffffffu, fine);
          if (exact) {
            wg_wait<0>();
            row_stats(x, odd, sum, squares);
          }
          const float mean = sum * (1.f / 192.f);
          const float r = 16.f * rsqrt_fast(fmaxf(fmaf(squares, 1.f / 192.f, -mean * mean), 0.f) + 1e-5f);
          if (exact) {
            const uint32_t range = __reduce_max_sync(0xffffffffu, __float_as_uint(squares * fmaxf(r * r, 1.f)));
            if ((range > 0x4D400000u || (range != 0u && range < 0x4585A800u)) && lead) {
              scr->redo[first + j] = 1;
              sts32(tail + T_ANY, 1u);
            }
          }
          const float o = __shfl_xor_sync(0xffffffffu, r, 1);
          rr = pack_f16(odd ? o : r, odd ? r : o);
          if (!full && lead) {
            asm volatile("cp.async.bulk.wait_group.read 0;" ::: "memory");
            mbar_arrive(bars + B_OUTFREE);
          }
          __syncwarp();
          mbar_wait(bars + B_OUTFREE, ph);
        } else {
          mbar_wait(bars + B_KVFREE, 0);
        }
        wg_wait<1>();
        fence_regs(ka);
        if (lead) mbar_arrive(tail + T_EMPTY);
        store_k(ka, k_st, full, lane < 4, rr);
        mbar_wait(tail + T_FULL + 16, ph ^ p);
        wg_fence();
        issue_proj<true>(qa, x, desc_at(w_desc, 2 * W_PART));
        wg_commit();
        wg_wait<1>();
        fence_regs(va);
        if (lead) mbar_arrive(tail + T_EMPTY + 8);
        store_v(va, v_st, full, rr);
        fence_async();
        warp_arrive(bars + B_KVRDY, lead);
        wg_wait<0>();
        fence_regs(qa);
        if (lead) mbar_arrive(tail + T_EMPTY + 16);
        {
          const uint32_t rq = hmul2(rr, 0x18001800u);
#pragma unroll
          for (int i = 0; i < 24; i += 2) {
            qa[i] = hmul2_lo(qa[i], rq);
            qa[i + 1] = hmul2_hi(qa[i + 1], rq);
          }
        }
        mbar_wait(bars + B_KVRDY, p);

        wg_fence();
        issue_s(sc0, &qa[0], desc_at(k_desc, 0));
        wg_commit();
        uint32_t top0, top1;
        if (p == 0) {
          issue_s(sc1, &qa[12], desc_at(k_desc, A_K1));
          wg_commit();
          wg_wait<1>();
          fence_regs(sc0);
          top0 = softmax_max<0>(sc0, keep, scales);
          softmax_exp<0>(sc0, top0, scales, pad, pa0);
          wg_fence();
          issue_pv(ov0, pa0, desc_at(v_desc, 0));
          wg_commit();
          wg_wait<1>();
          fence_regs(sc1);
          top1 = softmax_max<0>(sc1, keep, scales);
          softmax_exp<0>(sc1, top1, scales, pad, pa1);
        } else {
          wg_wait<0>();
          fence_regs(sc0);
          wg_fence();
          issue_s(sc1, &qa[12], desc_at(k_desc, A_K1));
          wg_commit();
          top0 = softmax_max<1>(sc0, keep, scales);
          wg_wait<0>();
          fence_regs(sc1);
          softmax_exp<1>(sc0, top0, scales, pad, pa0);
          mbar_wait(tail + T_FULL, ph);
          wg_fence();
          issue_pv(ov0, pa0, desc_at(v_desc, 0));
          wg_commit();
          issue_out<6>(x, oa, desc_at(w_desc, 0));
          wg_commit();
          top1 = softmax_max<1>(sc1, keep, scales);
          wg_wait<1>();
          fence_regs(ov0);
          softmax_exp<1>(sc1, top1, scales, pad, pa1);
        }
        wg_fence();
        issue_pv(ov1, pa1, desc_at(v_desc, A_ONES - A_V0));
        wg_commit();
        if (p == 0) {
          wg_wait<1>();
          fence_regs(ov0);
        }
        {
          uint32_t big;
          asm("{\n.reg .pred p, q;\n.reg .b32 t;\nmax.xorsign.abs.f16x2 t, %1, %2;\nabs.f16x2 t, t;\nsetp.gt.f16x2 p|q, t, %3;\n"
              "or.pred p, p, q;\nselp.u32 %0, 1, 0, p;\n}" : "=r"(big) : "r"(top0), "r"(top1), "r"(0x60006000u));
          if (__any_sync(0xffffffffu, big) && lead) {
            scr->redo[first + j] = 1;
            sts32(tail + T_ANY, 1u);
          }
          __syncwarp();
        }
        uint32_t (&o)[24] = (p == 0) ? oa : ob;
        pack_o<12, 0>(ov0, &o[0]);
        if (p == 1) {
          mbar_wait(tail + T_FULL + 8, ph);
          wg_fence();
          issue_out<3>(x, &ob[0], desc_at(w_desc, W_PART));
          wg_commit();
          wg_wait<1>();
          if (lead) mbar_arrive(tail + T_EMPTY);
        } else {
          wg_wait<0>();
        }
        fence_regs(ov1);
        if (lead) mbar_arrive(bars + B_KVFREE);
        pack_o<0, 2>(ov1, &o[12]);
      }
      mbar_wait(tail + T_FULL + 16, ph);
      wg_fence();
      issue_out<3>(x, &ob[12], desc_at(w_desc, 2 * W_PART));
      wg_commit();
      mbar_wait(bars + B_KVFREE, 1);
      wg_wait<1>();
      if (lead) mbar_arrive(tail + T_EMPTY + 8);
      wg_wait<0>();
      fence_regs(x);
      if (lead) mbar_arrive(tail + T_EMPTY + 16);
      asm volatile("" : "+r"(o_st));
      if (full) {
#pragma unroll
        for (int s = 0; s < 12; s++)
          stsm4((o_st ^ (((s & 1) ^ out_flip(s >> 1)) << 5)) + out_group(s >> 1), f16x2_to_bf16x2(x[4 * s]), f16x2_to_bf16x2(x[4 * s + 1]),
                f16x2_to_bf16x2(x[4 * s + 2]), f16x2_to_bf16x2(x[4 * s + 3]));
        fence_async();
        warp_arrive(bars + B_OUTRDY, lead);
      } else {
#pragma unroll
        for (int i = 0; i < 24; i++)
          sts32_if(lane < 4, (o_st ^ (((i & 3) ^ (out_flip(i >> 2) << 1)) << 4)) + out_group(i >> 2), f16x2_to_bf16x2(x[2 * i]));
        fence_async();
        warp_arrive(bars + B_OUTRDY, lead);
        if (lead) {
          const uint32_t wx = ((first + j) * 14365u) >> 20;
          mbar_wait(bars + B_OUTRDY, ph);
#pragma unroll
          for (int i = 0; i < 6; i++) store_group(&tmo, stage + out_group(i), 32 * i, 7 * wx, 7 * (first + j) - kImg * wx);
          asm volatile("cp.async.bulk.commit_group;" ::: "memory");
        }
        __syncwarp();
      }
    }
    if (j - wg < count) {
#pragma unroll 1
      for (uint32_t i = 0; i < 6; i++) {
        if (i % 3 == 0 && (3 & (1 << (i / 3)))) {
          asm volatile("bar.sync %0, 256;" ::"r"(8 + wg) : "memory");
          asm volatile("bar.arrive %0, 256;" ::"r"(wg == 2 ? 8 : 9 + wg) : "memory");
        }
        mbar_wait(tail + T_FULL + 8 * (i % 3), ph ^ (i / 3));
        if (lead) mbar_arrive(tail + T_EMPTY + 8 * (i % 3));
        __syncwarp();
      }
    }
    if (!full && lead) asm volatile("cp.async.bulk.wait_group 0;\nfence.proxy.async.global;" ::: "memory");
    __syncwarp();
    asm volatile("bar.sync 0, 512;" ::: "memory");
    const uint32_t redo_all = lds32(tail + T_ALL);
    if (redo_all | lds32(tail + T_ANY)) {
      const uint32_t t = fresh_tid(), c = t >> 7;
      cta_windows(per_cta, fewer, first, count);
      for (uint32_t v = first + c; v < first + count; v += 3) {
        if (!redo_all && !*reinterpret_cast<volatile uint8_t*>(&scr->redo[v])) continue;
        redo_window(v, t & 127, 1 + c, smem_raw + c * REDO_BYTES, x_raw, dw, wqkv_raw, wo_raw, out);
        if ((t & 127) == 0) scr->redo[v] = 0;
      }
    }
  }
}

typedef CUresult (*EncodeTiledFn)(CUtensorMap*, CUtensorMapDataType, cuuint32_t, void*, const cuuint64_t*, const cuuint64_t*,
                                  const cuuint32_t*, const cuuint32_t*, CUtensorMapInterleave, CUtensorMapSwizzle,
                                  CUtensorMapL2promotion, CUtensorMapFloatOOBfill);

}

extern "C" void kernel_launch(void* const* d_in, const int* in_sizes, int n_in, void* d_out, int out_size) {
  (void)in_sizes; (void)n_in; (void)out_size;
  static EncodeTiledFn encode = nullptr;
  static int grid = 0;
  static void* scratch = nullptr;
  if (!encode) {
    void* fn = nullptr;
    cudaDriverEntryPointQueryResult st;
    cudaGetDriverEntryPoint("cuTensorMapEncodeTiled", &fn, cudaEnableDefault, &st);
    encode = (EncodeTiledFn)fn;
    cudaFuncSetAttribute(davit_window_attn_kernel, cudaFuncAttributeMaxDynamicSharedMemorySize, SMEM_BYTES);
    cudaGetSymbolAddress(&scratch, g_scratch);
    int dev = 0;
    cudaGetDevice(&dev);
    cudaDeviceGetAttribute(&grid, cudaDevAttrMultiProcessorCount, dev);
  }
  auto image_map = [&](void* base, cuuint32_t c, cuuint32_t w, cuuint32_t h, CUtensorMapSwizzle swizzle) {
    CUtensorMap tm;
    const cuuint64_t dims[3] = {(cuuint64_t)kCh, (cuuint64_t)kImg, (cuuint64_t)kImg};
    const cuuint64_t strides[2] = {(cuuint64_t)kCh * 2, (cuuint64_t)kCh * 2 * kImg};
    const cuuint32_t box[3] = {c, w, h};
    const cuuint32_t estr[3] = {1, 1, 1};
    encode(&tm, CU_TENSOR_MAP_DATA_TYPE_BFLOAT16, 3, base, dims, strides, box, estr, CU_TENSOR_MAP_INTERLEAVE_NONE, swizzle,
           CU_TENSOR_MAP_L2_PROMOTION_L2_128B, CU_TENSOR_MAP_FLOAT_OOB_FILL_NONE);
    return tm;
  };
  auto weight_map = [&](void* base, cuuint64_t cols, cuuint32_t rows) {
    CUtensorMap tm;
    const cuuint64_t dims[2] = {cols, (cuuint64_t)kCh};
    const cuuint64_t strides[1] = {cols * 2};
    const cuuint32_t box[2] = {32, rows};
    const cuuint32_t estr[2] = {1, 1};
    encode(&tm, CU_TENSOR_MAP_DATA_TYPE_BFLOAT16, 2, base, dims, strides, box, estr, CU_TENSOR_MAP_INTERLEAVE_NONE,
           CU_TENSOR_MAP_SWIZZLE_64B, CU_TENSOR_MAP_L2_PROMOTION_L2_128B, CU_TENSOR_MAP_FLOAT_OOB_FILL_NONE);
    return tm;
  };
  davit_window_attn_kernel<<<grid, 512, SMEM_BYTES, cudaStreamPerThread>>>(
      image_map(d_in[0], 64, 9, 2, CU_TENSOR_MAP_SWIZZLE_NONE), image_map(d_in[0], 64, 9, 3, CU_TENSOR_MAP_SWIZZLE_NONE),
      image_map(d_in[0], 192, 9, 7, CU_TENSOR_MAP_SWIZZLE_NONE), image_map(d_out, 32, 7, 7, CU_TENSOR_MAP_SWIZZLE_64B),
      weight_map(d_in[2], 576, 192), weight_map(d_in[3], 192, 32),
      (const __nv_bfloat16*)d_in[1], (const __nv_bfloat16*)d_in[0], (const __nv_bfloat16*)d_in[2], (const __nv_bfloat16*)d_in[3],
      (__nv_bfloat16*)d_out, (Scratch*)scratch, kNumWin / grid, grid - kNumWin % grid);
}
```

```cpp
#include <cuda.h>
#include <cuda_bf16.h>
#include <cuda_runtime.h>
#include <stdint.h>

namespace {

constexpr int kImg = 511;
constexpr int kCh = 192;
constexpr int kWinPerCol = 73;
constexpr int kNumWin = 73 * 73;

constexpr uint32_t W_PART = 36864;
constexpr uint32_t W_STEP = 3072;
constexpr uint32_t WO_STEP = 6144;
constexpr uint32_t W_BYTES = 8 * W_PART;

struct Scratch {
  uint8_t weights[W_BYTES];
  uint32_t ready;
  uint32_t passed;
  uint8_t redo[kNumWin];
};
__device__ __align__(128) Scratch g_scratch;

constexpr uint32_t OFF_RING = 0;
constexpr uint32_t OFF_X0 = 3 * W_PART;
constexpr uint32_t kSlots = 2;
constexpr uint32_t kRows = (2 == 3) ? 17 : 19;
constexpr uint32_t X0_ROW = 7 * 128;
constexpr uint32_t X0_CHUNK = kRows * X0_ROW;
constexpr uint32_t OFF_HALO = OFF_X0 + 3 * X0_CHUNK;
constexpr uint32_t HALO_ROW = 9 * 128;
constexpr uint32_t OFF_KV = OFF_HALO + 3 * kSlots * HALO_ROW;
constexpr uint32_t K_CHUNK = 784;
constexpr uint32_t A_K0 = 0;
constexpr uint32_t A_V0 = 6 * K_CHUNK;
constexpr uint32_t A_ONES = A_V0 + 5376;
constexpr uint32_t A_V1 = A_ONES + 896;
constexpr uint32_t A_K1 = A_V1 + 5376;
constexpr uint32_t KV_SIZE = A_K1 + 6 * K_CHUNK;
constexpr uint32_t OUT_GROUP = 3328;
constexpr uint32_t OUT_HALF = 11008;
__host__ __device__ constexpr uint32_t out_group(uint32_t g) { return (g / 3) * OUT_HALF + (g % 3) * OUT_GROUP; }
__host__ __device__ constexpr uint32_t out_flip(uint32_t g) { return (out_group(g) >> 8) & 1; }
static_assert(64 + out_group(2) + 3136 <= A_ONES && out_group(3) >= A_V1 && 64 + out_group(5) + 3136 <= KV_SIZE, "output staging");
constexpr uint32_t OFF_TAIL = OFF_KV + 3 * KV_SIZE;
constexpr uint32_t SMEM_BYTES = OFF_TAIL + 320;
static_assert(SMEM_BYTES <= 232448, "shared memory");

constexpr uint32_t T_FULL = 0;
constexpr uint32_t T_EMPTY = 24;
constexpr uint32_t T_X0FULL = 48;
constexpr uint32_t T_X0FREE = 72;
constexpr uint32_t T_HALO = 88;
constexpr uint32_t T_WG = 136;
constexpr uint32_t B_KVRDY = 0;
constexpr uint32_t B_KVFREE = 8;
constexpr uint32_t B_OUTRDY = 16;
constexpr uint32_t B_OUTFREE = 24;
constexpr uint32_t T_RAW = 232;
constexpr uint32_t T_ZERO = 240;
constexpr uint32_t T_SCALE = 256;
constexpr uint32_t T_ALL = 260;
constexpr uint32_t T_ANY = 264;
constexpr uint32_t T_DUMP = 268;
constexpr uint32_t T_ROW = 272;

__device__ __forceinline__ void hmma_n96_first(uint32_t (&d)[24], uint32_t a0, uint32_t a1, uint32_t a2, uint32_t a3, uint64_t desc) {
  asm volatile("wgmma.mma_async.sync.aligned.m64n96k16.f16.f16.f16 "
               "{%0, %1, %2, %3, %4, %5, %6, %7, %8, %9, %10, %11, %12, %13, %14, %15, "
               "%16, %17, %18, %19, %20, %21, %22, %23}, "
               "{%24, %25, %26, %27}, %28, 0, 1, 1, 0;\n"
               : "=r"(d[0]), "=r"(d[1]), "=r"(d[2]), "=r"(d[3]), "=r"(d[4]), "=r"(d[5]), "=r"(d[6]), "=r"(d[7]),
                 "=r"(d[8]), "=r"(d[9]), "=r"(d[10]), "=r"(d[11]), "=r"(d[12]), "=r"(d[13]), "=r"(d[14]), "=r"(d[15]),
                 "=r"(d[16]), "=r"(d[17]), "=r"(d[18]), "=r"(d[19]), "=r"(d[20]), "=r"(d[21]), "=r"(d[22]), "=r"(d[23])
               : "r"(a0), "r"(a1), "r"(a2), "r"(a3), "l"(desc));
}
__device__ __forceinline__ void hmma_n96(uint32_t (&d)[24], uint32_t a0, uint32_t a1, uint32_t a2, uint32_t a3, uint64_t desc) {
  asm volatile("wgmma.mma_async.sync.aligned.m64n96k16.f16.f16.f16 "
               "{%0, %1, %2, %3, %4, %5, %6, %7, %8, %9, %10, %11, %12, %13, %14, %15, "
               "%16, %17, %18, %19, %20, %21, %22, %23}, "
               "{%24, %25, %26, %27}, %28, 1, 1, 1, 0;\n"
               : "+r"(d[0]), "+r"(d[1]), "+r"(d[2]), "+r"(d[3]), "+r"(d[4]), "+r"(d[5]), "+r"(d[6]), "+r"(d[7]),
                 "+r"(d[8]), "+r"(d[9]), "+r"(d[10]), "+r"(d[11]), "+r"(d[12]), "+r"(d[13]), "+r"(d[14]), "+r"(d[15]),
                 "+r"(d[16]), "+r"(d[17]), "+r"(d[18]), "+r"(d[19]), "+r"(d[20]), "+r"(d[21]), "+r"(d[22]), "+r"(d[23])
               : "r"(a0), "r"(a1), "r"(a2), "r"(a3), "l"(desc));
}
__device__ __forceinline__ void hmma_n96_over(uint32_t (&d)[24], uint32_t a0, uint32_t a1, uint32_t a2, uint32_t a3, uint64_t desc) {
  asm volatile("wgmma.mma_async.sync.aligned.m64n96k16.f16.f16.f16 "
               "{%0, %1, %2, %3, %4, %5, %6, %7, %8, %9, %10, %11, %12, %13, %14, %15, "
               "%16, %17, %18, %19, %20, %21, %22, %23}, "
               "{%24, %25, %26, %27}, %28, 0, 1, 1, 0;\n"
               : "+r"(d[0]), "+r"(d[1]), "+r"(d[2]), "+r"(d[3]), "+r"(d[4]), "+r"(d[5]), "+r"(d[6]), "+r"(d[7]),
                 "+r"(d[8]), "+r"(d[9]), "+r"(d[10]), "+r"(d[11]), "+r"(d[12]), "+r"(d[13]), "+r"(d[14]), "+r"(d[15]),
                 "+r"(d[16]), "+r"(d[17]), "+r"(d[18]), "+r"(d[19]), "+r"(d[20]), "+r"(d[21]), "+r"(d[22]), "+r"(d[23])
               : "r"(a0), "r"(a1), "r"(a2), "r"(a3), "l"(desc));
}
__device__ __forceinline__ void hmma_n56_first(uint32_t (&d)[14], uint32_t a0, uint32_t a1, uint32_t a2, uint32_t a3, uint64_t desc) {
  asm volatile("wgmma.mma_async.sync.aligned.m64n56k16.f16.f16.f16 "
               "{%0, %1, %2, %3, %4, %5, %6, %7, %8, %9, %10, %11, %12, %13}, "
               "{%14, %15, %16, %17}, %18, 0, 1, 1, 0;\n"
               : "=r"(d[0]), "=r"(d[1]), "=r"(d[2]), "=r"(d[3]), "=r"(d[4]), "=r"(d[5]), "=r"(d[6]), "=r"(d[7]),
                 "=r"(d[8]), "=r"(d[9]), "=r"(d[10]), "=r"(d[11]), "=r"(d[12]), "=r"(d[13])
               : "r"(a0), "r"(a1), "r"(a2), "r"(a3), "l"(desc));
}
__device__ __forceinline__ void hmma_n56(uint32_t (&d)[14], uint32_t a0, uint32_t a1, uint32_t a2, uint32_t a3, uint64_t desc) {
  asm volatile("wgmma.mma_async.sync.aligned.m64n56k16.f16.f16.f16 "
               "{%0, %1, %2, %3, %4, %5, %6, %7, %8, %9, %10, %11, %12, %13}, "
               "{%14, %15, %16, %17}, %18, 1, 1, 1, 0;\n"
               : "+r"(d[0]), "+r"(d[1]), "+r"(d[2]), "+r"(d[3]), "+r"(d[4]), "+r"(d[5]), "+r"(d[6]), "+r"(d[7]),
                 "+r"(d[8]), "+r"(d[9]), "+r"(d[10]), "+r"(d[11]), "+r"(d[12]), "+r"(d[13])
               : "r"(a0), "r"(a1), "r"(a2), "r"(a3), "l"(desc));
}
__device__ __forceinline__ void hmma_n192(uint32_t (&d)[48], uint32_t a0, uint32_t a1, uint32_t a2, uint32_t a3, uint64_t desc) {
  asm volatile("wgmma.mma_async.sync.aligned.m64n192k16.f16.f16.f16 "
               "{%0, %1, %2, %3, %4, %5, %6, %7, %8, %9, %10, %11, %12, %13, %14, %15, "
               "%16, %17, %18, %19, %20, %21, %22, %23, %24, %25, %26, %27, %28, %29, %30, %31, "
               "%32, %33, %34, %35, %36, %37, %38, %39, %40, %41, %42, %43, %44, %45, %46, %47}, "
               "{%48, %49, %50, %51}, %52, 1, 1, 1, 0;\n"
               : "+r"(d[0]), "+r"(d[1]), "+r"(d[2]), "+r"(d[3]), "+r"(d[4]), "+r"(d[5]), "+r"(d[6]), "+r"(d[7]),
                 "+r"(d[8]), "+r"(d[9]), "+r"(d[10]), "+r"(d[11]), "+r"(d[12]), "+r"(d[13]), "+r"(d[14]), "+r"(d[15]),
                 "+r"(d[16]), "+r"(d[17]), "+r"(d[18]), "+r"(d[19]), "+r"(d[20]), "+r"(d[21]), "+r"(d[22]), "+r"(d[23]),
                 "+r"(d[24]), "+r"(d[25]), "+r"(d[26]), "+r"(d[27]), "+r"(d[28]), "+r"(d[29]), "+r"(d[30]), "+r"(d[31]),
                 "+r"(d[32]), "+r"(d[33]), "+r"(d[34]), "+r"(d[35]), "+r"(d[36]), "+r"(d[37]), "+r"(d[38]), "+r"(d[39]),
                 "+r"(d[40]), "+r"(d[41]), "+r"(d[42]), "+r"(d[43]), "+r"(d[44]), "+r"(d[45]), "+r"(d[46]), "+r"(d[47])
               : "r"(a0), "r"(a1), "r"(a2), "r"(a3), "l"(desc));
}

__device__ __forceinline__ void wg_fence() { asm volatile("wgmma.fence.sync.aligned;\n" ::: "memory"); }
__device__ __forceinline__ void wg_commit() { asm volatile("wgmma.commit_group.sync.aligned;\n" ::: "memory"); }
template <int N> __device__ __forceinline__ void wg_wait() { asm volatile("wgmma.wait_group.sync.aligned %0;\n" ::"n"(N) : "memory"); }
__device__ __forceinline__ uint64_t make_desc(uint32_t addr, uint32_t lbo, uint32_t sbo) {
  return (uint64_t)((addr & 0x3FFFF) >> 4) | ((uint64_t)(lbo >> 4) << 16) | ((uint64_t)(sbo >> 4) << 32);
}
__device__ __forceinline__ uint64_t desc_add(uint64_t d, uint32_t bytes) { return d + (bytes >> 4); }
__device__ __forceinline__ uint64_t desc_at(uint64_t d, uint32_t bytes) {
  uint64_t r;
  asm volatile("mov.b64 %0, %1;" : "=l"(r) : "l"(d));
  return desc_add(r, bytes);
}

__device__ __forceinline__ void mbar_init(uint32_t bar, uint32_t count) {
  asm volatile("mbarrier.init.shared::cta.b64 [%0], %1;" ::"r"(bar), "r"(count) : "memory");
}
__device__ __forceinline__ void mbar_expect_tx(uint32_t bar, uint32_t bytes) {
  asm volatile("mbarrier.arrive.expect_tx.shared::cta.b64 _, [%0], %1;" ::"r"(bar), "r"(bytes) : "memory");
}
__device__ __forceinline__ void mbar_wait(uint32_t bar, uint32_t parity) {
  asm volatile("{\n.reg .pred p;\n.reg .u32 c;\n"
               "mbarrier.try_wait.parity.shared::cta.b64 p, [%0], %1;\n"
               "@p bra DONE;\n"
               "mov.u32 c, 0;\n"
               "SPIN:\n"
               "mbarrier.try_wait.parity.shared::cta.b64 p, [%0], %1, 4000;\n"
               "@p bra DONE;\n"
               "add.u32 c, c, 1;\n"
               "setp.lt.u32 p, c, 1048576;\n"
               "@!p trap;\n"
               "bra SPIN;\n"
               "DONE:\n}" ::"r"(bar), "r"(parity) : "memory");
}
__device__ __forceinline__ void bar_sync(uint32_t id) { asm volatile("bar.sync %0, 128;" ::"r"(id) : "memory"); }
__device__ __forceinline__ void mbar_arrive(uint32_t bar) { asm volatile("mbarrier.arrive.shared::cta.b64 _, [%0];" ::"r"(bar) : "memory"); }
__device__ __forceinline__ void warp_arrive(uint32_t bar, bool first) {
  __syncwarp();
  if (first) mbar_arrive(bar);
}
__device__ __forceinline__ void arrive_elected(uint32_t bar) {
  asm volatile("{\n.reg .pred p;\nelect.sync _|p, 0xffffffff;\n@p mbarrier.arrive.shared::cta.b64 _, [%0];\n}" ::"r"(bar) : "memory");
}
__device__ __forceinline__ void fence_async() { asm volatile("fence.proxy.async.shared::cta;" ::: "memory"); }
__device__ __forceinline__ uint32_t lds32(uint32_t a) {
  uint32_t v;
  asm volatile("ld.shared.b32 %0, [%1];" : "=r"(v) : "r"(a) : "memory");
  return v;
}
__device__ __forceinline__ void lds64(uint32_t a, uint32_t& v0, uint32_t& v1) {
  asm volatile("ld.shared.v2.b32 {%0, %1}, [%2];" : "=r"(v0), "=r"(v1) : "r"(a) : "memory");
}
__device__ __forceinline__ void sts32(uint32_t a, uint32_t v) { asm volatile("st.shared.b32 [%0], %1;" ::"r"(a), "r"(v) : "memory"); }
__device__ __forceinline__ void sts64(uint32_t a, uint32_t v0, uint32_t v1) {
  asm volatile("st.shared.v2.b32 [%0], {%1, %2};" ::"r"(a), "r"(v0), "r"(v1) : "memory");
}
__device__ __forceinline__ void sts32_if(bool on, uint32_t a, uint32_t v) {
  asm volatile("{\n.reg .pred p;\nsetp.ne.u32 p, %2, 0;\n@p st.shared.b32 [%0], %1;\n}" ::"r"(a), "r"(v), "r"((uint32_t)on) : "memory");
}
__device__ __forceinline__ void ldsm4(uint32_t a, uint32_t& r0, uint32_t& r1, uint32_t& r2, uint32_t& r3) {
  asm volatile("ldmatrix.sync.aligned.m8n8.x4.shared.b16 {%0, %1, %2, %3}, [%4];" : "=r"(r0), "=r"(r1), "=r"(r2), "=r"(r3) : "r"(a) : "memory");
}
__device__ __forceinline__ void stsm4(uint32_t a, uint32_t r0, uint32_t r1, uint32_t r2, uint32_t r3) {
  asm volatile("stmatrix.sync.aligned.m8n8.x4.shared.b16 [%0], {%1, %2, %3, %4};" ::"r"(a), "r"(r0), "r"(r1), "r"(r2), "r"(r3) : "memory");
}
__device__ __forceinline__ void stsm2_t(uint32_t a, uint32_t r0, uint32_t r1) {
  asm volatile("stmatrix.sync.aligned.m8n8.x2.trans.shared.b16 [%0], {%1, %2};" ::"r"(a), "r"(r0), "r"(r1) : "memory");
}
__device__ __forceinline__ void stsm4_t(uint32_t a, uint32_t r0, uint32_t r1, uint32_t r2, uint32_t r3) {
  asm volatile("stmatrix.sync.aligned.m8n8.x4.trans.shared.b16 [%0], {%1, %2, %3, %4};" ::"r"(a), "r"(r0), "r"(r1), "r"(r2), "r"(r3) : "memory");
}
__device__ __forceinline__ uint32_t pack_bf16(float lo, float hi) {
  uint32_t r;
  asm("cvt.rn.bf16x2.f32 %0, %1, %2;" : "=r"(r) : "f"(hi), "f"(lo));
  return r;
}
__device__ __forceinline__ uint32_t pack_f16(float lo, float hi) {
  uint32_t r;
  asm("cvt.rn.f16x2.f32 %0, %1, %2;" : "=r"(r) : "f"(hi), "f"(lo));
  return r;
}
__device__ __forceinline__ float bf_lo(uint32_t v) { return __uint_as_float(v << 16); }
__device__ __forceinline__ float bf_hi(uint32_t v) { return __uint_as_float(v & 0xffff0000u); }
__device__ __forceinline__ float h_lo(uint32_t v) {
  float r;
  asm("{\n.reg .b16 l, h;\nmov.b32 {l, h}, %1;\ncvt.f32.f16 %0, l;\n}" : "=f"(r) : "r"(v));
  return r;
}
__device__ __forceinline__ float h_hi(uint32_t v) {
  float r;
  asm("{\n.reg .b16 l, h;\nmov.b32 {l, h}, %1;\ncvt.f32.f16 %0, h;\n}" : "=f"(r) : "r"(v));
  return r;
}
__device__ __forceinline__ uint32_t bf16x2_to_f16x2(uint32_t v) { return pack_f16(bf_lo(v), bf_hi(v)); }
__device__ __forceinline__ uint32_t f16x2_to_bf16x2(uint32_t v) { return pack_bf16(h_lo(v), h_hi(v)); }
__device__ __forceinline__ uint32_t bmul2(uint32_t a, uint32_t b) {
  uint32_t r;
  asm("mul.rn.bf16x2 %0, %1, %2;" : "=r"(r) : "r"(a), "r"(b));
  return r;
}
__device__ __forceinline__ uint32_t badd2(uint32_t a, uint32_t b) {
  uint32_t r;
  asm("add.rn.bf16x2 %0, %1, %2;" : "=r"(r) : "r"(a), "r"(b));
  return r;
}
__device__ __forceinline__ uint32_t bfma2(uint32_t a, uint32_t b, uint32_t c) {
  uint32_t r;
  asm("fma.rn.bf16x2 %0, %1, %2, %3;" : "=r"(r) : "r"(a), "r"(b), "r"(c));
  return r;
}
__device__ __forceinline__ uint32_t hadd2(uint32_t a, uint32_t b) {
  uint32_t d;
  asm("add.rn.f16x2 %0, %1, %2;" : "=r"(d) : "r"(a), "r"(b));
  return d;
}
__device__ __forceinline__ uint32_t hmax2(uint32_t a, uint32_t b) {
  uint32_t d;
  asm("max.f16x2 %0, %1, %2;" : "=r"(d) : "r"(a), "r"(b));
  return d;
}
__device__ __forceinline__ uint32_t hmul2(uint32_t a, uint32_t b) {
  uint32_t d;
  asm("mul.rn.f16x2 %0, %1, %2;" : "=r"(d) : "r"(a), "r"(b));
  return d;
}
__device__ __forceinline__ uint32_t hmul2_lo(uint32_t a, uint32_t r) {
  uint32_t d;
  asm("{\n.reg .b16 l, h;\n.reg .b32 t;\nmov.b32 {l, h}, %2;\nmov.b32 t, {l, l};\nmul.rn.f16x2 %0, %1, t;\n}" : "=r"(d) : "r"(a), "r"(r));
  return d;
}
__device__ __forceinline__ uint32_t hmul2_hi(uint32_t a, uint32_t r) {
  uint32_t d;
  asm("{\n.reg .b16 l, h;\n.reg .b32 t;\nmov.b32 {l, h}, %2;\nmov.b32 t, {h, h};\nmul.rn.f16x2 %0, %1, t;\n}" : "=r"(d) : "r"(a), "r"(r));
  return d;
}
__device__ __forceinline__ float rcp(float x) {
  float r;
  asm("rcp.approx.ftz.f32 %0, %1;" : "=f"(r) : "f"(x));
  return r;
}
__device__ __forceinline__ float rsqrt_fast(float x) {
  float r;
  asm("rsqrt.approx.ftz.f32 %0, %1;" : "=f"(r) : "f"(x));
  return r;
}
template <int N> __device__ __forceinline__ void fence_regs(uint32_t (&d)[N]) {
#pragma unroll
  for (int i = 0; i < N; i++) asm volatile("" : "+r"(d[i])::"memory");
}

__device__ __forceinline__ void row_stats(const uint32_t (&x)[48], bool odd, float& sum, float& squares) {
  float s0 = 0.f, q0 = 0.f, s1 = 0.f, q1 = 0.f;
#pragma unroll
  for (int i = 0; i < 48; i++) {
    const float lo = h_lo(x[i]), hi = h_hi(x[i]);
    if (i & 1) {
      s1 += lo; q1 = fmaf(lo, lo, q1);
      s1 += hi; q1 = fmaf(hi, hi, q1);
    } else {
      s0 += lo; q0 = fmaf(lo, lo, q0);
      s0 += hi; q0 = fmaf(hi, hi, q0);
    }
  }
  sum = (odd ? s1 : s0) + __shfl_xor_sync(0xffffffffu, odd ? s0 : s1, 1);
  squares = (odd ? q1 : q0) + __shfl_xor_sync(0xffffffffu, odd ? q0 : q1, 1);
  sum += __shfl_xor_sync(0xffffffffu, sum, 2);
  squares += __shfl_xor_sync(0xffffffffu, squares, 2);
}
__device__ __forceinline__ void lane_stats_packed(const uint32_t (&x)[48], uint32_t (&t)[2]) {
  uint32_t s[4] = {x[0], x[1], x[2], x[3]}, q[4];
#pragma unroll
  for (int r = 0; r < 4; r++) q[r] = hmul2(x[r], x[r]);
#pragma unroll
  for (int i = 4; i < 48; i++) {
    asm("add.rn.f16x2 %0, %0, %1;" : "+r"(s[i & 3]) : "r"(x[i]));
    asm("fma.rn.f16x2 %0, %1, %1, %0;" : "+r"(q[i & 3]) : "r"(x[i]));
  }
#pragma unroll
  for (int r = 0; r < 2; r++) {
    const uint32_t a = hadd2(s[r], s[r + 2]), b = hadd2(q[r], q[r + 2]);
    t[r] = hadd2(__byte_perm(a, b, 0x5410), __byte_perm(a, b, 0x7632));
  }
}
__device__ __forceinline__ uint32_t quad_stats_packed(const uint32_t (&t)[2], bool odd) {
  const uint32_t u = hadd2(__shfl_xor_sync(0xffffffffu, odd ? t[0] : t[1], 1), odd ? t[1] : t[0]);
  return hadd2(u, __shfl_xor_sync(0xffffffffu, u, 2));
}

__device__ __forceinline__ void store_k(const uint32_t (&k)[24], uint32_t k_st, bool full, bool first_row, uint32_t r) {
  if (full) {
#pragma unroll
    for (int j = 0; j < 12; j += 2)
      stsm4(k_st + (j / 6) * A_K1 + (j % 6) * K_CHUNK, hmul2_lo(k[2 * j], r), hmul2_hi(k[2 * j + 1], r), hmul2_lo(k[2 * j + 2], r),
            hmul2_hi(k[2 * j + 3], r));
  } else {
#pragma unroll
    for (int j = 0; j < 12; j++) sts32_if(first_row, k_st + (j / 6) * A_K1 + (j % 6) * K_CHUNK, hmul2_lo(k[2 * j], r));
    __syncwarp();
  }
}
__device__ __forceinline__ void store_v(const uint32_t (&v)[24], uint32_t v_st, bool full, uint32_t r) {
  if (full) {
#pragma unroll
    for (int j = 0; j < 12; j += 2)
      stsm4_t(v_st + (j / 6) * (A_V1 - A_V0) + (j % 6) * 896, hmul2_lo(v[2 * j], r), hmul2_hi(v[2 * j + 1], r), hmul2_lo(v[2 * j + 2], r),
              hmul2_hi(v[2 * j + 3], r));
  } else {
#pragma unroll
    for (int j = 0; j < 12; j += 2) stsm2_t(v_st + (j / 6) * (A_V1 - A_V0) + (j % 6) * 896, hmul2_lo(v[2 * j], r), hmul2_lo(v[2 * j + 2], r));
  }
}
template <int HALF> __device__ __forceinline__ uint32_t both(uint32_t v) {
  uint32_t d;
  if (HALF == 0) asm("{\n.reg .b16 l, h;\nmov.b32 {l, h}, %1;\nmov.b32 %0, {l, l};\n}" : "=r"(d) : "r"(v));
  else asm("{\n.reg .b16 l, h;\nmov.b32 {l, h}, %1;\nmov.b32 %0, {h, h};\n}" : "=r"(d) : "r"(v));
  return d;
}
__device__ __forceinline__ uint32_t exp2_scaled(uint32_t s, uint32_t c, uint32_t off) {
  uint32_t d;
  asm("{\n.reg .b32 t;\nfma.rn.f16x2 t, %1, %2, %3;\nex2.approx.f16x2 %0, t;\n}" : "=r"(d) : "r"(s), "r"(c), "r"(off));
  return d;
}
__device__ __forceinline__ uint32_t exp2_scaled_low(uint32_t s, uint32_t c, uint32_t off) {
  uint32_t d;
  asm("{\n.reg .b16 l, h, z;\nmov.b32 {l, _}, %1;\nmov.b32 {z, _}, %2;\nmov.b32 {h, _}, %3;\nfma.rn.f16 l, l, z, h;\n"
      "ex2.approx.f16 l, l;\nmov.b16 z, 0;\nmov.b32 %0, {l, z};\n}" : "=r"(d) : "r"(s), "r"(c), "r"(off));
  return d;
}
template <int PAIR>
__device__ __forceinline__ uint32_t softmax_max(uint32_t (&s)[14], uint32_t keep, uint32_t scales) {
  const uint32_t fill = 0xFC00FC00u & ~keep;
  asm("lop3.b32 %0, %0, %1, %2, 0xEA;" : "+r"(s[12]) : "r"(keep), "r"(fill));
  asm("lop3.b32 %0, %0, %1, %2, 0xEA;" : "+r"(s[13]) : "r"(keep), "r"(fill));
  const uint32_t a = hmax2(hmax2(hmax2(s[0], s[2]), hmax2(s[4], s[6])), hmax2(hmax2(s[8], s[10]), s[12]));
  const uint32_t b = hmax2(hmax2(hmax2(s[1], s[3]), hmax2(s[5], s[7])), hmax2(hmax2(s[9], s[11]), s[13]));
  uint32_t m = hmax2(__byte_perm(a, b, 0x5410), __byte_perm(a, b, 0x7632));
  m = hmax2(m, __shfl_xor_sync(0xffffffffu, m, 1));
  m = hmax2(m, __shfl_xor_sync(0xffffffffu, m, 2));
  return hmul2(m, both<PAIR>(scales));
}
template <int PAIR>
__device__ __forceinline__ void softmax_exp(const uint32_t (&s)[14], uint32_t top, uint32_t scales, uint32_t pad, uint32_t (&pa)[14]) {
  uint32_t off;
  asm("sub.rn.f16x2 %0, %1, %2;" : "=r"(off) : "r"(pad), "r"(top));
#pragma unroll
  for (int j = 0; j < 6; j++) {
    pa[2 * j] = exp2_scaled(s[2 * j], both<PAIR>(scales), both<0>(off));
    pa[2 * j + 1] = exp2_scaled(s[2 * j + 1], both<PAIR>(scales), both<1>(off));
  }
  pa[12] = exp2_scaled_low(s[12], both<PAIR>(scales), both<0>(off));
  pa[13] = exp2_scaled_low(s[13], both<PAIR>(scales), both<1>(off));
}
__device__ __forceinline__ void issue_s(uint32_t (&s)[14], const uint32_t* qa, uint64_t k_desc) {
  hmma_n56_first(s, qa[0], qa[1], qa[2], qa[3], k_desc);
#pragma unroll
  for (int k = 1; k < 3; k++) hmma_n56(s, qa[4 * k], qa[4 * k + 1], qa[4 * k + 2], qa[4 * k + 3], desc_add(k_desc, k * 2 * K_CHUNK));
}
__device__ __forceinline__ void issue_pv(uint32_t (&ov)[14], const uint32_t (&pa)[14], uint64_t v_desc) {
  hmma_n56_first(ov, pa[0], pa[1], pa[2], pa[3], v_desc);
#pragma unroll
  for (int k = 1; k < 3; k++) hmma_n56(ov, pa[4 * k], pa[4 * k + 1], pa[4 * k + 2], pa[4 * k + 3], desc_add(v_desc, k * 256));
  hmma_n56(ov, pa[12], pa[13], 0u, 0u, v_desc + (uint64_t)(int64_t)(768 / 16 - ((128 / 16) << 16)));
}
template <int SUM, int VAL>
__device__ __forceinline__ void pack_o(const uint32_t (&ov)[14], uint32_t* o) {
  const uint32_t p = pack_f16(rcp(fmaxf(h_lo(ov[SUM]), 0.5f)), rcp(fmaxf(h_lo(ov[SUM + 1]), 0.5f)));
#pragma unroll
  for (int j = 0; j < 6; j++) {
    o[2 * j] = hmul2_lo(ov[VAL + 2 * j], p);
    o[2 * j + 1] = hmul2_hi(ov[VAL + 2 * j + 1], p);
  }
}
template <bool OVER>
__device__ __forceinline__ void issue_proj(uint32_t (&d)[24], const uint32_t (&x)[48], uint64_t desc) {
  if (OVER) hmma_n96_over(d, x[0], x[1], x[2], x[3], desc);
  else hmma_n96_first(d, x[0], x[1], x[2], x[3], desc);
#pragma unroll
  for (int s = 1; s < 12; s++) hmma_n96(d, x[4 * s], x[4 * s + 1], x[4 * s + 2], x[4 * s + 3], desc_add(desc, s * W_STEP));
}
template <int FIRST>
__device__ __forceinline__ void issue_half(uint32_t (&d)[24], const uint32_t (&x)[48], uint64_t desc) {
  if (FIRST == 2) hmma_n96_over(d, x[0], x[1], x[2], x[3], desc);
  if (FIRST == 1) hmma_n96_first(d, x[0], x[1], x[2], x[3], desc);
#pragma unroll
  for (int s = FIRST ? 1 : 6; s < (FIRST ? 6 : 12); s++) hmma_n96(d, x[4 * s], x[4 * s + 1], x[4 * s + 2], x[4 * s + 3], desc_add(desc, s * W_STEP));
}
template <int N>
__device__ __forceinline__ void issue_out(uint32_t (&d)[48], const uint32_t* o, uint64_t desc) {
#pragma unroll
  for (int s = 0; s < N; s++) hmma_n192(d, o[4 * s], o[4 * s + 1], o[4 * s + 2], o[4 * s + 3], desc_add(desc, s * WO_STEP));
}

__device__ __forceinline__ void mma_bf16(float (&c)[4], uint32_t a0, uint32_t a1, uint32_t a2, uint32_t a3, uint32_t b0, uint32_t b1) {
  asm("mma.sync.aligned.m16n8k16.row.col.f32.bf16.bf16.f32 {%0, %1, %2, %3}, {%4, %5, %6, %7}, {%8, %9}, {%0, %1, %2, %3};"
      : "+f"(c[0]), "+f"(c[1]), "+f"(c[2]), "+f"(c[3]) : "r"(a0), "r"(a1), "r"(a2), "r"(a3), "r"(b0), "r"(b1));
}
__device__ __forceinline__ void mma_bf16_k8(float (&d)[4], uint32_t a0, uint32_t a1, uint32_t b, const float (&c)[4]) {
  asm("mma.sync.aligned.m16n8k8.row.col.f32.bf16.bf16.f32 {%0, %1, %2, %3}, {%4, %5}, {%6}, {%7, %8, %9, %10};"
      : "=f"(d[0]), "=f"(d[1]), "=f"(d[2]), "=f"(d[3]) : "r"(a0), "r"(a1), "r"(b), "f"(c[0]), "f"(c[1]), "f"(c[2]), "f"(c[3]));
}
__device__ __forceinline__ bool on_diagonal(uint32_t lane) { return (lane & 3) == (lane >> 3); }
__device__ __forceinline__ float column_stats(const uint32_t (&v)[24], uint32_t lane, uint32_t& hi, uint32_t& lo) {
  float sum[2][4] = {}, sq[2][4] = {}, sr[2][4] = {};
#pragma unroll
  for (int c = 0; c < 24; c += 4) mma_bf16(sum[(c >> 2) & 1], v[c], v[c + 1], v[c + 2], v[c + 3], 0x3F803F80u, 0x3F803F80u);
#pragma unroll
  for (int c = 0; c < 24; c += 2) {
    mma_bf16_k8(sq[(c >> 1) & 1], v[c], v[c + 1], v[c], sq[(c >> 1) & 1]);
    mma_bf16_k8(sr[(c >> 1) & 1], v[c], v[c + 1], v[c + 1], sr[(c >> 1) & 1]);
  }
  const float total = (sum[0][0] + sum[0][2]) + (sum[1][0] + sum[1][2]), mean = total * (1.f / 192.f);
  const bool diag = on_diagonal(lane);
  const float n2 = (lane & 4) ? (sq[0][1] + sq[1][1]) + (sr[0][3] + sr[1][3]) : (sq[0][0] + sq[1][0]) + (sr[0][2] + sr[1][2]);
  hi = diag ? __float_as_uint(n2) : 0u;
  lo = __float_as_uint((diag && n2 > 0.f) ? fmaxf(fmaf(-total, mean, n2), 0.f) : INFINITY);
  return mean;
}
__device__ __forceinline__ uint32_t warp_max_abs(const uint32_t (&v)[8]) {
  uint32_t m = v[0];
#pragma unroll
  for (int c = 1; c < 8; c++) asm("max.NaN.xorsign.abs.bf16x2 %0, %0, %1;" : "+r"(m) : "r"(v[c]));
  return __reduce_max_sync(0xffffffffu, max(m & 0x7fffu, (m >> 16) & 0x7fffu));
}
__device__ __forceinline__ bool norms_in_range(uint32_t hi, uint32_t lo) {
  return hi - 0x08800000u <= 0x7B000000u - 0x08800000u && lo >= hi - (12u << 23);
}
__device__ __forceinline__ int norm_exponent(uint32_t n2) { return (int)(0x453B8000u - n2) >> 24; }
__device__ __forceinline__ void scale_to_f16(uint32_t (&v)[8], uint32_t lane, int e, float mean) {
  const uint32_t ident = on_diagonal(lane) ? (uint32_t)(e + 127) << ((lane & 4) ? 23 : 7) : 0u;
  const float c0 = -mean * __uint_as_float((uint32_t)(e + 127) << 23), c[4] = {c0, c0, c0, c0};
#pragma unroll
  for (int i = 0; i < 8; i += 2) {
    float d[4];
    mma_bf16_k8(d, v[i], v[i + 1], ident, c);
    v[i] = pack_f16(d[0], d[1]);
    v[i + 1] = pack_f16(d[2], d[3]);
  }
}
__device__ __forceinline__ float pow2(int e) { return __uint_as_float((uint32_t)(min(max(e, -126), 127) + 127) << 23); }

constexpr uint32_t kUnits = 24;
constexpr uint32_t RAW_O = W_PART, RAW_RED = RAW_O + 32 * 384;
__device__ __forceinline__ void bulk_load(uint32_t dst, const void* src, uint32_t bytes, uint32_t bar) {
  asm volatile("cp.async.bulk.shared::cluster.global.mbarrier::complete_tx::bytes [%0], [%1], %2, [%3];"
               ::"r"(dst), "l"(src), "r"(bytes), "r"(bar) : "memory");
}
__device__ __forceinline__ void tile_load(uint32_t dst, const CUtensorMap* tm, uint32_t c0, uint32_t c1, uint32_t bar) {
  asm volatile("cp.async.bulk.tensor.2d.shared::cluster.global.tile.mbarrier::complete_tx::bytes [%0], [%1, {%2, %3}], [%4];"
               ::"r"(dst), "l"(tm), "r"(c0), "r"(c1), "r"(bar) : "memory");
}
__device__ __forceinline__ void request_unit(uint32_t u, uint32_t raw, uint32_t bar, const CUtensorMap* tmw, const CUtensorMap* tmwo) {
  const bool is_o = (u & 7) >= 6;
  const uint32_t pair = is_o ? u & 1 : (u & 7) / 3, part = is_o ? 1 : (u & 7) % 3;
  mbar_expect_tx(bar, is_o ? W_PART + 32 * 384 : W_PART);
#pragma unroll
  for (uint32_t i = 0; i < 3; i++) tile_load(raw + i * (192 * 64), tmw, ((part + 1) % 3) * 192 + pair * 96 + 32 * i, 0, bar);
  if (is_o) {
#pragma unroll
    for (uint32_t i = 0; i < 6; i++) tile_load(raw + RAW_O + i * (32 * 64), tmwo, 32 * i, pair * 96 + (u >> 3) * 32, bar);
  }
}
__device__ __forceinline__ void ldsm4_t(uint32_t a, uint32_t* v) {
  asm volatile("ldmatrix.sync.aligned.m8n8.x4.trans.shared.b16 {%0, %1, %2, %3}, [%4];" : "=r"(v[0]), "=r"(v[1]), "=r"(v[2]), "=r"(v[3]) : "r"(a) : "memory");
}
__device__ __forceinline__ void prepare_unit(uint32_t u, uint32_t wid, uint32_t lane, uint32_t raw, Scratch* scr) {
  const bool is_o = (u & 7) >= 6;
  const uint32_t third = u >> 3;
  uint32_t v[24], w[8];
  const uint32_t src = raw + (wid >> 2) * (192 * 64) + lane * 64 + (((wid ^ (lane >> 1)) & 3) << 4);
#pragma unroll
  for (int m = 0; m < 6; m++) ldsm4_t(src + m * (32 * 64), &v[4 * m]);
  uint32_t hi, lo, top = 0;
  const float mean = column_stats(v, lane, hi, lo);
  if (is_o) {
#pragma unroll
    for (int m = 0; m < 2; m++)
      ldsm4_t(raw + RAW_O + (wid >> 1) * (32 * 64) + lane * 64 + ((((2 * wid + m) ^ (lane >> 1)) & 3) << 4), &w[4 * m]);
    top = warp_max_abs(w);
  } else {
#pragma unroll
    for (int m = 0; m < 2; m++) ldsm4_t(src + (2 * third + m) * (32 * 64), &w[4 * m]);
  }
  hi = __reduce_max_sync(0xffffffffu, hi);
  lo = __reduce_min_sync(0xffffffffu, lo);
  if (lane == 0) {
    sts64(raw + RAW_RED + wid * 16, hi, lo);
    sts32(raw + RAW_RED + wid * 16 + 8, top);
  }
  asm volatile("bar.sync 4, 384;" ::: "memory");
  lds64(raw + RAW_RED + (lane % 12) * 16, hi, lo);
  top = lds32(raw + RAW_RED + (lane % 12) * 16 + 8);
  hi = __reduce_max_sync(0xffffffffu, hi);
  lo = __reduce_min_sync(0xffffffffu, lo);
  top = __reduce_max_sync(0xffffffffu, top);
  const int e = norm_exponent(hi);
  scale_to_f16(w, lane, is_o ? -e : e - 4, is_o ? 0.f : mean);
  const uint32_t mat = lane >> 3, at = (mat & 1) * 128 + (lane & 7) * 16;
#pragma unroll
  for (int m = 0; m < 2; m++)
    stsm4(raw + at + (is_o ? (mat >> 1) * WO_STEP + (2 * wid + m) * 256 : (2 * m + (mat >> 1)) * W_STEP + wid * 256), w[4 * m], w[4 * m + 1],
          w[4 * m + 2], w[4 * m + 3]);
  fence_async();
  asm volatile("bar.sync 4, 384;" ::: "memory");
  if (wid == 0 && lane == 0) {
    asm volatile("cp.async.bulk.global.shared::cta.bulk_group [%0], [%1], %2;\ncp.async.bulk.commit_group;"
                 ::"l"(scr->weights + (u & 7) * W_PART + third * (W_PART / 3)), "r"(raw), "n"(W_PART / 3) : "memory");
    const bool bad = is_o ? !(__uint_as_float(top << 16) * pow2(-e) <= 0.25f) : !norms_in_range(hi, lo);
    const uint32_t exponent = (!is_o && third == 0 && u % 3 != 1) ? (uint32_t)(e + 64) << (u < 3 ? 10 : 19) : 0u;
    asm volatile("cp.async.bulk.wait_group 0;" ::: "memory");
    asm volatile("red.relaxed.gpu.global.add.u32 [%0], %1;" ::"l"(&scr->ready), "r"(bad ? 33u : 1u + exponent) : "memory");
  }
  __syncwarp();
}

constexpr uint32_t REDO_BYTES = 75776;
static_assert(3 * REDO_BYTES <= OFF_TAIL && (3 * 49 * 192 + 49 * 144) * 2 <= REDO_BYTES, "redo scratch");
__device__ __forceinline__ float round_bf16(float x) { return __bfloat162float(__float2bfloat16(x)); }
__device__ __forceinline__ void redo_window(int w, int t, uint32_t bar, uint8_t* scratch, const __nv_bfloat16* x,
                                            const __nv_bfloat16* dw, const __nv_bfloat16* wqkv, const __nv_bfloat16* wo,
                                            __nv_bfloat16* out) {
  __nv_bfloat16* x0 = reinterpret_cast<__nv_bfloat16*>(scratch);
  __nv_bfloat16* h = x0 + 49 * 192;
  __nv_bfloat16* o = h + 49 * 192;
  __nv_bfloat16* qkv = o + 49 * 192;
  const int y0 = (w % kWinPerCol) * 7, c0 = (w / kWinPerCol) * 7;
  bar_sync(bar);
#pragma unroll 1
  for (int i = t; i < 49 * 192; i += 128) {
    const int tok = i / 192, c = i % 192, y = y0 + tok / 7, xx = c0 + tok % 7;
    float pe = 0.f;
#pragma unroll 1
    for (int k = 0; k < 9; k++) {
      const int yy = y + k / 3 - 1, xj = xx + k % 3 - 1;
      const bool in = (uint32_t)yy < kImg && (uint32_t)xj < kImg;
      const float v = in ? __bfloat162float(x[((size_t)yy * kImg + xj) * kCh + c]) : 0.f;
      pe = round_bf16(pe + round_bf16(v * __bfloat162float(dw[k * kCh + c])));
    }
    x0[i] = __float2bfloat16(__bfloat162float(x[((size_t)y * kImg + xx) * kCh + c]) + pe);
  }
  bar_sync(bar);
  if (t < 49) {
    float s = 0.f, v = 0.f;
#pragma unroll 1
    for (int c = 0; c < 192; c++) s += __bfloat162float(x0[t * 192 + c]);
    const float mean = s * (1.f / 192.f);
#pragma unroll 1
    for (int c = 0; c < 192; c++) {
      const float d = __bfloat162float(x0[t * 192 + c]) - mean;
      v = fmaf(d, d, v);
    }
    const float m = round_bf16(mean), sd = round_bf16(sqrtf(round_bf16(round_bf16(v * (1.f / 192.f)) + 1e-5f)));
#pragma unroll 1
    for (int c = 0; c < 192; c++) h[t * 192 + c] = __float2bfloat16(round_bf16(__bfloat162float(x0[t * 192 + c]) - m) / sd);
  }
#pragma unroll 1
  for (int head = 0; head < 4; head++) {
    bar_sync(bar);
#pragma unroll 1
    for (int i = t; i < 49 * 144; i += 128) {
      const int tok = i / 144, n = i % 144, col = (n / 48) * 192 + head * 48 + n % 48;
      float a = 0.f;
#pragma unroll 4
      for (int c = 0; c < 192; c++) a = fmaf(__bfloat162float(h[tok * 192 + c]), __bfloat162float(wqkv[c * 576 + col]), a);
      qkv[i] = __float2bfloat16(a);
    }
    bar_sync(bar);
    if (t < 49) {
      float p[49], m = -INFINITY, s = 0.f;
#pragma unroll
      for (int b = 0; b < 49; b++) {
        float a = 0.f;
#pragma unroll 4
        for (int d = 0; d < 48; d++) a = fmaf(__bfloat162float(qkv[t * 144 + d]), __bfloat162float(qkv[b * 144 + 48 + d]), a);
        p[b] = round_bf16(round_bf16(a) * 0.14433757f);
        m = fmaxf(m, p[b]);
      }
#pragma unroll
      for (int b = 0; b < 49; b++) {
        p[b] = expf(p[b] - m);
        s += p[b];
      }
#pragma unroll
      for (int b = 0; b < 49; b++) p[b] = round_bf16(p[b] / s);
#pragma unroll 1
      for (int d = 0; d < 48; d++) {
        float a = 0.f;
#pragma unroll
        for (int b = 0; b < 49; b++) a = fmaf(p[b], __bfloat162float(qkv[b * 144 + 96 + d]), a);
        o[t * 192 + head * 48 + d] = __float2bfloat16(a);
      }
    }
  }
  bar_sync(bar);
#pragma unroll 1
  for (int i = t; i < 49 * 192; i += 128) {
    const int tok = i / 192, n = i % 192;
    float a = 0.f;
#pragma unroll 4
    for (int c = 0; c < 192; c++) a = fmaf(__bfloat162float(o[tok * 192 + c]), __bfloat162float(wo[c * kCh + n]), a);
    out[((size_t)(y0 + tok / 7) * kImg + c0 + tok % 7) * kCh + n] = __float2bfloat16(__bfloat162float(x0[tok * 192 + n]) + round_bf16(a));
  }
}

__device__ __forceinline__ uint32_t fresh_tid() {
  uint32_t t;
  asm volatile("mov.u32 %0, %%tid.x;" : "=r"(t));
  return t;
}
__device__ __forceinline__ void cta_windows(uint32_t n, uint32_t fewer, uint32_t& first, uint32_t& count) {
  uint32_t b;
  asm volatile("mov.u32 %0, %%ctaid.x;" : "=r"(b));
  first = b * n + max(b, fewer) - fewer;
  count = n + max(b + 1, fewer) - max(b, fewer);
}
template <uint32_t BYTES>
__device__ __forceinline__ void load_rows(uint32_t dst, const CUtensorMap* tm, uint32_t ch, int x, int y, uint32_t bar) {
  asm volatile("{\n.reg .pred p;\nelect.sync _|p, 0xffffffff;\n"
               "@p mbarrier.arrive.expect_tx.shared::cta.b64 _, [%5], %6;\n"
               "@p cp.async.bulk.tensor.3d.shared::cluster.global.tile.mbarrier::complete_tx::bytes [%0], [%1, {%2, %3, %4}], [%5];\n}"
               ::"r"(dst), "l"(tm), "r"(ch), "r"(x), "r"(y), "r"(bar), "n"(BYTES) : "memory");
}
__device__ __forceinline__ void prefetch_box(const CUtensorMap* tm, int x, int y) {
  asm volatile("cp.async.bulk.prefetch.tensor.3d.L2.global.tile [%0, {%1, %2, %3}];" ::"l"(tm), "r"(0), "r"(x), "r"(y) : "memory");
}
__device__ __forceinline__ void prefetch_rows(const CUtensorMap* tm, int x, int y) {
  asm volatile("{\n.reg .pred p;\nelect.sync _|p, 0xffffffff;\n"
               "@p cp.async.bulk.prefetch.tensor.3d.L2.global.tile [%0, {%1, %2, %3}];\n}" ::"l"(tm), "r"(0), "r"(x), "r"(y) : "memory");
}
__device__ __forceinline__ void store_group(const CUtensorMap* tm, uint32_t src, uint32_t ch, uint32_t x, uint32_t y) {
  asm volatile("cp.async.bulk.tensor.3d.global.shared::cta.tile.bulk_group [%0, {%2, %3, %4}], [%1];"
               ::"l"(tm), "r"(src), "r"(ch), "r"(x), "r"(y) : "memory");
}

template <int N> struct Int { static constexpr int value = N; };
struct Conv {
  uint32_t wt[9], prev[9], acc[7];
  __device__ __forceinline__ void begin(const uint32_t (&cur)[9]) {
#pragma unroll
    for (int x = 0; x < 7; x++) {
      uint32_t a = bmul2(prev[x], wt[0]);
      a = bfma2(prev[x + 1], wt[1], a);
      a = bfma2(prev[x + 2], wt[2], a);
#pragma unroll
      for (int t = 0; t < 3; t++) a = bfma2(cur[x + t], wt[3 + t], a);
      acc[x] = a;
    }
#pragma unroll
    for (int x = 0; x < 9; x++) prev[x] = cur[x];
  }
  __device__ __forceinline__ void start_column(uint32_t slot0, uint32_t bar0, uint32_t parity0, uint32_t slot1, uint32_t bar1,
                                               uint32_t parity1, uint32_t lane, uint32_t dump, bool request, const CUtensorMap* tm,
                                               uint32_t ch, int x, int y) {
    uint32_t cur[9];
    mbar_wait(bar0, parity0);
#pragma unroll
    for (int i = 0; i < 9; i++) prev[i] = lds32(slot0 + lane * 4 + i * 128);
    sts32(dump, prev[0] ^ prev[1] ^ prev[2] ^ prev[3] ^ prev[4] ^ prev[5] ^ prev[6] ^ prev[7] ^ prev[8]);
    if (request) load_rows<HALO_ROW>(slot0, tm, ch, x, y, bar0);
    mbar_wait(bar1, parity1);
#pragma unroll
    for (int i = 0; i < 9; i++) cur[i] = lds32(slot1 + lane * 4 + i * 128);
    begin(cur);
    sts32(dump, acc[0] ^ acc[3] ^ acc[6]);
    if (request) load_rows<HALO_ROW>(slot1, tm, ch, x, y + 1, bar1);
  }
  __device__ __forceinline__ void row_at(uint32_t src, uint32_t dst, uint32_t t) {
    uint32_t cur[9];
#pragma unroll
    for (int x = 0; x < 9; x++) cur[x] = lds32(src + x * 128);
#pragma unroll
    for (int x = 0; x < 7; x++) {
      uint32_t a = acc[x];
#pragma unroll
      for (int i = 0; i < 3; i++) a = bfma2(cur[x + i], wt[6 + i], a);
      sts32((dst ^ (((t + x) & 7) << 4)) + x * 128, bf16x2_to_f16x2(badd2(prev[x + 1], a)));
    }
    begin(cur);
  }
  template <int R>
  __device__ __forceinline__ void row(uint32_t src, uint32_t dst, uint32_t at) {
    uint32_t cur[9];
#pragma unroll
    for (int x = 0; x < 9; x++) cur[x] = lds32(src + x * 128);
#pragma unroll
    for (int x = 0; x < 7; x++) {
      uint32_t a = acc[x];
#pragma unroll
      for (int t = 0; t < 3; t++) a = bfma2(cur[x + t], wt[6 + t], a);
      sts32((dst ^ (((R * 7 + x) & 7) << 4)) + at + x * 128, bf16x2_to_f16x2(badd2(prev[x + 1], a)));
    }
    begin(cur);
  }
};

__global__ void __launch_bounds__(512, 1)
davit_window_attn_kernel(const __grid_constant__ CUtensorMap tm1, const __grid_constant__ CUtensorMap tm7c,
                         const __grid_constant__ CUtensorMap tm7, const __grid_constant__ CUtensorMap tmo,
                         const __grid_constant__ CUtensorMap tmw, const __grid_constant__ CUtensorMap tmwo,
                         const __nv_bfloat16* __restrict__ dw, const __nv_bfloat16* __restrict__ x_raw,
                         const __nv_bfloat16* __restrict__ wqkv_raw, const __nv_bfloat16* __restrict__ wo_raw,
                         __nv_bfloat16* __restrict__ out, Scratch* __restrict__ scr, uint32_t per_cta, uint32_t fewer) {
  extern __shared__ __align__(1024) uint8_t smem_raw[];
  const uint32_t sb = (uint32_t)__cvta_generic_to_shared(smem_raw);
  const uint32_t tail = sb + OFF_TAIL;
  uint32_t wt[9];
  {
    const uint32_t tid = threadIdx.x;
    const uint32_t wid = __shfl_sync(0xffffffffu, tid >> 5, 0), lane = tid & 31;
    if (wid > 12) {
      const uint32_t chunk = wid - 13, hbar = tail + T_HALO + 16 * chunk, rbar = tail + T_ROW + 16 * chunk;
      if (lane == 0) {
        mbar_init(hbar, 1);
        mbar_init(hbar + 8, 1);
        mbar_init(rbar, 1);
        mbar_init(rbar + 8, 1);
        if (wid == 13) mbar_init(tail + T_RAW, 1);
        fence_async();
      }
      __syncwarp();
      if (blockIdx.x < kUnits) {
        if (wid == 13 && lane == 0) request_unit(blockIdx.x, sb + OFF_RING, tail + T_RAW, &tmw, &tmwo);
        asm volatile("bar.sync 5, 96;" ::: "memory");
      }
      uint32_t first, count;
      cta_windows(per_cta, fewer, first, count);
      const int x = (int)(first / kWinPerCol) * 7 - 1, y = (int)(first % kWinPerCol) * 7;
      const uint32_t halo = sb + OFF_HALO + chunk * 2 * HALO_ROW;
      load_rows<HALO_ROW>(halo, &tm1, chunk * 64, x, y - 1, hbar);
      load_rows<HALO_ROW>(halo + HALO_ROW, &tm1, chunk * 64, x, y, hbar + 8);
      load_rows<7 * HALO_ROW>(sb + OFF_KV + chunk * 7 * HALO_ROW, &tm7c, chunk * 64, x, y + 1, rbar);
#pragma unroll
      for (int i = 0; i < 9; i++) wt[i] = __ldg(reinterpret_cast<const uint32_t*>(dw) + i * (kCh / 2) + chunk * 32 + lane);
    } else {
      if (lane == 0) {
        if (wid < 12) {
          const uint32_t i = 2 * wid, counts = (uint32_t)((wid < 8 ? 0x4144444333CCC111ull >> (8 * wid) : 0x11444144u >> (8 * wid - 64)));
          mbar_init(tail + 8 * (i < 11 ? i : i + 6), counts & 15);
          if (wid < 11)
          mbar_init(tail + 8 * (i < 10 ? i + 1 : i + 7), (counts >> 4) & 15);
          fence_async();
        }
      }
      if (wid == 12) {
        for (uint32_t line = blockIdx.x + gridDim.x * lane; line < 2304; line += gridDim.x * 32) {
          const uint8_t* p = (line < 1728) ? reinterpret_cast<const uint8_t*>(wqkv_raw) + line * 128
                                           : reinterpret_cast<const uint8_t*>(wo_raw) + (line - 1728) * 128;
          asm volatile("prefetch.global.L2 [%0];" ::"l"(p));
        }
        if (lane < 7) sts32(tail + T_ZERO + 4 * lane, 0u);
      }
    }
    __syncthreads();
  }

  if (threadIdx.x >= 384) {
    asm volatile("setmaxnreg.dec.sync.aligned.u32 %0;" ::"n"(56));
    const uint32_t tid = fresh_tid();
    const uint32_t warp = __shfl_sync(0xffffffffu, (tid >> 5) & 3, 0), lane = tid & 31;
    uint32_t first, count;
    cta_windows(per_cta, fewer, first, count);
    if (warp == 0) {
      if (lane == 0) {
        uint32_t spins = 0, seen;
        while (true) {
          asm volatile("ld.acquire.gpu.global.u32 %0, [%1];" : "=r"(seen) : "l"(&scr->ready) : "memory");
          if ((seen & 31) == kUnits) break;
          if (++spins > (1u << 22)) __trap();
        }
        asm volatile("fence.proxy.async.global;" ::: "memory");
        const uint8_t* w = scr->weights;
        {
          const int e0 = (int)((seen >> 10) & 511) - 128, e1 = (int)(seen >> 19) - 128;
          sts32(tail + T_SCALE, pack_f16(fmaxf(0.20823509f * pow2(9 - e0), 0x1p-24f), fmaxf(0.20823509f * pow2(9 - e1), 0x1p-24f)));
          if ((seen & 0x3E0u) || e0 < 1 || e1 < 1) sts32(tail + T_ALL, 1u);
        }
#pragma unroll
        for (uint32_t s = 0; s < 3; s++) {
          mbar_expect_tx(tail + T_FULL + 8 * s, W_PART);
          bulk_load(sb + OFF_RING + s * W_PART, w + s * W_PART, W_PART, tail + T_FULL + 8 * s);
        }
#pragma unroll 1
        for (uint32_t v = first + 1; v < first + 4 && v < first + count; v++) {
          const int x = (int)(v / kWinPerCol) * 7 - 1, y = (int)(v % kWinPerCol) * 7;
          if (v > first + 1 || y == 0) prefetch_box(&tm7, x, y + 1);
          if (y == 0) prefetch_box(&tm7, x, -1);
        }
        if (atomicInc(&scr->passed, gridDim.x - 1) == gridDim.x - 1) scr->ready = 0;
        const uint32_t uses = 8 * ((count + 2) / 3);
        uint32_t s = 0, parity = 0;
#pragma unroll 1
        for (uint32_t u = 3; u < uses; u++) {
          mbar_wait(tail + T_EMPTY + 8 * s, parity);
          mbar_expect_tx(tail + T_FULL + 8 * s, W_PART);
          bulk_load(sb + OFF_RING + s * W_PART, w + (u & 7) * W_PART, W_PART, tail + T_FULL + 8 * s);
          s = (s == 2) ? 0 : s + 1;
          parity ^= (s == 0);
        }
      }
    } else {
      Conv cv;
#pragma unroll
      for (int i = 0; i < 9; i++) cv.wt[i] = wt[i];
      {
        const uint32_t chunk = warp - 1, halo = sb + OFF_HALO + chunk * 2 * HALO_ROW, hbar = tail + T_HALO + 16 * chunk;
        const uint32_t staged = (count > 1 && first % kWinPerCol != kWinPerCol - 1) ? 2 : 1;
        const int x = (int)((first + staged) / kWinPerCol) * 7 - 1, y = (int)((first + staged) % kWinPerCol) * 7;
        cv.start_column(halo, hbar, 0, halo + HALO_ROW, hbar + 8, 0, lane, tail + T_DUMP, staged < count, &tm1, chunk * 64, x, y ? y + 1 : -1);
        if (staged == 2)
          load_rows<7 * HALO_ROW>(sb + OFF_KV + (3 + chunk) * 7 * HALO_ROW, &tm7c, chunk * 64, (int)(first / kWinPerCol) * 7 - 1,
                                  (int)(first % kWinPerCol) * 7 + 8, tail + T_ROW + 16 * chunk + 8);
#pragma unroll 1
        for (uint32_t i = 0; i < staged; i++) {
          mbar_wait(tail + T_ROW + 16 * chunk + 8 * i, 0);
#pragma unroll 1
          for (uint32_t r = 0; r < 7; r++)
            cv.row_at(sb + OFF_KV + ((3 * i + chunk) * 7 + r) * HALO_ROW + lane * 4,
                      sb + OFF_X0 + chunk * X0_CHUNK + lane * 4 + (7 * i + r) * X0_ROW, 7 * r);
          __syncwarp();
          arrive_elected(tail + T_X0FULL + 8 * i);
        }
      }
      const uint32_t chunk = __shfl_sync(0xffffffffu, (fresh_tid() >> 5) & 3, 0) - 1, ch = chunk * 64;
      const uint32_t halo = sb + OFF_HALO + chunk * 2 * HALO_ROW, hbar = tail + T_HALO + 16 * chunk;
      const uint32_t src = halo + lane * 4, dst = sb + OFF_X0 + chunk * X0_CHUNK + lane * 4;
      cta_windows(per_cta, fewer, first, count);
      const uint32_t staged = (count > 1 && first % kWinPerCol != kWinPerCol - 1) ? 2 : 1;
      const uint32_t before = (first + staged - 1) / kWinPerCol;
#pragma unroll 1
      for (uint32_t j = staged; j < count; j++) {
        const uint32_t wx = (first + j) / kWinPerCol;
        int x = (int)wx * 7 - 1, y = (int)(7 * (first + j) - kImg * wx);
        const uint32_t n = 2 + 7 * (j - staged) + 2 * (wx - before);
        uint32_t at = 7 * j % kRows * X0_ROW;
        const uint32_t slot[2] = {(n & 1) * HALO_ROW, HALO_ROW - (n & 1) * HALO_ROW}, bar[2] = {hbar + 8 * (n & 1), hbar + 8 - 8 * (n & 1)};
        const uint32_t parity[2] = {(n >> 1) & 1, ((n + 1) >> 1) & 1};
        if (y == 0)
          cv.start_column(halo + slot[0], bar[0], parity[0] ^ 1, halo + slot[1], bar[1], parity[1] ^ 1, lane, tail + T_DUMP, true, &tm1, ch, x, 1);
        const bool more = j + 1 < count;
        const bool fresh = y == kImg - 7;
        if (chunk == 0 && j + 2 < count) {
          if (y >= kImg - 14) {
            prefetch_rows(&tm7, x + 7, fresh ? 8 : -1);
            if (!fresh) prefetch_rows(&tm7, x + 7, 1);
          } else {
            prefetch_rows(&tm7, x, y + 15);
          }
        }
        auto step = [&](auto r) {
          constexpr int R = decltype(r)::value;
          if (R == kRows - 14) {
            mbar_wait(tail + T_X0FREE + 8 * (j & 1), ((j >> 1) & 1) ^ 1);
            x = fresh ? x + 7 : x;
            y = fresh ? -9 : y;
          }
          mbar_wait(bar[R & 1], parity[R & 1] ^ ((R >> 1) & 1));
          cv.template row<R>(src + slot[R & 1], dst, at);
          if (R < 5 || more) load_rows<HALO_ROW>(halo + slot[R & 1], &tm1, ch, x, y + R + 3, bar[R & 1]);
          at = (at == (kRows - 1) * X0_ROW) ? 0 : at + X0_ROW;
        };
        static_assert(kRows - 14 == 5, "ring of x0 rows");
        step(Int<0>()); step(Int<1>()); step(Int<2>()); step(Int<3>()); step(Int<4>()); step(Int<5>()); step(Int<6>());
        __syncwarp();
        arrive_elected(tail + T_X0FULL + 8 * (j % 3));
      }
    }
    __syncwarp();
    asm volatile("bar.sync 0, 512;" ::: "memory");
  } else {
    asm volatile("setmaxnreg.inc.sync.aligned.u32 %0;" ::"n"(152));
    const uint32_t wid = __shfl_sync(0xffffffffu, fresh_tid() >> 5, 0);
    const uint32_t wg = wid >> 2, warp = wid & 3;
    uint32_t lane;
    asm volatile("mov.u32 %0, %%laneid;" : "=r"(lane));
#pragma unroll 1
    for (uint32_t u = blockIdx.x, i = 0; u < kUnits; u += gridDim.x, i++) {
      if (i) {
        asm volatile("bar.sync 4, 384;" ::: "memory");
        if (wid == 0 && lane == 0) request_unit(u, sb + OFF_RING, tail + T_RAW, &tmw, &tmwo);
      }
      mbar_wait(tail + T_RAW, i & 1);
      prepare_unit(u, wid, lane, sb + OFF_RING, scr);
    }
    uint32_t first, count;
    cta_windows(per_cta, fewer, first, count);
    const uint32_t q = lane & 3, mat = lane >> 3, row = lane & 7;
    const uint32_t area = sb + OFF_KV + wg * KV_SIZE, stage = (area + 127) & ~127u;
    const uint32_t bars = tail + T_WG + 32 * wg;
    const bool full = warp < 3;
    const bool valid = full || lane < 4;
    const bool lead = lane == 0;
    uint32_t k_st, v_st, x_ld, x_mask, x_row, o_st;
    {
      const uint32_t rowg = full ? 2 * warp + (mat & 1) : 6, colg = full ? (mat >> 1) : (mat & 1);
      k_st = full ? area + A_K0 + colg * K_CHUNK + rowg * 128 + row * 16 : area + A_K0 + 768 + q * 4;
      v_st = area + A_V0 + colg * 896 + rowg * 128 + row * 16;
      const uint32_t t = 16 * warp + row + 8 * (mat & 1);
      x_ld = (t < 49) ? sb + OFF_X0 + t * 128 + (((mat >> 1) ^ row) << 4) : tail + T_ZERO;
      x_mask = (t < 49) ? ~0u : 0u;
      x_row = t / 7;
      const uint32_t a = stage + (full ? t : 48) * 64;
      o_st = a + (((full ? (mat >> 1) : 0) ^ ((a >> 7) & 3)) << 4) + (full ? 0 : 4 * q);
    }
    const uint32_t keep = q ? 0u : 0xFFFFu;
    const uint32_t pad = (valid ? 0u : 0xFC00u) | (full ? 0u : 0xFC000000u);
    const uint64_t k_desc = make_desc(area + A_K0, K_CHUNK, 128);
    const uint64_t v_desc = make_desc(area + A_V0, 128, 896);
    const uint64_t w_desc = make_desc(sb + OFF_RING, 128, 256);
    if (wg == 2) asm volatile("bar.arrive 8, 256;" ::: "memory");
    if (wg < count) {
      mbar_wait(tail + T_X0FULL + 8 * wg, 0);
      if (warp < 2 && lane < 28) {
        sts64(area + A_ONES + (28 * warp + lane) * 16, 0x3C003C00u, 0x3C003C00u);
        sts64(area + A_ONES + (28 * warp + lane) * 16 + 8, 0x3C003C00u, 0x3C003C00u);
      }
      __syncwarp();
    }
    mbar_wait(tail + T_FULL, 0);
    const uint32_t scales = lds32(tail + T_SCALE);
    uint32_t round = 0;
#pragma unroll 1
    for (; 3 * round + wg < count; round++) {
      const uint32_t r = __shfl_sync(0xffffffffu, round, 0), j = 3 * r + wg, ph = r & 1;
      const uint32_t m = 8 * r / 3, rot = 8 * r - 3 * m;
      const uint32_t ra = 8 * rot, rb = (rot == 2) ? 0 : ra + 8, rc = (rot == 0) ? 16 : ra - 8;
      const uint32_t pa = m & 1, pb = pa ^ (rot == 2), pc = pa ^ (rot != 0);
      uint32_t x[48], ka[24], va[24], oa[24], ob[24], rr;
      uint32_t (&qa)[24] = ka;
      uint32_t sc0[14], sc1[14], pa0[14], pa1[14], ov0[14], ov1[14];
      mbar_wait(tail + T_X0FULL + 8 * wg, ph);
      {
        asm volatile("" : "+r"(x_mask));
        const uint32_t at = 7 * j % kRows;
        const uint32_t a = x_ld + ((at * X0_ROW - (x_row >= kRows - at ? X0_CHUNK : 0)) & x_mask);
#pragma unroll
        for (int s = 0; s < 12; s++)
          ldsm4((a ^ (((s & 3) << 5) & x_mask)) + ((s >> 2) * X0_CHUNK & x_mask), x[4 * s], x[4 * s + 1], x[4 * s + 2], x[4 * s + 3]);
      }
      uint32_t lane_sums[2];
      lane_stats_packed(x, lane_sums);
      fence_regs(lane_sums);
      warp_arrive(tail + T_X0FREE + 8 * (j & 1), lead);
#pragma unroll
      for (int p = 0; p < 2; p++) {
        asm volatile("bar.sync %0, 256;" ::"r"(8 + wg) : "memory");
        mbar_wait(tail + T_FULL + ra, pa ^ p);
        wg_fence();
        issue_proj<false>(ka, x, desc_at(w_desc, ra * (W_PART / 8)));
        wg_commit();
        mbar_wait(tail + T_FULL + rb, pb ^ p);
        wg_fence();
        {
          const uint64_t d = desc_at(w_desc, rb * (W_PART / 8));
          issue_half<1>(va, x, d);
          wg_commit();
          wg_wait<1>();
          if (lead) mbar_arrive(tail + T_EMPTY + ra);
          __syncwarp();
          issue_half<0>(va, x, d);
          wg_commit();
        }
        asm volatile("bar.arrive %0, 256;" ::"r"(wg == 2 ? 8 : 9 + wg) : "memory");
        if (p == 0) {
          const bool odd = q & 1;
          const uint32_t packed = quad_stats_packed(lane_sums, odd);
          float sum = h_lo(packed), squares = h_hi(packed);
          const bool fine = (squares >= 0.1875f || (pad & (odd ? 0xFC000000u : 0xFC00u))) & (squares <= 65504.f) & (sum * sum <= 96.f * squares);
          const bool exact = !__all_sync(0xffffffffu, fine);
          if (exact) {
            wg_wait<0>();
            row_stats(x, odd, sum, squares);
          }
          const float mean = sum * (1.f / 192.f);
          const float rs = 16.f * rsqrt_fast(fmaxf(fmaf(squares, 1.f / 192.f, -mean * mean), 0.f) + 1e-5f);
          if (exact) {
            const uint32_t range = __reduce_max_sync(0xffffffffu, __float_as_uint(squares * fmaxf(rs * rs, 1.f)));
            if ((range > 0x4D400000u || (range != 0u && range < 0x4585A800u)) && lead) {
              scr->redo[first + j] = 1;
              sts32(tail + T_ANY, 1u);
            }
          }
          const float o = __shfl_xor_sync(0xffffffffu, rs, 1);
          rr = pack_f16(odd ? o : rs, odd ? rs : o);
          if (!full && lead) {
            asm volatile("cp.async.bulk.wait_group.read 0;" ::: "memory");
            mbar_arrive(bars + B_OUTFREE);
          }
          __syncwarp();
          mbar_wait(bars + B_OUTFREE, ph);
        } else {
          mbar_wait(bars + B_KVFREE, 0);
        }
        fence_regs(ka);
        store_k(ka, k_st, full, lane < 4, rr);
        mbar_wait(tail + T_FULL + rc, pc ^ p);
        wg_fence();
        {
          const uint64_t d = desc_at(w_desc, rc * (W_PART / 8));
          issue_half<2>(qa, x, d);
          wg_commit();
          wg_wait<1>();
          if (lead) mbar_arrive(tail + T_EMPTY + rb);
          __syncwarp();
          issue_half<0>(qa, x, d);
          wg_commit();
        }
        fence_regs(va);
        store_v(va, v_st, full, rr);
        fence_async();
        warp_arrive(bars + B_KVRDY, lead);
        wg_wait<0>();
        fence_regs(qa);
        if (lead) mbar_arrive(tail + T_EMPTY + rc);
        {
          const uint32_t rq = hmul2(rr, 0x18001800u);
#pragma unroll
          for (int i = 0; i < 24; i += 2) {
            qa[i] = hmul2_lo(qa[i], rq);
            qa[i + 1] = hmul2_hi(qa[i + 1], rq);
          }
        }
        mbar_wait(bars + B_KVRDY, p);

        wg_fence();
        issue_s(sc0, &qa[0], desc_at(k_desc, 0));
        wg_commit();
        uint32_t top0, top1;
        if (p == 0) {
          issue_s(sc1, &qa[12], desc_at(k_desc, A_K1));
          wg_commit();
          wg_wait<1>();
          fence_regs(sc0);
          top0 = softmax_max<0>(sc0, keep, scales);
          softmax_exp<0>(sc0, top0, scales, pad, pa0);
          wg_fence();
          issue_pv(ov0, pa0, desc_at(v_desc, 0));
          wg_commit();
          wg_wait<1>();
          fence_regs(sc1);
          top1 = softmax_max<0>(sc1, keep, scales);
          softmax_exp<0>(sc1, top1, scales, pad, pa1);
        } else {
          wg_wait<0>();
          fence_regs(sc0);
          wg_fence();
          issue_s(sc1, &qa[12], desc_at(k_desc, A_K1));
          wg_commit();
          top0 = softmax_max<1>(sc0, keep, scales);
          wg_wait<0>();
          fence_regs(sc1);
          softmax_exp<1>(sc0, top0, scales, pad, pa0);
          mbar_wait(tail + T_FULL + ra, pa);
          wg_fence();
          issue_pv(ov0, pa0, desc_at(v_desc, 0));
          wg_commit();
          issue_out<6>(x, oa, desc_at(w_desc, ra * (W_PART / 8)));
          wg_commit();
          top1 = softmax_max<1>(sc1, keep, scales);
          wg_wait<1>();
          fence_regs(ov0);
          softmax_exp<1>(sc1, top1, scales, pad, pa1);
        }
        wg_fence();
        issue_pv(ov1, pa1, desc_at(v_desc, A_ONES - A_V0));
        wg_commit();
        wg_wait<1>();
        if (p == 0) fence_regs(ov0);
        else if (lead) mbar_arrive(tail + T_EMPTY + ra);
        {
          uint32_t big;
          asm("{\n.reg .pred p, q;\n.reg .b32 t;\nmax.xorsign.abs.f16x2 t, %1, %2;\nabs.f16x2 t, t;\nsetp.gt.f16x2 p|q, t, %3;\n"
              "or.pred p, p, q;\nselp.u32 %0, 1, 0, p;\n}" : "=r"(big) : "r"(top0), "r"(top1), "r"(0x60006000u));
          if (__any_sync(0xffffffffu, big) && lead) {
            scr->redo[first + j] = 1;
            sts32(tail + T_ANY, 1u);
          }
          __syncwarp();
        }
        uint32_t (&o)[24] = (p == 0) ? oa : ob;
        pack_o<12, 0>(ov0, &o[0]);
        if (p == 1) {
          mbar_wait(tail + T_FULL + rb, pb);
          wg_fence();
          issue_out<3>(x, &ob[0], desc_at(w_desc, rb * (W_PART / 8)));
          wg_commit();
          wg_wait<1>();
        } else {
          wg_wait<0>();
        }
        fence_regs(ov1);
        if (lead) mbar_arrive(bars + B_KVFREE);
        pack_o<0, 2>(ov1, &o[12]);
      }
      wg_fence();
      issue_out<3>(x, &ob[12], desc_at(w_desc, rb * (W_PART / 8) + 3 * WO_STEP));
      wg_commit();
      mbar_wait(bars + B_KVFREE, 1);
      wg_wait<0>();
      fence_regs(x);
      if (lead) mbar_arrive(tail + T_EMPTY + rb);
      asm volatile("" : "+r"(o_st));
      if (full) {
#pragma unroll
        for (int s = 0; s < 12; s++)
          stsm4((o_st ^ (((s & 1) ^ out_flip(s >> 1)) << 5)) + out_group(s >> 1), f16x2_to_bf16x2(x[4 * s]), f16x2_to_bf16x2(x[4 * s + 1]),
                f16x2_to_bf16x2(x[4 * s + 2]), f16x2_to_bf16x2(x[4 * s + 3]));
        fence_async();
        warp_arrive(bars + B_OUTRDY, lead);
      } else {
#pragma unroll
        for (int i = 0; i < 24; i++)
          sts32_if(lane < 4, (o_st ^ (((i & 3) ^ (out_flip(i >> 2) << 1)) << 4)) + out_group(i >> 2), f16x2_to_bf16x2(x[2 * i]));
        fence_async();
        warp_arrive(bars + B_OUTRDY, lead);
        if (lead) {
          const uint32_t wx = ((first + j) * 14365u) >> 20;
          mbar_wait(bars + B_OUTRDY, ph);
#pragma unroll
          for (int i = 0; i < 6; i++) store_group(&tmo, stage + out_group(i), 32 * i, 7 * wx, 7 * (first + j) - kImg * wx);
          asm volatile("cp.async.bulk.commit_group;" ::: "memory");
        }
        __syncwarp();
      }
    }
    if (3 * round < count) {
#pragma unroll 1
      for (uint32_t i = 0; i < 5; i++) {
        if (i % 3 == 0) {
          asm volatile("bar.sync %0, 256;" ::"r"(8 + wg) : "memory");
          asm volatile("bar.arrive %0, 256;" ::"r"(wg == 2 ? 8 : 9 + wg) : "memory");
        }
        const uint32_t u = 8 * round + i;
        mbar_wait(tail + T_FULL + 8 * (u % 3), (u / 3) & 1);
        if (lead) mbar_arrive(tail + T_EMPTY + 8 * (u % 3));
        __syncwarp();
      }
    }
    if (!full && lead) asm volatile("cp.async.bulk.wait_group 0;\nfence.proxy.async.global;" ::: "memory");
    __syncwarp();
    asm volatile("bar.sync 0, 512;" ::: "memory");
    const uint32_t redo_all = lds32(tail + T_ALL);
    if (redo_all | lds32(tail + T_ANY)) {
      const uint32_t t = fresh_tid(), c = t >> 7;
      cta_windows(per_cta, fewer, first, count);
      for (uint32_t v = first + c; v < first + count; v += 3) {
        if (!redo_all && !*reinterpret_cast<volatile uint8_t*>(&scr->redo[v])) continue;
        redo_window(v, t & 127, 1 + c, smem_raw + c * REDO_BYTES, x_raw, dw, wqkv_raw, wo_raw, out);
        if ((t & 127) == 0) scr->redo[v] = 0;
      }
    }
  }
}

typedef CUresult (*EncodeTiledFn)(CUtensorMap*, CUtensorMapDataType, cuuint32_t, void*, const cuuint64_t*, const cuuint64_t*,
                                  const cuuint32_t*, const cuuint32_t*, CUtensorMapInterleave, CUtensorMapSwizzle,
                                  CUtensorMapL2promotion, CUtensorMapFloatOOBfill);

}

extern "C" void kernel_launch(void* const* d_in, const int* in_sizes, int n_in, void* d_out, int out_size) {
  (void)in_sizes; (void)n_in; (void)out_size;
  static EncodeTiledFn encode = nullptr;
  static int grid = 0;
  static void* scratch = nullptr;
  if (!encode) {
    void* fn = nullptr;
    cudaDriverEntryPointQueryResult st;
    cudaGetDriverEntryPoint("cuTensorMapEncodeTiled", &fn, cudaEnableDefault, &st);
    encode = (EncodeTiledFn)fn;
    cudaFuncSetAttribute(davit_window_attn_kernel, cudaFuncAttributeMaxDynamicSharedMemorySize, SMEM_BYTES);
    cudaGetSymbolAddress(&scratch, g_scratch);
    int dev = 0;
    cudaGetDevice(&dev);
    cudaDeviceGetAttribute(&grid, cudaDevAttrMultiProcessorCount, dev);
  }
  auto image_map = [&](void* base, cuuint32_t c, cuuint32_t w, cuuint32_t h, CUtensorMapSwizzle swizzle) {
    CUtensorMap tm;
    const cuuint64_t dims[3] = {(cuuint64_t)kCh, (cuuint64_t)kImg, (cuuint64_t)kImg};
    const cuuint64_t strides[2] = {(cuuint64_t)kCh * 2, (cuuint64_t)kCh * 2 * kImg};
    const cuuint32_t box[3] = {c, w, h};
    const cuuint32_t estr[3] = {1, 1, 1};
    encode(&tm, CU_TENSOR_MAP_DATA_TYPE_BFLOAT16, 3, base, dims, strides, box, estr, CU_TENSOR_MAP_INTERLEAVE_NONE, swizzle,
           CU_TENSOR_MAP_L2_PROMOTION_L2_128B, CU_TENSOR_MAP_FLOAT_OOB_FILL_NONE);
    return tm;
  };
  auto weight_map = [&](void* base, cuuint64_t cols, cuuint32_t rows) {
    CUtensorMap tm;
    const cuuint64_t dims[2] = {cols, (cuuint64_t)kCh};
    const cuuint64_t strides[1] = {cols * 2};
    const cuuint32_t box[2] = {32, rows};
    const cuuint32_t estr[2] = {1, 1};
    encode(&tm, CU_TENSOR_MAP_DATA_TYPE_BFLOAT16, 2, base, dims, strides, box, estr, CU_TENSOR_MAP_INTERLEAVE_NONE,
           CU_TENSOR_MAP_SWIZZLE_64B, CU_TENSOR_MAP_L2_PROMOTION_L2_128B, CU_TENSOR_MAP_FLOAT_OOB_FILL_NONE);
    return tm;
  };
  davit_window_attn_kernel<<<grid, 512, SMEM_BYTES, cudaStreamPerThread>>>(
      image_map(d_in[0], 64, 9, 1, CU_TENSOR_MAP_SWIZZLE_NONE), image_map(d_in[0], 64, 9, 7, CU_TENSOR_MAP_SWIZZLE_NONE),
      image_map(d_in[0], 192, 9, 7, CU_TENSOR_MAP_SWIZZLE_NONE), image_map(d_out, 32, 7, 7, CU_TENSOR_MAP_SWIZZLE_64B),
      weight_map(d_in[2], 576, 192), weight_map(d_in[3], 192, 32),
      (const __nv_bfloat16*)d_in[1], (const __nv_bfloat16*)d_in[0], (const __nv_bfloat16*)d_in[2], (const __nv_bfloat16*)d_in[3],
      (__nv_bfloat16*)d_out, (Scratch*)scratch, kNumWin / grid, grid - kNumWin % grid);
}
```

```cpp
#include <cuda.h>
#include <cuda_bf16.h>
#include <cuda_runtime.h>
#include <stdint.h>

namespace {

constexpr int kImg = 511;
constexpr int kCh = 192;
constexpr int kWinPerCol = 73;
constexpr int kNumWin = 73 * 73;

constexpr uint32_t W_PART = 36864;
constexpr uint32_t W_STEP = 3072;
constexpr uint32_t WO_STEP = 6144;
constexpr uint32_t W_BYTES = 8 * W_PART;

struct Scratch {
  uint8_t weights[W_BYTES];
  uint32_t ready;
  uint32_t passed;
  uint8_t redo[2 * kNumWin];
};
__device__ __align__(128) Scratch g_scratch;

constexpr uint32_t OFF_RING = 0;
constexpr uint32_t OFF_X0 = 3 * W_PART;
constexpr uint32_t kSlots = 2;
constexpr uint32_t kRows = (2 == 3) ? 17 : 19;
constexpr uint32_t X0_ROW = 7 * 128;
constexpr uint32_t X0_CHUNK = kRows * X0_ROW;
constexpr uint32_t OFF_HALO = OFF_X0 + 3 * X0_CHUNK;
constexpr uint32_t HALO_ROW = 9 * 128;
constexpr uint32_t OFF_KV = OFF_HALO + 3 * kSlots * HALO_ROW;
constexpr uint32_t K_CHUNK = 784;
constexpr uint32_t A_K0 = 0;
constexpr uint32_t A_V0 = 6 * K_CHUNK;
constexpr uint32_t A_ONES = A_V0 + 5376;
constexpr uint32_t A_V1 = A_ONES + 896;
constexpr uint32_t A_K1 = A_V1 + 5376;
constexpr uint32_t KV_SIZE = A_K1 + 6 * K_CHUNK;
constexpr uint32_t OUT_GROUP = 3328;
constexpr uint32_t OUT_HALF = 11008;
__host__ __device__ constexpr uint32_t out_group(uint32_t g) { return (g / 3) * OUT_HALF + (g % 3) * OUT_GROUP; }
__host__ __device__ constexpr uint32_t out_flip(uint32_t g) { return (out_group(g) >> 8) & 1; }
static_assert(64 + out_group(2) + 3136 <= A_ONES && out_group(3) >= A_V1 && 64 + out_group(5) + 3136 <= KV_SIZE, "output staging");
constexpr uint32_t OFF_TAIL = OFF_KV + 3 * KV_SIZE;
constexpr uint32_t SMEM_BYTES = OFF_TAIL + 320;
static_assert(SMEM_BYTES <= 232448, "shared memory");

constexpr uint32_t T_FULL = 0;
constexpr uint32_t T_EMPTY = 24;
constexpr uint32_t T_X0FULL = 48;
constexpr uint32_t T_X0FREE = 72;
constexpr uint32_t T_HALO = 88;
constexpr uint32_t T_WG = 136;
constexpr uint32_t B_KVRDY = 0;
constexpr uint32_t B_KVFREE = 8;
constexpr uint32_t B_OUTRDY = 16;
constexpr uint32_t B_OUTFREE = 24;
constexpr uint32_t T_RAW = 232;
constexpr uint32_t T_ZERO = 240;
constexpr uint32_t T_SCALE = 256;
constexpr uint32_t T_ALL = 260;
constexpr uint32_t T_ANY = 264;
constexpr uint32_t T_DUMP = 268;
constexpr uint32_t T_ROW = 272;

__device__ __forceinline__ void hmma_n96_first(uint32_t (&d)[24], uint32_t a0, uint32_t a1, uint32_t a2, uint32_t a3, uint64_t desc) {
  asm volatile("wgmma.mma_async.sync.aligned.m64n96k16.f16.f16.f16 "
               "{%0, %1, %2, %3, %4, %5, %6, %7, %8, %9, %10, %11, %12, %13, %14, %15, "
               "%16, %17, %18, %19, %20, %21, %22, %23}, "
               "{%24, %25, %26, %27}, %28, 0, 1, 1, 0;\n"
               : "=r"(d[0]), "=r"(d[1]), "=r"(d[2]), "=r"(d[3]), "=r"(d[4]), "=r"(d[5]), "=r"(d[6]), "=r"(d[7]),
                 "=r"(d[8]), "=r"(d[9]), "=r"(d[10]), "=r"(d[11]), "=r"(d[12]), "=r"(d[13]), "=r"(d[14]), "=r"(d[15]),
                 "=r"(d[16]), "=r"(d[17]), "=r"(d[18]), "=r"(d[19]), "=r"(d[20]), "=r"(d[21]), "=r"(d[22]), "=r"(d[23])
               : "r"(a0), "r"(a1), "r"(a2), "r"(a3), "l"(desc));
}
__device__ __forceinline__ void hmma_n96(uint32_t (&d)[24], uint32_t a0, uint32_t a1, uint32_t a2, uint32_t a3, uint64_t desc) {
  asm volatile("wgmma.mma_async.sync.aligned.m64n96k16.f16.f16.f16 "
               "{%0, %1, %2, %3, %4, %5, %6, %7, %8, %9, %10, %11, %12, %13, %14, %15, "
               "%16, %17, %18, %19, %20, %21, %22, %23}, "
               "{%24, %25, %26, %27}, %28, 1, 1, 1, 0;\n"
               : "+r"(d[0]), "+r"(d[1]), "+r"(d[2]), "+r"(d[3]), "+r"(d[4]), "+r"(d[5]), "+r"(d[6]), "+r"(d[7]),
                 "+r"(d[8]), "+r"(d[9]), "+r"(d[10]), "+r"(d[11]), "+r"(d[12]), "+r"(d[13]), "+r"(d[14]), "+r"(d[15]),
                 "+r"(d[16]), "+r"(d[17]), "+r"(d[18]), "+r"(d[19]), "+r"(d[20]), "+r"(d[21]), "+r"(d[22]), "+r"(d[23])
               : "r"(a0), "r"(a1), "r"(a2), "r"(a3), "l"(desc));
}
__device__ __forceinline__ void hmma_n96_over(uint32_t (&d)[24], uint32_t a0, uint32_t a1, uint32_t a2, uint32_t a3, uint64_t desc) {
  asm volatile("wgmma.mma_async.sync.aligned.m64n96k16.f16.f16.f16 "
               "{%0, %1, %2, %3, %4, %5, %6, %7, %8, %9, %10, %11, %12, %13, %14, %15, "
               "%16, %17, %18, %19, %20, %21, %22, %23}, "
               "{%24, %25, %26, %27}, %28, 0, 1, 1, 0;\n"
               : "+r"(d[0]), "+r"(d[1]), "+r"(d[2]), "+r"(d[3]), "+r"(d[4]), "+r"(d[5]), "+r"(d[6]), "+r"(d[7]),
                 "+r"(d[8]), "+r"(d[9]), "+r"(d[10]), "+r"(d[11]), "+r"(d[12]), "+r"(d[13]), "+r"(d[14]), "+r"(d[15]),
                 "+r"(d[16]), "+r"(d[17]), "+r"(d[18]), "+r"(d[19]), "+r"(d[20]), "+r"(d[21]), "+r"(d[22]), "+r"(d[23])
               : "r"(a0), "r"(a1), "r"(a2), "r"(a3), "l"(desc));
}
__device__ __forceinline__ void hmma_n56_first(uint32_t (&d)[14], uint32_t a0, uint32_t a1, uint32_t a2, uint32_t a3, uint64_t desc) {
  asm volatile("wgmma.mma_async.sync.aligned.m64n56k16.f16.f16.f16 "
               "{%0, %1, %2, %3, %4, %5, %6, %7, %8, %9, %10, %11, %12, %13}, "
               "{%14, %15, %16, %17}, %18, 0, 1, 1, 0;\n"
               : "=r"(d[0]), "=r"(d[1]), "=r"(d[2]), "=r"(d[3]), "=r"(d[4]), "=r"(d[5]), "=r"(d[6]), "=r"(d[7]),
                 "=r"(d[8]), "=r"(d[9]), "=r"(d[10]), "=r"(d[11]), "=r"(d[12]), "=r"(d[13])
               : "r"(a0), "r"(a1), "r"(a2), "r"(a3), "l"(desc));
}
__device__ __forceinline__ void hmma_n56(uint32_t (&d)[14], uint32_t a0, uint32_t a1, uint32_t a2, uint32_t a3, uint64_t desc) {
  asm volatile("wgmma.mma_async.sync.aligned.m64n56k16.f16.f16.f16 "
               "{%0, %1, %2, %3, %4, %5, %6, %7, %8, %9, %10, %11, %12, %13}, "
               "{%14, %15, %16, %17}, %18, 1, 1, 1, 0;\n"
               : "+r"(d[0]), "+r"(d[1]), "+r"(d[2]), "+r"(d[3]), "+r"(d[4]), "+r"(d[5]), "+r"(d[6]), "+r"(d[7]),
                 "+r"(d[8]), "+r"(d[9]), "+r"(d[10]), "+r"(d[11]), "+r"(d[12]), "+r"(d[13])
               : "r"(a0), "r"(a1), "r"(a2), "r"(a3), "l"(desc));
}
__device__ __forceinline__ void hmma_n192(uint32_t (&d)[48], uint32_t a0, uint32_t a1, uint32_t a2, uint32_t a3, uint64_t desc) {
  asm volatile("wgmma.mma_async.sync.aligned.m64n192k16.f16.f16.f16 "
               "{%0, %1, %2, %3, %4, %5, %6, %7, %8, %9, %10, %11, %12, %13, %14, %15, "
               "%16, %17, %18, %19, %20, %21, %22, %23, %24, %25, %26, %27, %28, %29, %30, %31, "
               "%32, %33, %34, %35, %36, %37, %38, %39, %40, %41, %42, %43, %44, %45, %46, %47}, "
               "{%48, %49, %50, %51}, %52, 1, 1, 1, 0;\n"
               : "+r"(d[0]), "+r"(d[1]), "+r"(d[2]), "+r"(d[3]), "+r"(d[4]), "+r"(d[5]), "+r"(d[6]), "+r"(d[7]),
                 "+r"(d[8]), "+r"(d[9]), "+r"(d[10]), "+r"(d[11]), "+r"(d[12]), "+r"(d[13]), "+r"(d[14]), "+r"(d[15]),
                 "+r"(d[16]), "+r"(d[17]), "+r"(d[18]), "+r"(d[19]), "+r"(d[20]), "+r"(d[21]), "+r"(d[22]), "+r"(d[23]),
                 "+r"(d[24]), "+r"(d[25]), "+r"(d[26]), "+r"(d[27]), "+r"(d[28]), "+r"(d[29]), "+r"(d[30]), "+r"(d[31]),
                 "+r"(d[32]), "+r"(d[33]), "+r"(d[34]), "+r"(d[35]), "+r"(d[36]), "+r"(d[37]), "+r"(d[38]), "+r"(d[39]),
                 "+r"(d[40]), "+r"(d[41]), "+r"(d[42]), "+r"(d[43]), "+r"(d[44]), "+r"(d[45]), "+r"(d[46]), "+r"(d[47])
               : "r"(a0), "r"(a1), "r"(a2), "r"(a3), "l"(desc));
}

__device__ __forceinline__ void wg_fence() { asm volatile("wgmma.fence.sync.aligned;\n" ::: "memory"); }
__device__ __forceinline__ void wg_commit() { asm volatile("wgmma.commit_group.sync.aligned;\n" ::: "memory"); }
template <int N> __device__ __forceinline__ void wg_wait() { asm volatile("wgmma.wait_group.sync.aligned %0;\n" ::"n"(N) : "memory"); }
__device__ __forceinline__ uint64_t make_desc(uint32_t addr, uint32_t lbo, uint32_t sbo) {
  return (uint64_t)((addr & 0x3FFFF) >> 4) | ((uint64_t)(lbo >> 4) << 16) | ((uint64_t)(sbo >> 4) << 32);
}
__device__ __forceinline__ uint64_t desc_add(uint64_t d, uint32_t bytes) { return d + (bytes >> 4); }
__device__ __forceinline__ uint64_t desc_at(uint64_t d, uint32_t bytes) {
  uint64_t r;
  asm volatile("mov.b64 %0, %1;" : "=l"(r) : "l"(d));
  return desc_add(r, bytes);
}

__device__ __forceinline__ void mbar_init(uint32_t bar, uint32_t count) {
  asm volatile("mbarrier.init.shared::cta.b64 [%0], %1;" ::"r"(bar), "r"(count) : "memory");
}
__device__ __forceinline__ void mbar_expect_tx(uint32_t bar, uint32_t bytes) {
  asm volatile("mbarrier.arrive.expect_tx.shared::cta.b64 _, [%0], %1;" ::"r"(bar), "r"(bytes) : "memory");
}
__device__ __forceinline__ void mbar_wait(uint32_t bar, uint32_t parity) {
  asm volatile("{\n.reg .pred p;\n.reg .u32 c;\n"
               "mbarrier.try_wait.parity.shared::cta.b64 p, [%0], %1;\n"
               "@p bra DONE;\n"
               "mov.u32 c, 0;\n"
               "SPIN:\n"
               "mbarrier.try_wait.parity.shared::cta.b64 p, [%0], %1, 4000;\n"
               "@p bra DONE;\n"
               "add.u32 c, c, 1;\n"
               "setp.lt.u32 p, c, 1048576;\n"
               "@!p trap;\n"
               "bra SPIN;\n"
               "DONE:\n}" ::"r"(bar), "r"(parity) : "memory");
}
__device__ __forceinline__ void bar_sync(uint32_t id) { asm volatile("bar.sync %0, 128;" ::"r"(id) : "memory"); }
__device__ __forceinline__ void mbar_arrive(uint32_t bar) { asm volatile("mbarrier.arrive.shared::cta.b64 _, [%0];" ::"r"(bar) : "memory"); }
__device__ __forceinline__ void warp_arrive(uint32_t bar, bool first) {
  __syncwarp();
  if (first) mbar_arrive(bar);
}
__device__ __forceinline__ void arrive_elected(uint32_t bar) {
  asm volatile("{\n.reg .pred p;\nelect.sync _|p, 0xffffffff;\n@p mbarrier.arrive.shared::cta.b64 _, [%0];\n}" ::"r"(bar) : "memory");
}
__device__ __forceinline__ void fence_async() { asm volatile("fence.proxy.async.shared::cta;" ::: "memory"); }
__device__ __forceinline__ uint32_t lds32(uint32_t a) {
  uint32_t v;
  asm volatile("ld.shared.b32 %0, [%1];" : "=r"(v) : "r"(a) : "memory");
  return v;
}
__device__ __forceinline__ void lds64(uint32_t a, uint32_t& v0, uint32_t& v1) {
  asm volatile("ld.shared.v2.b32 {%0, %1}, [%2];" : "=r"(v0), "=r"(v1) : "r"(a) : "memory");
}
__device__ __forceinline__ void sts32(uint32_t a, uint32_t v) { asm volatile("st.shared.b32 [%0], %1;" ::"r"(a), "r"(v) : "memory"); }
__device__ __forceinline__ void sts64(uint32_t a, uint32_t v0, uint32_t v1) {
  asm volatile("st.shared.v2.b32 [%0], {%1, %2};" ::"r"(a), "r"(v0), "r"(v1) : "memory");
}
__device__ __forceinline__ void sts32_if(bool on, uint32_t a, uint32_t v) {
  asm volatile("{\n.reg .pred p;\nsetp.ne.u32 p, %2, 0;\n@p st.shared.b32 [%0], %1;\n}" ::"r"(a), "r"(v), "r"((uint32_t)on) : "memory");
}
__device__ __forceinline__ void ldsm4(uint32_t a, uint32_t& r0, uint32_t& r1, uint32_t& r2, uint32_t& r3) {
  asm volatile("ldmatrix.sync.aligned.m8n8.x4.shared.b16 {%0, %1, %2, %3}, [%4];" : "=r"(r0), "=r"(r1), "=r"(r2), "=r"(r3) : "r"(a) : "memory");
}
__device__ __forceinline__ void stsm4(uint32_t a, uint32_t r0, uint32_t r1, uint32_t r2, uint32_t r3) {
  asm volatile("stmatrix.sync.aligned.m8n8.x4.shared.b16 [%0], {%1, %2, %3, %4};" ::"r"(a), "r"(r0), "r"(r1), "r"(r2), "r"(r3) : "memory");
}
__device__ __forceinline__ void stsm4_t(uint32_t a, uint32_t r0, uint32_t r1, uint32_t r2, uint32_t r3) {
  asm volatile("stmatrix.sync.aligned.m8n8.x4.trans.shared.b16 [%0], {%1, %2, %3, %4};" ::"r"(a), "r"(r0), "r"(r1), "r"(r2), "r"(r3) : "memory");
}
__device__ __forceinline__ uint32_t pack_bf16(float lo, float hi) {
  uint32_t r;
  asm("cvt.rn.bf16x2.f32 %0, %1, %2;" : "=r"(r) : "f"(hi), "f"(lo));
  return r;
}
__device__ __forceinline__ uint32_t pack_f16(float lo, float hi) {
  uint32_t r;
  asm("cvt.rn.f16x2.f32 %0, %1, %2;" : "=r"(r) : "f"(hi), "f"(lo));
  return r;
}
__device__ __forceinline__ float bf_lo(uint32_t v) { return __uint_as_float(v << 16); }
__device__ __forceinline__ float bf_hi(uint32_t v) { return __uint_as_float(v & 0xffff0000u); }
__device__ __forceinline__ float h_lo(uint32_t v) {
  float r;
  asm("{\n.reg .b16 l, h;\nmov.b32 {l, h}, %1;\ncvt.f32.f16 %0, l;\n}" : "=f"(r) : "r"(v));
  return r;
}
__device__ __forceinline__ float h_hi(uint32_t v) {
  float r;
  asm("{\n.reg .b16 l, h;\nmov.b32 {l, h}, %1;\ncvt.f32.f16 %0, h;\n}" : "=f"(r) : "r"(v));
  return r;
}
__device__ __forceinline__ uint32_t bf16x2_to_f16x2(uint32_t v) { return pack_f16(bf_lo(v), bf_hi(v)); }
__device__ __forceinline__ uint32_t f16x2_to_bf16x2(uint32_t v) { return pack_bf16(h_lo(v), h_hi(v)); }
__device__ __forceinline__ uint32_t bmul2(uint32_t a, uint32_t b) {
  uint32_t r;
  asm("mul.rn.bf16x2 %0, %1, %2;" : "=r"(r) : "r"(a), "r"(b));
  return r;
}
__device__ __forceinline__ uint32_t badd2(uint32_t a, uint32_t b) {
  uint32_t r;
  asm("add.rn.bf16x2 %0, %1, %2;" : "=r"(r) : "r"(a), "r"(b));
  return r;
}
__device__ __forceinline__ uint32_t bfma2(uint32_t a, uint32_t b, uint32_t c) {
  uint32_t r;
  asm("fma.rn.bf16x2 %0, %1, %2, %3;" : "=r"(r) : "r"(a), "r"(b), "r"(c));
  return r;
}
__device__ __forceinline__ uint32_t hadd2(uint32_t a, uint32_t b) {
  uint32_t d;
  asm("add.rn.f16x2 %0, %1, %2;" : "=r"(d) : "r"(a), "r"(b));
  return d;
}
__device__ __forceinline__ uint32_t hmax2(uint32_t a, uint32_t b) {
  uint32_t d;
  asm("max.f16x2 %0, %1, %2;" : "=r"(d) : "r"(a), "r"(b));
  return d;
}
__device__ __forceinline__ uint32_t hmul2(uint32_t a, uint32_t b) {
  uint32_t d;
  asm("mul.rn.f16x2 %0, %1, %2;" : "=r"(d) : "r"(a), "r"(b));
  return d;
}
__device__ __forceinline__ uint32_t hmul2_lo(uint32_t a, uint32_t r) {
  uint32_t d;
  asm("{\n.reg .b16 l, h;\n.reg .b32 t;\nmov.b32 {l, h}, %2;\nmov.b32 t, {l, l};\nmul.rn.f16x2 %0, %1, t;\n}" : "=r"(d) : "r"(a), "r"(r));
  return d;
}
__device__ __forceinline__ uint32_t hmul2_hi(uint32_t a, uint32_t r) {
  uint32_t d;
  asm("{\n.reg .b16 l, h;\n.reg .b32 t;\nmov.b32 {l, h}, %2;\nmov.b32 t, {h, h};\nmul.rn.f16x2 %0, %1, t;\n}" : "=r"(d) : "r"(a), "r"(r));
  return d;
}
__device__ __forceinline__ float rcp(float x) {
  float r;
  asm("rcp.approx.ftz.f32 %0, %1;" : "=f"(r) : "f"(x));
  return r;
}
__device__ __forceinline__ float rsqrt_fast(float x) {
  float r;
  asm("rsqrt.approx.ftz.f32 %0, %1;" : "=f"(r) : "f"(x));
  return r;
}
template <int N> __device__ __forceinline__ void fence_regs(uint32_t (&d)[N]) {
#pragma unroll
  for (int i = 0; i < N; i++) asm volatile("" : "+r"(d[i])::"memory");
}

__device__ __forceinline__ void row_stats(const uint32_t (&x)[48], bool odd, float& sum, float& squares) {
  float s0 = 0.f, q0 = 0.f, s1 = 0.f, q1 = 0.f;
#pragma unroll
  for (int i = 0; i < 48; i++) {
    const float lo = h_lo(x[i]), hi = h_hi(x[i]);
    if (i & 1) {
      s1 += lo; q1 = fmaf(lo, lo, q1);
      s1 += hi; q1 = fmaf(hi, hi, q1);
    } else {
      s0 += lo; q0 = fmaf(lo, lo, q0);
      s0 += hi; q0 = fmaf(hi, hi, q0);
    }
  }
  sum = (odd ? s1 : s0) + __shfl_xor_sync(0xffffffffu, odd ? s0 : s1, 1);
  squares = (odd ? q1 : q0) + __shfl_xor_sync(0xffffffffu, odd ? q0 : q1, 1);
  sum += __shfl_xor_sync(0xffffffffu, sum, 2);
  squares += __shfl_xor_sync(0xffffffffu, squares, 2);
}
__device__ __forceinline__ void lane_stats_packed(const uint32_t (&x)[48], uint32_t (&t)[2]) {
  uint32_t s[4] = {x[0], x[1], x[2], x[3]}, q[4];
#pragma unroll
  for (int r = 0; r < 4; r++) q[r] = hmul2(x[r], x[r]);
#pragma unroll
  for (int i = 4; i < 48; i++) {
    asm("add.rn.f16x2 %0, %0, %1;" : "+r"(s[i & 3]) : "r"(x[i]));
    asm("fma.rn.f16x2 %0, %1, %1, %0;" : "+r"(q[i & 3]) : "r"(x[i]));
  }
#pragma unroll
  for (int r = 0; r < 2; r++) {
    const uint32_t a = hadd2(s[r], s[r + 2]), b = hadd2(q[r], q[r + 2]);
    t[r] = hadd2(__byte_perm(a, b, 0x5410), __byte_perm(a, b, 0x7632));
  }
}
__device__ __forceinline__ uint32_t quad_stats_packed(const uint32_t (&t)[2], bool odd) {
  const uint32_t u = hadd2(__shfl_xor_sync(0xffffffffu, odd ? t[0] : t[1], 1), odd ? t[1] : t[0]);
  return hadd2(u, __shfl_xor_sync(0xffffffffu, u, 2));
}

__device__ __forceinline__ void store_k(const uint32_t (&k)[24], uint32_t k_st, bool full, bool first_row, uint32_t r) {
  if (full) {
#pragma unroll
    for (int j = 0; j < 12; j += 2)
      stsm4(k_st + (j / 6) * A_K1 + (j % 6) * K_CHUNK, hmul2_lo(k[2 * j], r), hmul2_hi(k[2 * j + 1], r), hmul2_lo(k[2 * j + 2], r),
            hmul2_hi(k[2 * j + 3], r));
  } else {
#pragma unroll
    for (int j = 0; j < 12; j++) sts32_if(first_row, k_st + (j / 6) * A_K1 + (j % 6) * K_CHUNK, hmul2_lo(k[2 * j], r));
    __syncwarp();
  }
}
template <int HALF> __device__ __forceinline__ uint32_t both(uint32_t v) {
  uint32_t d;
  if (HALF == 0) asm("{\n.reg .b16 l, h;\nmov.b32 {l, h}, %1;\nmov.b32 %0, {l, l};\n}" : "=r"(d) : "r"(v));
  else asm("{\n.reg .b16 l, h;\nmov.b32 {l, h}, %1;\nmov.b32 %0, {h, h};\n}" : "=r"(d) : "r"(v));
  return d;
}
__device__ __forceinline__ uint32_t exp2_scaled(uint32_t s, uint32_t c, uint32_t off) {
  uint32_t d;
  asm("{\n.reg .b32 t;\nfma.rn.f16x2 t, %1, %2, %3;\nex2.approx.f16x2 %0, t;\n}" : "=r"(d) : "r"(s), "r"(c), "r"(off));
  return d;
}
template <int PAIR>
__device__ __forceinline__ uint32_t softmax_max(uint32_t (&s)[14], uint32_t keep, uint32_t scales) {
  const uint32_t fill = 0xFC00FC00u & ~keep;
  asm("lop3.b32 %0, %0, %1, %2, 0xEA;" : "+r"(s[12]) : "r"(keep), "r"(fill));
  asm("lop3.b32 %0, %0, %1, %2, 0xEA;" : "+r"(s[13]) : "r"(keep), "r"(fill));
  const uint32_t a = hmax2(hmax2(hmax2(s[0], s[2]), hmax2(s[4], s[6])), hmax2(hmax2(s[8], s[10]), s[12]));
  const uint32_t b = hmax2(hmax2(hmax2(s[1], s[3]), hmax2(s[5], s[7])), hmax2(hmax2(s[9], s[11]), s[13]));
  uint32_t m = hmax2(__byte_perm(a, b, 0x5410), __byte_perm(a, b, 0x7632));
  m = hmax2(m, __shfl_xor_sync(0xffffffffu, m, 1));
  m = hmax2(m, __shfl_xor_sync(0xffffffffu, m, 2));
  return hmul2(m, both<PAIR>(scales));
}
template <int PAIR>
__device__ __forceinline__ uint32_t softmax_top(const uint32_t (&s)[14], uint32_t lane, uint32_t scales, uint32_t& last) {
  last = __shfl_sync(0xffffffffu, __byte_perm(s[12], s[13], 0x5410), lane & 28);
  const uint32_t a = hmax2(hmax2(hmax2(s[0], s[2]), s[4]), hmax2(hmax2(s[6], s[8]), s[10]));
  const uint32_t b = hmax2(hmax2(hmax2(s[1], s[3]), s[5]), hmax2(hmax2(s[7], s[9]), s[11]));
  uint32_t m = hmax2(__byte_perm(a, b, 0x5410), __byte_perm(a, b, 0x7632));
  m = hmax2(m, __shfl_xor_sync(0xffffffffu, m, 1));
  m = hmax2(hmax2(m, last), __shfl_xor_sync(0xffffffffu, m, 2));
  return hmul2(m, both<PAIR>(scales));
}
__device__ __forceinline__ void lds128(uint32_t a, uint32_t* v) {
  asm volatile("ld.shared.v4.b32 {%0, %1, %2, %3}, [%4];" : "=r"(v[0]), "=r"(v[1]), "=r"(v[2]), "=r"(v[3]) : "r"(a) : "memory");
}
template <int PAIR, int SUM, int VAL>
__device__ __forceinline__ void softmax_rows(const uint32_t (&s)[14], uint32_t top, uint32_t last, uint32_t scales, uint32_t pad,
                                             uint32_t v_last, uint32_t (&pa)[12], uint32_t (&ov)[14]) {
  uint32_t off, v[6];
  lds128(v_last, v);
  lds64(v_last + 16, v[4], v[5]);
  asm("sub.rn.f16x2 %0, %1, %2;" : "=r"(off) : "r"(pad), "r"(top));
#pragma unroll
  for (int j = 0; j < 6; j++) {
    pa[2 * j] = exp2_scaled(s[2 * j], both<PAIR>(scales), both<0>(off));
    pa[2 * j + 1] = exp2_scaled(s[2 * j + 1], both<PAIR>(scales), both<1>(off));
  }
  const uint32_t p = exp2_scaled(last, both<PAIR>(scales), off);
#pragma unroll
  for (int j = 0; j < 6; j++) {
    ov[VAL + 2 * j] = hmul2_lo(v[j], p);
    ov[VAL + 2 * j + 1] = hmul2_hi(v[j], p);
  }
  ov[SUM] = __byte_perm(p, p, 0x1010);
  ov[SUM + 1] = __byte_perm(p, p, 0x3232);
}
__device__ __forceinline__ void issue_pv3(uint32_t (&ov)[14], const uint32_t (&pa)[12], uint64_t v_desc) {
#pragma unroll
  for (int k = 0; k < 3; k++) hmma_n56(ov, pa[4 * k], pa[4 * k + 1], pa[4 * k + 2], pa[4 * k + 3], desc_add(v_desc, k * 256));
}
__device__ __forceinline__ void sts128_if(bool on, uint32_t a, uint32_t v0, uint32_t v1, uint32_t v2, uint32_t v3) {
  asm volatile("{\n.reg .pred p;\nsetp.ne.u32 p, %5, 0;\n@p st.shared.v4.b32 [%0], {%1, %2, %3, %4};\n}"
               ::"r"(a), "r"(v0), "r"(v1), "r"(v2), "r"(v3), "r"((uint32_t)on) : "memory");
}
__device__ __forceinline__ void store_v3(const uint32_t (&v)[24], uint32_t v_st, uint32_t v_last, bool full, bool first_row, uint32_t r) {
  if (full) {
#pragma unroll
    for (int j = 0; j < 12; j += 2)
      stsm4_t(v_st + (j / 6) * (A_V1 - A_V0) + (j % 6) * 896, hmul2_lo(v[2 * j], r), hmul2_hi(v[2 * j + 1], r), hmul2_lo(v[2 * j + 2], r),
              hmul2_hi(v[2 * j + 3], r));
  } else {
#pragma unroll
    for (int h = 0; h < 2; h++) {
      sts128_if(first_row, v_last + h * (A_V1 - A_V0), hmul2_lo(v[12 * h], r), hmul2_lo(v[12 * h + 2], r), hmul2_lo(v[12 * h + 4], r),
                hmul2_lo(v[12 * h + 6], r));
      sts128_if(first_row, v_last + h * (A_V1 - A_V0) + 16, hmul2_lo(v[12 * h + 8], r), hmul2_lo(v[12 * h + 10], r), 0u, 0u);
    }
    __syncwarp();
  }
}
__device__ __forceinline__ void issue_s(uint32_t (&s)[14], const uint32_t* qa, uint64_t k_desc) {
  hmma_n56_first(s, qa[0], qa[1], qa[2], qa[3], k_desc);
#pragma unroll
  for (int k = 1; k < 3; k++) hmma_n56(s, qa[4 * k], qa[4 * k + 1], qa[4 * k + 2], qa[4 * k + 3], desc_add(k_desc, k * 2 * K_CHUNK));
}
template <int SUM, int VAL>
__device__ __forceinline__ void pack_o(const uint32_t (&ov)[14], uint32_t* o) {
  const uint32_t p = pack_f16(rcp(fmaxf(h_lo(ov[SUM]), 0.5f)), rcp(fmaxf(h_lo(ov[SUM + 1]), 0.5f)));
#pragma unroll
  for (int j = 0; j < 6; j++) {
    o[2 * j] = hmul2_lo(ov[VAL + 2 * j], p);
    o[2 * j + 1] = hmul2_hi(ov[VAL + 2 * j + 1], p);
  }
}
template <bool OVER>
__device__ __forceinline__ void issue_proj(uint32_t (&d)[24], const uint32_t (&x)[48], uint64_t desc) {
  if (OVER) hmma_n96_over(d, x[0], x[1], x[2], x[3], desc);
  else hmma_n96_first(d, x[0], x[1], x[2], x[3], desc);
#pragma unroll
  for (int s = 1; s < 12; s++) hmma_n96(d, x[4 * s], x[4 * s + 1], x[4 * s + 2], x[4 * s + 3], desc_add(desc, s * W_STEP));
}
template <int FIRST>
__device__ __forceinline__ void issue_half(uint32_t (&d)[24], const uint32_t (&x)[48], uint64_t desc) {
  if (FIRST == 2) hmma_n96_over(d, x[0], x[1], x[2], x[3], desc);
  if (FIRST == 1) hmma_n96_first(d, x[0], x[1], x[2], x[3], desc);
#pragma unroll
  for (int s = FIRST ? 1 : 6; s < (FIRST ? 6 : 12); s++) hmma_n96(d, x[4 * s], x[4 * s + 1], x[4 * s + 2], x[4 * s + 3], desc_add(desc, s * W_STEP));
}
template <int N>
__device__ __forceinline__ void issue_out(uint32_t (&d)[48], const uint32_t* o, uint64_t desc) {
#pragma unroll
  for (int s = 0; s < N; s++) hmma_n192(d, o[4 * s], o[4 * s + 1], o[4 * s + 2], o[4 * s + 3], desc_add(desc, s * WO_STEP));
}

__device__ __forceinline__ void mma_bf16(float (&c)[4], uint32_t a0, uint32_t a1, uint32_t a2, uint32_t a3, uint32_t b0, uint32_t b1) {
  asm("mma.sync.aligned.m16n8k16.row.col.f32.bf16.bf16.f32 {%0, %1, %2, %3}, {%4, %5, %6, %7}, {%8, %9}, {%0, %1, %2, %3};"
      : "+f"(c[0]), "+f"(c[1]), "+f"(c[2]), "+f"(c[3]) : "r"(a0), "r"(a1), "r"(a2), "r"(a3), "r"(b0), "r"(b1));
}
__device__ __forceinline__ void mma_bf16_k8(float (&d)[4], uint32_t a0, uint32_t a1, uint32_t b, const float (&c)[4]) {
  asm("mma.sync.aligned.m16n8k8.row.col.f32.bf16.bf16.f32 {%0, %1, %2, %3}, {%4, %5}, {%6}, {%7, %8, %9, %10};"
      : "=f"(d[0]), "=f"(d[1]), "=f"(d[2]), "=f"(d[3]) : "r"(a0), "r"(a1), "r"(b), "f"(c[0]), "f"(c[1]), "f"(c[2]), "f"(c[3]));
}
__device__ __forceinline__ bool on_diagonal(uint32_t lane) { return (lane & 3) == (lane >> 3); }
__device__ __forceinline__ float column_stats(const uint32_t (&v)[24], uint32_t lane, uint32_t& hi, uint32_t& lo) {
  float sum[2][4] = {}, sq[2][4] = {}, sr[2][4] = {};
#pragma unroll
  for (int c = 0; c < 24; c += 4) mma_bf16(sum[(c >> 2) & 1], v[c], v[c + 1], v[c + 2], v[c + 3], 0x3F803F80u, 0x3F803F80u);
#pragma unroll
  for (int c = 0; c < 24; c += 2) {
    mma_bf16_k8(sq[(c >> 1) & 1], v[c], v[c + 1], v[c], sq[(c >> 1) & 1]);
    mma_bf16_k8(sr[(c >> 1) & 1], v[c], v[c + 1], v[c + 1], sr[(c >> 1) & 1]);
  }
  const float total = (sum[0][0] + sum[0][2]) + (sum[1][0] + sum[1][2]), mean = total * (1.f / 192.f);
  const bool diag = on_diagonal(lane);
  const float n2 = (lane & 4) ? (sq[0][1] + sq[1][1]) + (sr[0][3] + sr[1][3]) : (sq[0][0] + sq[1][0]) + (sr[0][2] + sr[1][2]);
  hi = diag ? __float_as_uint(n2) : 0u;
  lo = __float_as_uint((diag && n2 > 0.f) ? fmaxf(fmaf(-total, mean, n2), 0.f) : INFINITY);
  return mean;
}
__device__ __forceinline__ uint32_t warp_max_abs(const uint32_t (&v)[8]) {
  uint32_t m = v[0];
#pragma unroll
  for (int c = 1; c < 8; c++) asm("max.NaN.xorsign.abs.bf16x2 %0, %0, %1;" : "+r"(m) : "r"(v[c]));
  return __reduce_max_sync(0xffffffffu, max(m & 0x7fffu, (m >> 16) & 0x7fffu));
}
__device__ __forceinline__ bool norms_in_range(uint32_t hi, uint32_t lo) {
  return hi - 0x08800000u <= 0x7B000000u - 0x08800000u && lo >= hi - (12u << 23);
}
__device__ __forceinline__ int norm_exponent(uint32_t n2) { return (int)(0x453B8000u - n2) >> 24; }
__device__ __forceinline__ void scale_to_f16(uint32_t (&v)[8], uint32_t lane, int e, float mean) {
  const uint32_t ident = on_diagonal(lane) ? (uint32_t)(e + 127) << ((lane & 4) ? 23 : 7) : 0u;
  const float c0 = -mean * __uint_as_float((uint32_t)(e + 127) << 23), c[4] = {c0, c0, c0, c0};
#pragma unroll
  for (int i = 0; i < 8; i += 2) {
    float d[4];
    mma_bf16_k8(d, v[i], v[i + 1], ident, c);
    v[i] = pack_f16(d[0], d[1]);
    v[i + 1] = pack_f16(d[2], d[3]);
  }
}
__device__ __forceinline__ float pow2(int e) { return __uint_as_float((uint32_t)(min(max(e, -126), 127) + 127) << 23); }

constexpr uint32_t kUnits = 24;
constexpr uint32_t RAW_O = W_PART, RAW_RED = RAW_O + 32 * 384;
__device__ __forceinline__ void bulk_load(uint32_t dst, const void* src, uint32_t bytes, uint32_t bar) {
  asm volatile("cp.async.bulk.shared::cluster.global.mbarrier::complete_tx::bytes [%0], [%1], %2, [%3];"
               ::"r"(dst), "l"(src), "r"(bytes), "r"(bar) : "memory");
}
__device__ __forceinline__ void tile_load(uint32_t dst, const CUtensorMap* tm, uint32_t c0, uint32_t c1, uint32_t bar) {
  asm volatile("cp.async.bulk.tensor.2d.shared::cluster.global.tile.mbarrier::complete_tx::bytes [%0], [%1, {%2, %3}], [%4];"
               ::"r"(dst), "l"(tm), "r"(c0), "r"(c1), "r"(bar) : "memory");
}
__device__ __forceinline__ void request_unit(uint32_t u, uint32_t raw, uint32_t bar, const CUtensorMap* tmw, const CUtensorMap* tmwo) {
  const bool is_o = (u & 7) >= 6;
  const uint32_t pair = is_o ? u & 1 : (u & 7) / 3, part = is_o ? 1 : (u & 7) % 3;
  mbar_expect_tx(bar, is_o ? W_PART + 32 * 384 : W_PART);
#pragma unroll
  for (uint32_t i = 0; i < 3; i++) tile_load(raw + i * (192 * 64), tmw, ((part + 1) % 3) * 192 + pair * 96 + 32 * i, 0, bar);
  if (is_o) {
#pragma unroll
    for (uint32_t i = 0; i < 6; i++) tile_load(raw + RAW_O + i * (32 * 64), tmwo, 32 * i, pair * 96 + (u >> 3) * 32, bar);
  }
}
__device__ __forceinline__ void ldsm4_t(uint32_t a, uint32_t* v) {
  asm volatile("ldmatrix.sync.aligned.m8n8.x4.trans.shared.b16 {%0, %1, %2, %3}, [%4];" : "=r"(v[0]), "=r"(v[1]), "=r"(v[2]), "=r"(v[3]) : "r"(a) : "memory");
}
__device__ __forceinline__ void prepare_unit(uint32_t u, uint32_t wid, uint32_t lane, uint32_t raw, Scratch* scr) {
  const bool is_o = (u & 7) >= 6;
  const uint32_t third = u >> 3;
  uint32_t v[24], w[8];
  const uint32_t src = raw + (wid >> 2) * (192 * 64) + lane * 64 + (((wid ^ (lane >> 1)) & 3) << 4);
#pragma unroll
  for (int m = 0; m < 6; m++) ldsm4_t(src + m * (32 * 64), &v[4 * m]);
  uint32_t hi, lo, top = 0;
  const float mean = column_stats(v, lane, hi, lo);
  if (is_o) {
#pragma unroll
    for (int m = 0; m < 2; m++)
      ldsm4_t(raw + RAW_O + (wid >> 1) * (32 * 64) + lane * 64 + ((((2 * wid + m) ^ (lane >> 1)) & 3) << 4), &w[4 * m]);
    top = warp_max_abs(w);
  } else {
#pragma unroll
    for (int m = 0; m < 2; m++) ldsm4_t(src + (2 * third + m) * (32 * 64), &w[4 * m]);
  }
  hi = __reduce_max_sync(0xffffffffu, hi);
  lo = __reduce_min_sync(0xffffffffu, lo);
  if (lane == 0) {
    sts64(raw + RAW_RED + wid * 16, hi, lo);
    sts32(raw + RAW_RED + wid * 16 + 8, top);
  }
  asm volatile("bar.sync 4, 384;" ::: "memory");
  lds64(raw + RAW_RED + (lane % 12) * 16, hi, lo);
  top = lds32(raw + RAW_RED + (lane % 12) * 16 + 8);
  hi = __reduce_max_sync(0xffffffffu, hi);
  lo = __reduce_min_sync(0xffffffffu, lo);
  top = __reduce_max_sync(0xffffffffu, top);
  const int e = norm_exponent(hi);
  scale_to_f16(w, lane, is_o ? -e : e - 4, is_o ? 0.f : mean);
  const uint32_t mat = lane >> 3, at = (mat & 1) * 128 + (lane & 7) * 16;
#pragma unroll
  for (int m = 0; m < 2; m++)
    stsm4(raw + at + (is_o ? (mat >> 1) * WO_STEP + (2 * wid + m) * 256 : (2 * m + (mat >> 1)) * W_STEP + wid * 256), w[4 * m], w[4 * m + 1],
          w[4 * m + 2], w[4 * m + 3]);
  fence_async();
  asm volatile("bar.sync 4, 384;" ::: "memory");
  if (wid == 0 && lane == 0) {
    asm volatile("cp.async.bulk.global.shared::cta.bulk_group [%0], [%1], %2;\ncp.async.bulk.commit_group;"
                 ::"l"(scr->weights + (u & 7) * W_PART + third * (W_PART / 3)), "r"(raw), "n"(W_PART / 3) : "memory");
    const bool bad = is_o ? !(__uint_as_float(top << 16) * pow2(-e) <= 0.25f) : !norms_in_range(hi, lo);
    const uint32_t exponent = (!is_o && third == 0 && u % 3 != 1) ? (uint32_t)(e + 64) << (u < 3 ? 10 : 19) : 0u;
    asm volatile("cp.async.bulk.wait_group 0;" ::: "memory");
    asm volatile("red.relaxed.gpu.global.add.u32 [%0], %1;" ::"l"(&scr->ready), "r"(bad ? 33u : 1u + exponent) : "memory");
  }
  __syncwarp();
}

constexpr uint32_t REDO_BYTES = 75776;
static_assert(3 * REDO_BYTES <= OFF_TAIL && (3 * 49 * 192 + 49 * 144) * 2 <= REDO_BYTES, "redo scratch");
__device__ __forceinline__ float round_bf16(float x) { return __bfloat162float(__float2bfloat16(x)); }
__device__ __forceinline__ void redo_window(int c0, int y0, int t, uint32_t bar, uint8_t* scratch, const __nv_bfloat16* x,
                                            const __nv_bfloat16* dw, const __nv_bfloat16* wqkv, const __nv_bfloat16* wo,
                                            __nv_bfloat16* out) {
  __nv_bfloat16* x0 = reinterpret_cast<__nv_bfloat16*>(scratch);
  __nv_bfloat16* h = x0 + 49 * 192;
  __nv_bfloat16* o = h + 49 * 192;
  __nv_bfloat16* qkv = o + 49 * 192;
  bar_sync(bar);
#pragma unroll 1
  for (int i = t; i < 49 * 192; i += 128) {
    const int tok = i / 192, c = i % 192, y = y0 + tok / 7, xx = c0 + tok % 7;
    float pe = 0.f;
#pragma unroll 1
    for (int k = 0; k < 9; k++) {
      const int yy = y + k / 3 - 1, xj = xx + k % 3 - 1;
      const bool in = (uint32_t)yy < kImg && (uint32_t)xj < kImg;
      const float v = in ? __bfloat162float(x[((size_t)yy * kImg + xj) * kCh + c]) : 0.f;
      pe = round_bf16(pe + round_bf16(v * __bfloat162float(dw[k * kCh + c])));
    }
    x0[i] = __float2bfloat16(__bfloat162float(x[((size_t)y * kImg + xx) * kCh + c]) + pe);
  }
  bar_sync(bar);
  if (t < 49) {
    float s = 0.f, v = 0.f;
#pragma unroll 1
    for (int c = 0; c < 192; c++) s += __bfloat162float(x0[t * 192 + c]);
    const float mean = s * (1.f / 192.f);
#pragma unroll 1
    for (int c = 0; c < 192; c++) {
      const float d = __bfloat162float(x0[t * 192 + c]) - mean;
      v = fmaf(d, d, v);
    }
    const float m = round_bf16(mean), sd = round_bf16(sqrtf(round_bf16(round_bf16(v * (1.f / 192.f)) + 1e-5f)));
#pragma unroll 1
    for (int c = 0; c < 192; c++) h[t * 192 + c] = __float2bfloat16(round_bf16(__bfloat162float(x0[t * 192 + c]) - m) / sd);
  }
#pragma unroll 1
  for (int head = 0; head < 4; head++) {
    bar_sync(bar);
#pragma unroll 1
    for (int i = t; i < 49 * 144; i += 128) {
      const int tok = i / 144, n = i % 144, col = (n / 48) * 192 + head * 48 + n % 48;
      float a = 0.f;
#pragma unroll 4
      for (int c = 0; c < 192; c++) a = fmaf(__bfloat162float(h[tok * 192 + c]), __bfloat162float(wqkv[c * 576 + col]), a);
      qkv[i] = __float2bfloat16(a);
    }
    bar_sync(bar);
    if (t < 49) {
      float p[49], m = -INFINITY, s = 0.f;
#pragma unroll
      for (int b = 0; b < 49; b++) {
        float a = 0.f;
#pragma unroll 4
        for (int d = 0; d < 48; d++) a = fmaf(__bfloat162float(qkv[t * 144 + d]), __bfloat162float(qkv[b * 144 + 48 + d]), a);
        p[b] = round_bf16(round_bf16(a) * 0.14433757f);
        m = fmaxf(m, p[b]);
      }
#pragma unroll
      for (int b = 0; b < 49; b++) {
        p[b] = expf(p[b] - m);
        s += p[b];
      }
#pragma unroll
      for (int b = 0; b < 49; b++) p[b] = round_bf16(p[b] / s);
#pragma unroll 1
      for (int d = 0; d < 48; d++) {
        float a = 0.f;
#pragma unroll
        for (int b = 0; b < 49; b++) a = fmaf(p[b], __bfloat162float(qkv[b * 144 + 96 + d]), a);
        o[t * 192 + head * 48 + d] = __float2bfloat16(a);
      }
    }
  }
  bar_sync(bar);
#pragma unroll 1
  for (int i = t; i < 49 * 192; i += 128) {
    const int tok = i / 192, n = i % 192;
    float a = 0.f;
#pragma unroll 4
    for (int c = 0; c < 192; c++) a = fmaf(__bfloat162float(o[tok * 192 + c]), __bfloat162float(wo[c * kCh + n]), a);
    out[((size_t)(y0 + tok / 7) * kImg + c0 + tok % 7) * kCh + n] = __float2bfloat16(__bfloat162float(x0[tok * 192 + n]) + round_bf16(a));
  }
}

__device__ __forceinline__ uint32_t fresh_tid() {
  uint32_t t;
  asm volatile("mov.u32 %0, %%tid.x;" : "=r"(t));
  return t;
}
struct Split {
  uint32_t top, rows, alone, share, fewer;
  uint32_t magic[2];
};
struct Windows {
  uint32_t first, count, alone, jump, height, row0, magic;
  __device__ __forceinline__ explicit Windows(const Split& s) {
    uint32_t b;
    asm volatile("mov.u32 %0, %%ctaid.x;" : "=r"(b));
    const bool upper = b < s.top;
    const uint32_t i = upper ? 0 : b - s.top;
    height = upper ? s.rows : kWinPerCol - s.rows;
    row0 = upper ? 0 : s.rows;
    magic = upper ? s.magic[0] : s.magic[1];
    alone = upper ? s.rows : s.alone;
    first = upper ? b * s.rows : i * s.alone;
    count = upper ? s.rows : s.alone + s.share + max(i + 1, s.fewer) - max(i, s.fewer);
    jump = (gridDim.x - s.top - 1 - i) * s.alone + i * s.share + max(i, s.fewer) - s.fewer;
  }
  __device__ __forceinline__ bool at(uint32_t j, uint32_t& col, uint32_t& row) const {
    const uint32_t v = first + j + (j >= alone ? jump : 0);
    col = (v * magic) >> 20;
    row = v - col * height + row0;
    return row == row0 || j == alone;
  }
};
template <uint32_t BYTES>
__device__ __forceinline__ void load_rows(uint32_t dst, const CUtensorMap* tm, uint32_t ch, int x, int y, uint32_t bar) {
  asm volatile("{\n.reg .pred p;\nelect.sync _|p, 0xffffffff;\n"
               "@p mbarrier.arrive.expect_tx.shared::cta.b64 _, [%5], %6;\n"
               "@p cp.async.bulk.tensor.3d.shared::cluster.global.tile.mbarrier::complete_tx::bytes [%0], [%1, {%2, %3, %4}], [%5];\n}"
               ::"r"(dst), "l"(tm), "r"(ch), "r"(x), "r"(y), "r"(bar), "n"(BYTES) : "memory");
}
__device__ __forceinline__ void prefetch_box(const CUtensorMap* tm, int x, int y) {
  asm volatile("cp.async.bulk.prefetch.tensor.3d.L2.global.tile [%0, {%1, %2, %3}];" ::"l"(tm), "r"(0), "r"(x), "r"(y) : "memory");
}
__device__ __forceinline__ void prefetch_rows(const CUtensorMap* tm, int x, int y) {
  asm volatile("{\n.reg .pred p;\nelect.sync _|p, 0xffffffff;\n"
               "@p cp.async.bulk.prefetch.tensor.3d.L2.global.tile [%0, {%1, %2, %3}];\n}" ::"l"(tm), "r"(0), "r"(x), "r"(y) : "memory");
}
__device__ __forceinline__ void store_group(const CUtensorMap* tm, uint32_t src, uint32_t ch, uint32_t x, uint32_t y) {
  asm volatile("cp.async.bulk.tensor.3d.global.shared::cta.tile.bulk_group [%0, {%2, %3, %4}], [%1];"
               ::"l"(tm), "r"(src), "r"(ch), "r"(x), "r"(y) : "memory");
}

template <int N> struct Int { static constexpr int value = N; };
struct Conv {
  uint32_t wt[9], prev[9], acc[7];
  __device__ __forceinline__ void begin(const uint32_t (&cur)[9]) {
#pragma unroll
    for (int x = 0; x < 7; x++) {
      uint32_t a = bmul2(prev[x], wt[0]);
      a = bfma2(prev[x + 1], wt[1], a);
      a = bfma2(prev[x + 2], wt[2], a);
#pragma unroll
      for (int t = 0; t < 3; t++) a = bfma2(cur[x + t], wt[3 + t], a);
      acc[x] = a;
    }
#pragma unroll
    for (int x = 0; x < 9; x++) prev[x] = cur[x];
  }
  __device__ __forceinline__ void start_column(uint32_t slot0, uint32_t bar0, uint32_t parity0, uint32_t slot1, uint32_t bar1,
                                               uint32_t parity1, uint32_t lane, uint32_t dump, bool request, const CUtensorMap* tm,
                                               uint32_t ch, int x, int y) {
    uint32_t cur[9];
    mbar_wait(bar0, parity0);
#pragma unroll
    for (int i = 0; i < 9; i++) prev[i] = lds32(slot0 + lane * 4 + i * 128);
    sts32(dump, prev[0] ^ prev[1] ^ prev[2] ^ prev[3] ^ prev[4] ^ prev[5] ^ prev[6] ^ prev[7] ^ prev[8]);
    if (request) load_rows<HALO_ROW>(slot0, tm, ch, x, y, bar0);
    mbar_wait(bar1, parity1);
#pragma unroll
    for (int i = 0; i < 9; i++) cur[i] = lds32(slot1 + lane * 4 + i * 128);
    begin(cur);
    sts32(dump, acc[0] ^ acc[3] ^ acc[6]);
    if (request) load_rows<HALO_ROW>(slot1, tm, ch, x, y + 1, bar1);
  }
  __device__ __forceinline__ void row_at(uint32_t src, uint32_t dst, uint32_t t) {
    uint32_t cur[9];
#pragma unroll
    for (int x = 0; x < 9; x++) cur[x] = lds32(src + x * 128);
#pragma unroll
    for (int x = 0; x < 7; x++) {
      uint32_t a = acc[x];
#pragma unroll
      for (int i = 0; i < 3; i++) a = bfma2(cur[x + i], wt[6 + i], a);
      sts32((dst ^ (((t + x) & 7) << 4)) + x * 128, bf16x2_to_f16x2(badd2(prev[x + 1], a)));
    }
    begin(cur);
  }
  template <int R>
  __device__ __forceinline__ void row(uint32_t src, uint32_t dst, uint32_t at) {
    uint32_t cur[9];
#pragma unroll
    for (int x = 0; x < 9; x++) cur[x] = lds32(src + x * 128);
#pragma unroll
    for (int x = 0; x < 7; x++) {
      uint32_t a = acc[x];
#pragma unroll
      for (int t = 0; t < 3; t++) a = bfma2(cur[x + t], wt[6 + t], a);
      sts32((dst ^ (((R * 7 + x) & 7) << 4)) + at + x * 128, bf16x2_to_f16x2(badd2(prev[x + 1], a)));
    }
    begin(cur);
  }
};

__global__ void __launch_bounds__(512, 1)
davit_window_attn_kernel(const __grid_constant__ CUtensorMap tm1, const __grid_constant__ CUtensorMap tm7c,
                         const __grid_constant__ CUtensorMap tm7, const __grid_constant__ CUtensorMap tmo,
                         const __grid_constant__ CUtensorMap tmw, const __grid_constant__ CUtensorMap tmwo,
                         const __nv_bfloat16* __restrict__ dw, const __nv_bfloat16* __restrict__ x_raw,
                         const __nv_bfloat16* __restrict__ wqkv_raw, const __nv_bfloat16* __restrict__ wo_raw,
                         __nv_bfloat16* __restrict__ out, Scratch* __restrict__ scr, const Split split) {
  extern __shared__ __align__(1024) uint8_t smem_raw[];
  const uint32_t sb = (uint32_t)__cvta_generic_to_shared(smem_raw);
  const uint32_t tail = sb + OFF_TAIL;
  uint32_t wt[9];
  {
    const uint32_t tid = threadIdx.x;
    const uint32_t wid = __shfl_sync(0xffffffffu, tid >> 5, 0), lane = tid & 31;
    if (wid > 12) {
      const uint32_t chunk = wid - 13, hbar = tail + T_HALO + 16 * chunk, rbar = tail + T_ROW + 16 * chunk;
      if (lane == 0) {
        mbar_init(hbar, 1);
        mbar_init(hbar + 8, 1);
        mbar_init(rbar, 1);
        mbar_init(rbar + 8, 1);
        if (wid == 13) mbar_init(tail + T_RAW, 1);
        fence_async();
      }
      __syncwarp();
      if (blockIdx.x < kUnits) {
        if (wid == 13 && lane == 0) request_unit(blockIdx.x, sb + OFF_RING, tail + T_RAW, &tmw, &tmwo);
        asm volatile("bar.sync 5, 96;" ::: "memory");
      }
      uint32_t col, row;
      Windows(split).at(0, col, row);
      const int x = (int)col * 7 - 1, y = (int)row * 7;
      const uint32_t halo = sb + OFF_HALO + chunk * 2 * HALO_ROW;
      load_rows<HALO_ROW>(halo, &tm1, chunk * 64, x, y - 1, hbar);
      load_rows<HALO_ROW>(halo + HALO_ROW, &tm1, chunk * 64, x, y, hbar + 8);
      load_rows<7 * HALO_ROW>(sb + OFF_KV + chunk * 7 * HALO_ROW, &tm7c, chunk * 64, x, y + 1, rbar);
#pragma unroll
      for (int i = 0; i < 9; i++) wt[i] = __ldg(reinterpret_cast<const uint32_t*>(dw) + i * (kCh / 2) + chunk * 32 + lane);
    } else {
      if (lane == 0) {
        if (wid < 12) {
          const uint32_t i = 2 * wid, counts = (uint32_t)((wid < 8 ? 0x4144444333CCC111ull >> (8 * wid) : 0x11444144u >> (8 * wid - 64)));
          mbar_init(tail + 8 * (i < 11 ? i : i + 6), counts & 15);
          if (wid < 11)
          mbar_init(tail + 8 * (i < 10 ? i + 1 : i + 7), (counts >> 4) & 15);
          fence_async();
        }
      }
      if (wid == 12) {
        for (uint32_t line = blockIdx.x + gridDim.x * lane; line < 2304; line += gridDim.x * 32) {
          const uint8_t* p = (line < 1728) ? reinterpret_cast<const uint8_t*>(wqkv_raw) + line * 128
                                           : reinterpret_cast<const uint8_t*>(wo_raw) + (line - 1728) * 128;
          asm volatile("prefetch.global.L2 [%0];" ::"l"(p));
        }
        if (lane < 7) sts32(tail + T_ZERO + 4 * lane, 0u);
      }
    }
    __syncthreads();
  }

  if (threadIdx.x >= 384) {
    asm volatile("setmaxnreg.dec.sync.aligned.u32 %0;" ::"n"(56));
    const uint32_t tid = fresh_tid();
    const uint32_t warp = __shfl_sync(0xffffffffu, (tid >> 5) & 3, 0), lane = tid & 31;
    if (warp == 0) {
      if (lane == 0) {
        const Windows win(split);
        uint32_t spins = 0, seen;
        while (true) {
          asm volatile("ld.acquire.gpu.global.u32 %0, [%1];" : "=r"(seen) : "l"(&scr->ready) : "memory");
          if ((seen & 31) == kUnits) break;
          if (++spins > (1u << 22)) __trap();
        }
        asm volatile("fence.proxy.async.global;" ::: "memory");
        const uint8_t* w = scr->weights;
        {
          const int e0 = (int)((seen >> 10) & 511) - 128, e1 = (int)(seen >> 19) - 128;
          sts32(tail + T_SCALE, pack_f16(fmaxf(0.20823509f * pow2(9 - e0), 0x1p-24f), fmaxf(0.20823509f * pow2(9 - e1), 0x1p-24f)));
          if ((seen & 0x3E0u) || e0 < 1 || e1 < 1) sts32(tail + T_ALL, 1u);
        }
#pragma unroll
        for (uint32_t s = 0; s < 3; s++) {
          mbar_expect_tx(tail + T_FULL + 8 * s, W_PART);
          bulk_load(sb + OFF_RING + s * W_PART, w + s * W_PART, W_PART, tail + T_FULL + 8 * s);
        }
#pragma unroll 1
        for (uint32_t j = 1; j < 4 && j < win.count; j++) {
          uint32_t col, row;
          const bool fresh = win.at(j, col, row);
          if (j > 1 || fresh) prefetch_box(&tm7, 7 * col - 1, 7 * row + 1);
          if (fresh) prefetch_box(&tm7, 7 * col - 1, 7 * row - 1);
        }
        if (atomicInc(&scr->passed, gridDim.x - 1) == gridDim.x - 1) scr->ready = 0;
        const uint32_t uses = 8 * ((win.count + 2) / 3);
        uint32_t s = 0, parity = 0;
#pragma unroll 1
        for (uint32_t u = 3; u < uses; u++) {
          mbar_wait(tail + T_EMPTY + 8 * s, parity);
          mbar_expect_tx(tail + T_FULL + 8 * s, W_PART);
          bulk_load(sb + OFF_RING + s * W_PART, w + (u & 7) * W_PART, W_PART, tail + T_FULL + 8 * s);
          s = (s == 2) ? 0 : s + 1;
          parity ^= (s == 0);
        }
      }
    } else {
      Conv cv;
#pragma unroll
      for (int i = 0; i < 9; i++) cv.wt[i] = wt[i];
      {
        const uint32_t chunk = warp - 1, halo = sb + OFF_HALO + chunk * 2 * HALO_ROW, hbar = tail + T_HALO + 16 * chunk;
        const Windows win(split);
        uint32_t col, row, cn, rn;
        const uint32_t staged = (win.count > 1 && !win.at(1, col, row)) ? 2 : 1;
        const bool fresh = win.at(staged, cn, rn);
        cv.start_column(halo, hbar, 0, halo + HALO_ROW, hbar + 8, 0, lane, tail + T_DUMP, staged < win.count, &tm1, chunk * 64, 7 * cn - 1,
                        fresh ? 7 * rn - 1 : 7 * rn + 1);
        if (staged == 2)
          load_rows<7 * HALO_ROW>(sb + OFF_KV + (3 + chunk) * 7 * HALO_ROW, &tm7c, chunk * 64, 7 * col - 1, 7 * row + 1,
                                  tail + T_ROW + 16 * chunk + 8);
#pragma unroll 1
        for (uint32_t i = 0; i < staged; i++) {
          mbar_wait(tail + T_ROW + 16 * chunk + 8 * i, 0);
#pragma unroll 1
          for (uint32_t r = 0; r < 7; r++)
            cv.row_at(sb + OFF_KV + ((3 * i + chunk) * 7 + r) * HALO_ROW + lane * 4,
                      sb + OFF_X0 + chunk * X0_CHUNK + lane * 4 + (7 * i + r) * X0_ROW, 7 * r);
          __syncwarp();
          arrive_elected(tail + T_X0FULL + 8 * i);
        }
      }
      const uint32_t chunk = __shfl_sync(0xffffffffu, (fresh_tid() >> 5) & 3, 0) - 1, ch = chunk * 64;
      const uint32_t halo = sb + OFF_HALO + chunk * 2 * HALO_ROW, hbar = tail + T_HALO + 16 * chunk;
      const uint32_t src = halo + lane * 4, dst = sb + OFF_X0 + chunk * X0_CHUNK + lane * 4;
      const Windows win(split);
      const uint32_t count = win.count;
      uint32_t col, row;
      const uint32_t staged = (count > 1 && !win.at(1, col, row)) ? 2 : 1;
      bool fresh = win.at(staged, col, row);
      uint32_t n = 2;
#pragma unroll 1
      for (uint32_t j = staged; j < count; j++) {
        int x = (int)col * 7 - 1, y = (int)row * 7;
        uint32_t at = 7 * j % kRows * X0_ROW;
        const uint32_t slot[2] = {(n & 1) * HALO_ROW, HALO_ROW - (n & 1) * HALO_ROW}, bar[2] = {hbar + 8 * (n & 1), hbar + 8 - 8 * (n & 1)};
        if (fresh) {
          cv.start_column(halo + slot[0], bar[0], (n >> 1) & 1, halo + slot[1], bar[1], ((n + 1) >> 1) & 1, lane, tail + T_DUMP, true, &tm1, ch,
                          x, y + 1);
          n += 2;
        }
        const uint32_t parity[2] = {(n >> 1) & 1, ((n + 1) >> 1) & 1};
        const bool more = j + 1 < count;
        if (chunk == 0 && j + 2 < count) {
          if (win.at(j + 2, col, row)) prefetch_rows(&tm7, 7 * col - 1, 7 * row - 1);
          prefetch_rows(&tm7, 7 * col - 1, 7 * row + 1);
        }
        fresh = win.at(j + 1, col, row);
        auto step = [&](auto r) {
          constexpr int R = decltype(r)::value;
          if (R == kRows - 14) {
            mbar_wait(tail + T_X0FREE + 8 * (j & 1), ((j >> 1) & 1) ^ 1);
            x = (int)col * 7 - 1;
            y = (int)row * 7 - (fresh ? 9 : 7);
          }
          mbar_wait(bar[R & 1], parity[R & 1] ^ ((R >> 1) & 1));
          cv.template row<R>(src + slot[R & 1], dst, at);
          if (R < 5 || more) load_rows<HALO_ROW>(halo + slot[R & 1], &tm1, ch, x, y + R + 3, bar[R & 1]);
          at = (at == (kRows - 1) * X0_ROW) ? 0 : at + X0_ROW;
        };
        static_assert(kRows - 14 == 5, "ring of x0 rows");
        step(Int<0>()); step(Int<1>()); step(Int<2>()); step(Int<3>()); step(Int<4>()); step(Int<5>()); step(Int<6>());
        __syncwarp();
        arrive_elected(tail + T_X0FULL + 8 * (j % 3));
        n += 7;
      }
    }
    __syncwarp();
    asm volatile("bar.sync 0, 512;" ::: "memory");
  } else {
    asm volatile("setmaxnreg.inc.sync.aligned.u32 %0;" ::"n"(152));
    const uint32_t wid = __shfl_sync(0xffffffffu, fresh_tid() >> 5, 0);
    const uint32_t wg = wid >> 2, warp = wid & 3;
    uint32_t lane;
    asm volatile("mov.u32 %0, %%laneid;" : "=r"(lane));
#pragma unroll 1
    for (uint32_t u = blockIdx.x, i = 0; u < kUnits; u += gridDim.x, i++) {
      if (i) {
        asm volatile("bar.sync 4, 384;" ::: "memory");
        if (wid == 0 && lane == 0) request_unit(u, sb + OFF_RING, tail + T_RAW, &tmw, &tmwo);
      }
      mbar_wait(tail + T_RAW, i & 1);
      prepare_unit(u, wid, lane, sb + OFF_RING, scr);
    }
    const uint32_t count = Windows(split).count;
    const uint32_t q = lane & 3, mat = lane >> 3, row = lane & 7;
    const uint32_t area = sb + OFF_KV + wg * KV_SIZE, stage = (area + 127) & ~127u;
    const uint32_t bars = tail + T_WG + 32 * wg;
    const bool full = warp < 3;
    const bool valid = full || lane < 4;
    const bool lead = lane == 0;
    uint32_t k_st, v_st, x_ld, x_mask, x_row, o_st;
    {
      const uint32_t rowg = full ? 2 * warp + (mat & 1) : 6, colg = full ? (mat >> 1) : (mat & 1);
      k_st = full ? area + A_K0 + colg * K_CHUNK + rowg * 128 + row * 16 : area + A_K0 + 768 + q * 4;
      v_st = area + A_V0 + colg * 896 + rowg * 128 + row * 16;
      const uint32_t t = 16 * warp + row + 8 * (mat & 1);
      x_ld = (t < 49) ? sb + OFF_X0 + t * 128 + (((mat >> 1) ^ row) << 4) : tail + T_ZERO;
      x_mask = (t < 49) ? ~0u : 0u;
      x_row = t / 7;
      const uint32_t a = stage + (full ? t : 48) * 64;
      o_st = a + (((full ? (mat >> 1) : 0) ^ ((a >> 7) & 3)) << 4) + (full ? 0 : 4 * q);
    }
    const uint32_t v_last = area + A_V0 + 768 + q * 32;
    const uint32_t pad = (valid ? 0u : 0xFC00u) | (full ? 0u : 0xFC000000u);
    const uint64_t k_desc = make_desc(area + A_K0, K_CHUNK, 128);
    const uint64_t v_desc = make_desc(area + A_V0, 128, 896);
    const uint64_t w_desc = make_desc(sb + OFF_RING, 128, 256);
    if (wg == 2) asm volatile("bar.arrive 8, 256;" ::: "memory");
    if (wg < count) {
      mbar_wait(tail + T_X0FULL + 8 * wg, 0);
      if (warp < 2 && lane < 28) {
        sts64(area + A_ONES + (28 * warp + lane) * 16, 0x3C003C00u, 0x3C003C00u);
        sts64(area + A_ONES + (28 * warp + lane) * 16 + 8, 0x3C003C00u, 0x3C003C00u);
      }
      __syncwarp();
    }
    mbar_wait(tail + T_FULL, 0);
    const uint32_t scales = lds32(tail + T_SCALE);
    auto send_output = [&](uint32_t j, uint32_t parity) {
      uint32_t col, row;
      Windows(split).at(j, col, row);
      mbar_wait(bars + B_OUTRDY, parity);
#pragma unroll
      for (int i = 0; i < 6; i++) store_group(&tmo, stage + out_group(i), 32 * i, 7 * col, 7 * row);
      asm volatile("cp.async.bulk.commit_group;" ::: "memory");
    };
    uint32_t round = 0;
#pragma unroll 1
    for (; 3 * round + wg < count; round++) {
      const uint32_t r = __shfl_sync(0xffffffffu, round, 0), j = 3 * r + wg, ph = r & 1;
      const uint32_t m = 8 * r / 3, rot = 8 * r - 3 * m;
      const uint32_t ra = 8 * rot, rb = (rot == 2) ? 0 : ra + 8, rc = (rot == 0) ? 16 : ra - 8;
      const uint32_t pa = m & 1, pb = pa ^ (rot == 2), pc = pa ^ (rot != 0);
      uint32_t x[48], ka[24], va[24], oa[24], ob[24], rr;
      uint32_t (&qa)[24] = ka;
      uint32_t sc0[14], sc1[14], pa0[12], pa1[12], ov0[14], ov1[14];
      mbar_wait(tail + T_X0FULL + 8 * wg, ph);
      {
        asm volatile("" : "+r"(x_mask));
        const uint32_t at = 7 * j % kRows;
        const uint32_t a = x_ld + ((at * X0_ROW - (x_row >= kRows - at ? X0_CHUNK : 0)) & x_mask);
#pragma unroll
        for (int s = 0; s < 12; s++)
          ldsm4((a ^ (((s & 3) << 5) & x_mask)) + ((s >> 2) * X0_CHUNK & x_mask), x[4 * s], x[4 * s + 1], x[4 * s + 2], x[4 * s + 3]);
      }
      warp_arrive(tail + T_X0FREE + 8 * (j & 1), lead);
#pragma unroll
      for (int p = 0; p < 2; p++) {
        asm volatile("bar.sync %0, 256;" ::"r"(8 + wg) : "memory");
        mbar_wait(tail + T_FULL + ra, pa ^ p);
        wg_fence();
        issue_proj<false>(ka, x, desc_at(w_desc, ra * (W_PART / 8)));
        wg_commit();
        if (p == 0) {
          if (!full && lead && r > 0) send_output(j - 3, ph ^ 1);
          __syncwarp();
        }
        if (p == 1) {
          wg_wait<1>();
          fence_regs(ov1);
          if (lead) mbar_arrive(bars + B_KVFREE);
          pack_o<0, 2>(ov1, &oa[12]);
        }
        mbar_wait(tail + T_FULL + rb, pb ^ p);
        wg_fence();
        {
          const uint64_t d = desc_at(w_desc, rb * (W_PART / 8));
          issue_half<1>(va, x, d);
          wg_commit();
          wg_wait<1>();
          if (lead) mbar_arrive(tail + T_EMPTY + ra);
          __syncwarp();
          issue_half<0>(va, x, d);
          wg_commit();
        }
        asm volatile("bar.arrive %0, 256;" ::"r"(wg == 2 ? 8 : 9 + wg) : "memory");
        if (p == 0) {
          const bool odd = q & 1;
          uint32_t lane_sums[2];
          lane_stats_packed(x, lane_sums);
          const uint32_t packed = quad_stats_packed(lane_sums, odd);
          float sum = h_lo(packed), squares = h_hi(packed);
          const bool fine = (squares >= 0.1875f || (pad & (odd ? 0xFC000000u : 0xFC00u))) & (squares <= 65504.f) & (sum * sum <= 96.f * squares);
          const bool exact = !__all_sync(0xffffffffu, fine);
          if (exact) {
            wg_wait<0>();
            row_stats(x, odd, sum, squares);
          }
          const float mean = sum * (1.f / 192.f);
          const float rs = 16.f * rsqrt_fast(fmaxf(fmaf(squares, 1.f / 192.f, -mean * mean), 0.f) + 1e-5f);
          if (exact) {
            const uint32_t range = __reduce_max_sync(0xffffffffu, __float_as_uint(squares * fmaxf(rs * rs, 1.f)));
            if ((range > 0x4D400000u || (range != 0u && range < 0x4585A800u)) && lead) {
              scr->redo[blockIdx.x + gridDim.x * j] = 1;
              sts32(tail + T_ANY, 1u);
            }
          }
          const float o = __shfl_xor_sync(0xffffffffu, rs, 1);
          rr = pack_f16(odd ? o : rs, odd ? rs : o);
          if (!full && lead) {
            asm volatile("cp.async.bulk.wait_group.read 0;" ::: "memory");
            mbar_arrive(bars + B_OUTFREE);
          }
          __syncwarp();
          mbar_wait(bars + B_OUTFREE, ph);
        } else {
          mbar_wait(bars + B_KVFREE, 0);
        }
        fence_regs(ka);
        store_k(ka, k_st, full, lane < 4, rr);
        mbar_wait(tail + T_FULL + rc, pc ^ p);
        wg_fence();
        {
          const uint64_t d = desc_at(w_desc, rc * (W_PART / 8));
          issue_half<2>(qa, x, d);
          wg_commit();
          wg_wait<1>();
          if (lead) mbar_arrive(tail + T_EMPTY + rb);
          __syncwarp();
          issue_half<0>(qa, x, d);
          wg_commit();
        }
        fence_regs(va);
        store_v3(va, v_st, v_last, full, lane < 4, rr);
        fence_async();
        warp_arrive(bars + B_KVRDY, lead);
        wg_wait<0>();
        fence_regs(qa);
        if (lead) mbar_arrive(tail + T_EMPTY + rc);
        {
          const uint32_t rq = hmul2(rr, 0x18001800u);
#pragma unroll
          for (int i = 0; i < 24; i += 2) {
            qa[i] = hmul2_lo(qa[i], rq);
            qa[i + 1] = hmul2_hi(qa[i + 1], rq);
          }
        }
        mbar_wait(bars + B_KVRDY, p);

        wg_fence();
        issue_s(sc0, &qa[0], desc_at(k_desc, 0));
        wg_commit();
        uint32_t top0, top1, last0, last1;
        if (p == 0) {
          issue_s(sc1, &qa[12], desc_at(k_desc, A_K1));
          wg_commit();
          wg_wait<1>();
          fence_regs(sc0);
          top0 = softmax_top<0>(sc0, lane, scales, last0);
          softmax_rows<0, 12, 0>(sc0, top0, last0, scales, pad, v_last, pa0, ov0);
          wg_fence();
          issue_pv3(ov0, pa0, desc_at(v_desc, 0));
          wg_commit();
          wg_wait<1>();
          fence_regs(sc1);
          top1 = softmax_top<0>(sc1, lane, scales, last1);
          softmax_rows<0, 0, 2>(sc1, top1, last1, scales, pad, v_last + (A_V1 - A_V0), pa1, ov1);
        } else {
          wg_wait<0>();
          fence_regs(sc0);
          wg_fence();
          issue_s(sc1, &qa[12], desc_at(k_desc, A_K1));
          wg_commit();
          top0 = softmax_top<1>(sc0, lane, scales, last0);
          wg_wait<0>();
          fence_regs(sc1);
          softmax_rows<1, 12, 0>(sc0, top0, last0, scales, pad, v_last, pa0, ov0);
          mbar_wait(tail + T_FULL + ra, pa);
          wg_fence();
          issue_pv3(ov0, pa0, desc_at(v_desc, 0));
          wg_commit();
          issue_out<6>(x, oa, desc_at(w_desc, ra * (W_PART / 8)));
          wg_commit();
          top1 = softmax_top<1>(sc1, lane, scales, last1);
          wg_wait<1>();
          fence_regs(ov0);
          softmax_rows<1, 0, 2>(sc1, top1, last1, scales, pad, v_last + (A_V1 - A_V0), pa1, ov1);
        }
        wg_fence();
        issue_pv3(ov1, pa1, desc_at(v_desc, A_ONES - A_V0));
        wg_commit();
        wg_wait<1>();
        if (p == 0) fence_regs(ov0);
        else if (lead) mbar_arrive(tail + T_EMPTY + ra);
        {
          uint32_t big;
          asm("{\n.reg .pred p, q;\n.reg .b32 t;\nmax.xorsign.abs.f16x2 t, %1, %2;\nabs.f16x2 t, t;\nsetp.gt.f16x2 p|q, t, %3;\n"
              "or.pred p, p, q;\nselp.u32 %0, 1, 0, p;\n}" : "=r"(big) : "r"(top0), "r"(top1), "r"(0x60006000u));
          if (__any_sync(0xffffffffu, big) && lead) {
            scr->redo[blockIdx.x + gridDim.x * j] = 1;
            sts32(tail + T_ANY, 1u);
          }
          __syncwarp();
        }
        uint32_t (&o)[24] = (p == 0) ? oa : ob;
        pack_o<12, 0>(ov0, &o[0]);
        if (p == 1) {
          mbar_wait(tail + T_FULL + rb, pb);
          wg_fence();
          issue_out<3>(x, &ob[0], desc_at(w_desc, rb * (W_PART / 8)));
          wg_commit();
          wg_wait<1>();
          fence_regs(ov1);
          if (lead) mbar_arrive(bars + B_KVFREE);
          pack_o<0, 2>(ov1, &o[12]);
        }
      }
      wg_fence();
      issue_out<3>(x, &ob[12], desc_at(w_desc, rb * (W_PART / 8) + 3 * WO_STEP));
      wg_commit();
      mbar_wait(bars + B_KVFREE, 1);
      wg_wait<0>();
      fence_regs(x);
      if (lead) mbar_arrive(tail + T_EMPTY + rb);
      asm volatile("" : "+r"(o_st));
      if (full) {
#pragma unroll
        for (int s = 0; s < 12; s++)
          stsm4((o_st ^ (((s & 1) ^ out_flip(s >> 1)) << 5)) + out_group(s >> 1), f16x2_to_bf16x2(x[4 * s]), f16x2_to_bf16x2(x[4 * s + 1]),
                f16x2_to_bf16x2(x[4 * s + 2]), f16x2_to_bf16x2(x[4 * s + 3]));
        fence_async();
        warp_arrive(bars + B_OUTRDY, lead);
      } else {
#pragma unroll
        for (int i = 0; i < 24; i++)
          sts32_if(lane < 4, (o_st ^ (((i & 3) ^ (out_flip(i >> 2) << 1)) << 4)) + out_group(i >> 2), f16x2_to_bf16x2(x[2 * i]));
        fence_async();
        warp_arrive(bars + B_OUTRDY, lead);
      }
    }
    if (!full && lead && round > 0) send_output(3 * round + wg - 3, (round & 1) ^ 1);
    __syncwarp();
    if (3 * round < count) {
#pragma unroll 1
      for (uint32_t i = 0; i < 5; i++) {
        if (i % 3 == 0) {
          asm volatile("bar.sync %0, 256;" ::"r"(8 + wg) : "memory");
          asm volatile("bar.arrive %0, 256;" ::"r"(wg == 2 ? 8 : 9 + wg) : "memory");
        }
        const uint32_t u = 8 * round + i;
        mbar_wait(tail + T_FULL + 8 * (u % 3), (u / 3) & 1);
        if (lead) mbar_arrive(tail + T_EMPTY + 8 * (u % 3));
        __syncwarp();
      }
    }
    if (!full && lead) asm volatile("cp.async.bulk.wait_group 0;\nfence.proxy.async.global;" ::: "memory");
    __syncwarp();
    asm volatile("bar.sync 0, 512;" ::: "memory");
    const uint32_t redo_all = lds32(tail + T_ALL);
    if (redo_all | lds32(tail + T_ANY)) {
      const uint32_t t = fresh_tid(), c = t >> 7;
      const Windows win(split);
      for (uint32_t j = c; j < win.count; j += 3) {
        uint8_t* flag = &scr->redo[blockIdx.x + gridDim.x * j];
        if (!redo_all && !*reinterpret_cast<volatile uint8_t*>(flag)) continue;
        uint32_t col, row;
        win.at(j, col, row);
        redo_window(7 * col, 7 * row, t & 127, 1 + c, smem_raw + c * REDO_BYTES, x_raw, dw, wqkv_raw, wo_raw, out);
        if ((t & 127) == 0) *flag = 0;
      }
    }
  }
}

typedef CUresult (*EncodeTiledFn)(CUtensorMap*, CUtensorMapDataType, cuuint32_t, void*, const cuuint64_t*, const cuuint64_t*,
                                  const cuuint32_t*, const cuuint32_t*, CUtensorMapInterleave, CUtensorMapSwizzle,
                                  CUtensorMapL2promotion, CUtensorMapFloatOOBfill);

}

extern "C" void kernel_launch(void* const* d_in, const int* in_sizes, int n_in, void* d_out, int out_size) {
  (void)in_sizes; (void)n_in; (void)out_size;
  static EncodeTiledFn encode = nullptr;
  static int grid = 0;
  static void* scratch = nullptr;
  if (!encode) {
    void* fn = nullptr;
    cudaDriverEntryPointQueryResult st;
    cudaGetDriverEntryPoint("cuTensorMapEncodeTiled", &fn, cudaEnableDefault, &st);
    encode = (EncodeTiledFn)fn;
    cudaFuncSetAttribute(davit_window_attn_kernel, cudaFuncAttributeMaxDynamicSharedMemorySize, SMEM_BYTES);
    cudaGetSymbolAddress(&scratch, g_scratch);
    int dev = 0;
    cudaGetDevice(&dev);
    cudaDeviceGetAttribute(&grid, cudaDevAttrMultiProcessorCount, dev);
  }
  Split split = {};
  {
    const uint32_t g = grid, n = kNumWin / g;
    if (g > kWinPerCol && g <= 2 * kWinPerCol && kWinPerCol - n <= n) {
      const uint32_t below = (kWinPerCol - n) * kWinPerCol;
      split.top = kWinPerCol;
      split.rows = (below > (n + 1) * (g - kWinPerCol) && n + 1 < kWinPerCol) ? n + 1 : n;
      split.alone = kWinPerCol - split.rows;
    }
    const uint32_t others = g - split.top, rest = kNumWin - split.top * split.rows - others * split.alone;
    split.share = rest / others;
    split.fewer = others - rest % others;
    split.magic[0] = split.rows ? ((1u << 20) + split.rows - 1) / split.rows : 0;
    split.magic[1] = ((1u << 20) + kWinPerCol - split.rows - 1) / (kWinPerCol - split.rows);
  }
  auto image_map = [&](void* base, cuuint32_t c, cuuint32_t w, cuuint32_t h, CUtensorMapSwizzle swizzle) {
    CUtensorMap tm;
    const cuuint64_t dims[3] = {(cuuint64_t)kCh, (cuuint64_t)kImg, (cuuint64_t)kImg};
    const cuuint64_t strides[2] = {(cuuint64_t)kCh * 2, (cuuint64_t)kCh * 2 * kImg};
    const cuuint32_t box[3] = {c, w, h};
    const cuuint32_t estr[3] = {1, 1, 1};
    encode(&tm, CU_TENSOR_MAP_DATA_TYPE_BFLOAT16, 3, base, dims, strides, box, estr, CU_TENSOR_MAP_INTERLEAVE_NONE, swizzle,
           CU_TENSOR_MAP_L2_PROMOTION_L2_128B, CU_TENSOR_MAP_FLOAT_OOB_FILL_NONE);
    return tm;
  };
  auto weight_map = [&](void* base, cuuint64_t cols, cuuint32_t rows) {
    CUtensorMap tm;
    const cuuint64_t dims[2] = {cols, (cuuint64_t)kCh};
    const cuuint64_t strides[1] = {cols * 2};
    const cuuint32_t box[2] = {32, rows};
    const cuuint32_t estr[2] = {1, 1};
    encode(&tm, CU_TENSOR_MAP_DATA_TYPE_BFLOAT16, 2, base, dims, strides, box, estr, CU_TENSOR_MAP_INTERLEAVE_NONE,
           CU_TENSOR_MAP_SWIZZLE_64B, CU_TENSOR_MAP_L2_PROMOTION_L2_128B, CU_TENSOR_MAP_FLOAT_OOB_FILL_NONE);
    return tm;
  };
  davit_window_attn_kernel<<<grid, 512, SMEM_BYTES, cudaStreamPerThread>>>(
      image_map(d_in[0], 64, 9, 1, CU_TENSOR_MAP_SWIZZLE_NONE), image_map(d_in[0], 64, 9, 7, CU_TENSOR_MAP_SWIZZLE_NONE),
      image_map(d_in[0], 192, 9, 7, CU_TENSOR_MAP_SWIZZLE_NONE), image_map(d_out, 32, 7, 7, CU_TENSOR_MAP_SWIZZLE_64B),
      weight_map(d_in[2], 576, 192), weight_map(d_in[3], 192, 32),
      (const __nv_bfloat16*)d_in[1], (const __nv_bfloat16*)d_in[0], (const __nv_bfloat16*)d_in[2], (const __nv_bfloat16*)d_in[3],
      (__nv_bfloat16*)d_out, (Scratch*)scratch, split);
}
```

```cpp
#include <cuda.h>
#include <cuda_bf16.h>
#include <cuda_runtime.h>
#include <stdint.h>

namespace {

constexpr int kImg = 511;
constexpr int kCh = 192;
constexpr int kWinPerCol = 73;
constexpr int kNumWin = 73 * 73;

constexpr uint32_t W_PART = 36864;
constexpr uint32_t W_STEP = 3072;
constexpr uint32_t WO_STEP = 6144;
constexpr uint32_t W_BYTES = 8 * W_PART;

struct Scratch {
  uint8_t weights[W_BYTES];
  uint32_t ready;
  uint32_t passed;
  uint8_t redo[2 * kNumWin];
};
__device__ __align__(128) Scratch g_scratch;

constexpr uint32_t OFF_RING = 0;
constexpr uint32_t OFF_X0 = 3 * W_PART;
constexpr uint32_t kRows = 19;
constexpr uint32_t X0_ROW = 7 * 128;
constexpr uint32_t X0_CHUNK = kRows * X0_ROW;
constexpr uint32_t OFF_HALO = OFF_X0 + 3 * X0_CHUNK;
constexpr uint32_t HALO_ROW = 9 * 128;
constexpr uint32_t OFF_KV = OFF_HALO + 9 * HALO_ROW;
constexpr uint32_t K_CHUNK = 784;
constexpr uint32_t V_GROUP = 768;
constexpr uint32_t A_K0 = 0;
constexpr uint32_t A_V0 = 6 * K_CHUNK;
constexpr uint32_t A_ONES = A_V0 + 6 * V_GROUP;
constexpr uint32_t A_V1 = A_ONES + V_GROUP;
constexpr uint32_t A_K1 = A_V1 + 6 * V_GROUP;
constexpr uint32_t A_LAST = A_K1 + 6 * K_CHUNK;
constexpr uint32_t KV_SIZE = 19840;
constexpr uint32_t OUT_GROUP = 3328;
static_assert(A_LAST + 256 <= KV_SIZE && 5 * OUT_GROUP + 3136 <= KV_SIZE && KV_SIZE % 128 == 0 && 42 * HALO_ROW <= 3 * KV_SIZE &&
              21 * HALO_ROW >= KV_SIZE, "consumer area");
constexpr uint32_t OFF_TAIL = OFF_KV + 3 * KV_SIZE;
constexpr uint32_t SMEM_BYTES = OFF_TAIL + 352;
static_assert(SMEM_BYTES <= 232448, "shared memory");

constexpr uint32_t T_FULL = 0;
constexpr uint32_t T_EMPTY = 24;
constexpr uint32_t T_X0FULL = 48;
constexpr uint32_t T_X0FREE = 72;
constexpr uint32_t T_HALO = 88;
constexpr uint32_t T_WG = 160;
constexpr uint32_t B_KVRDY = 0;
constexpr uint32_t B_KVFREE = 8;
constexpr uint32_t B_OUTRDY = 16;
constexpr uint32_t B_OUTFREE = 24;
constexpr uint32_t T_RAW = 256;
constexpr uint32_t T_ZERO = 272;
constexpr uint32_t T_SCALE = 288;
constexpr uint32_t T_ALL = 292;
constexpr uint32_t T_ANY = 296;
constexpr uint32_t T_DUMP = 300;
constexpr uint32_t T_ROW = 304;

__device__ __forceinline__ void hmma_n96_first(uint32_t (&d)[24], uint32_t a0, uint32_t a1, uint32_t a2, uint32_t a3, uint64_t desc) {
  asm volatile("wgmma.mma_async.sync.aligned.m64n96k16.f16.f16.f16 "
               "{%0, %1, %2, %3, %4, %5, %6, %7, %8, %9, %10, %11, %12, %13, %14, %15, "
               "%16, %17, %18, %19, %20, %21, %22, %23}, "
               "{%24, %25, %26, %27}, %28, 0, 1, 1, 0;\n"
               : "=r"(d[0]), "=r"(d[1]), "=r"(d[2]), "=r"(d[3]), "=r"(d[4]), "=r"(d[5]), "=r"(d[6]), "=r"(d[7]),
                 "=r"(d[8]), "=r"(d[9]), "=r"(d[10]), "=r"(d[11]), "=r"(d[12]), "=r"(d[13]), "=r"(d[14]), "=r"(d[15]),
                 "=r"(d[16]), "=r"(d[17]), "=r"(d[18]), "=r"(d[19]), "=r"(d[20]), "=r"(d[21]), "=r"(d[22]), "=r"(d[23])
               : "r"(a0), "r"(a1), "r"(a2), "r"(a3), "l"(desc));
}
__device__ __forceinline__ void hmma_n96(uint32_t (&d)[24], uint32_t a0, uint32_t a1, uint32_t a2, uint32_t a3, uint64_t desc) {
  asm volatile("wgmma.mma_async.sync.aligned.m64n96k16.f16.f16.f16 "
               "{%0, %1, %2, %3, %4, %5, %6, %7, %8, %9, %10, %11, %12, %13, %14, %15, "
               "%16, %17, %18, %19, %20, %21, %22, %23}, "
               "{%24, %25, %26, %27}, %28, 1, 1, 1, 0;\n"
               : "+r"(d[0]), "+r"(d[1]), "+r"(d[2]), "+r"(d[3]), "+r"(d[4]), "+r"(d[5]), "+r"(d[6]), "+r"(d[7]),
                 "+r"(d[8]), "+r"(d[9]), "+r"(d[10]), "+r"(d[11]), "+r"(d[12]), "+r"(d[13]), "+r"(d[14]), "+r"(d[15]),
                 "+r"(d[16]), "+r"(d[17]), "+r"(d[18]), "+r"(d[19]), "+r"(d[20]), "+r"(d[21]), "+r"(d[22]), "+r"(d[23])
               : "r"(a0), "r"(a1), "r"(a2), "r"(a3), "l"(desc));
}
__device__ __forceinline__ void hmma_n96_over(uint32_t (&d)[24], uint32_t a0, uint32_t a1, uint32_t a2, uint32_t a3, uint64_t desc) {
  asm volatile("wgmma.mma_async.sync.aligned.m64n96k16.f16.f16.f16 "
               "{%0, %1, %2, %3, %4, %5, %6, %7, %8, %9, %10, %11, %12, %13, %14, %15, "
               "%16, %17, %18, %19, %20, %21, %22, %23}, "
               "{%24, %25, %26, %27}, %28, 0, 1, 1, 0;\n"
               : "+r"(d[0]), "+r"(d[1]), "+r"(d[2]), "+r"(d[3]), "+r"(d[4]), "+r"(d[5]), "+r"(d[6]), "+r"(d[7]),
                 "+r"(d[8]), "+r"(d[9]), "+r"(d[10]), "+r"(d[11]), "+r"(d[12]), "+r"(d[13]), "+r"(d[14]), "+r"(d[15]),
                 "+r"(d[16]), "+r"(d[17]), "+r"(d[18]), "+r"(d[19]), "+r"(d[20]), "+r"(d[21]), "+r"(d[22]), "+r"(d[23])
               : "r"(a0), "r"(a1), "r"(a2), "r"(a3), "l"(desc));
}
__device__ __forceinline__ void hmma_n56_first(uint32_t (&d)[14], uint32_t a0, uint32_t a1, uint32_t a2, uint32_t a3, uint64_t desc) {
  asm volatile("wgmma.mma_async.sync.aligned.m64n56k16.f16.f16.f16 "
               "{%0, %1, %2, %3, %4, %5, %6, %7, %8, %9, %10, %11, %12, %13}, "
               "{%14, %15, %16, %17}, %18, 0, 1, 1, 0;\n"
               : "=r"(d[0]), "=r"(d[1]), "=r"(d[2]), "=r"(d[3]), "=r"(d[4]), "=r"(d[5]), "=r"(d[6]), "=r"(d[7]),
                 "=r"(d[8]), "=r"(d[9]), "=r"(d[10]), "=r"(d[11]), "=r"(d[12]), "=r"(d[13])
               : "r"(a0), "r"(a1), "r"(a2), "r"(a3), "l"(desc));
}
__device__ __forceinline__ void hmma_n56(uint32_t (&d)[14], uint32_t a0, uint32_t a1, uint32_t a2, uint32_t a3, uint64_t desc) {
  asm volatile("wgmma.mma_async.sync.aligned.m64n56k16.f16.f16.f16 "
               "{%0, %1, %2, %3, %4, %5, %6, %7, %8, %9, %10, %11, %12, %13}, "
               "{%14, %15, %16, %17}, %18, 1, 1, 1, 0;\n"
               : "+r"(d[0]), "+r"(d[1]), "+r"(d[2]), "+r"(d[3]), "+r"(d[4]), "+r"(d[5]), "+r"(d[6]), "+r"(d[7]),
                 "+r"(d[8]), "+r"(d[9]), "+r"(d[10]), "+r"(d[11]), "+r"(d[12]), "+r"(d[13])
               : "r"(a0), "r"(a1), "r"(a2), "r"(a3), "l"(desc));
}
__device__ __forceinline__ void hmma_n192(uint32_t (&d)[48], uint32_t a0, uint32_t a1, uint32_t a2, uint32_t a3, uint64_t desc) {
  asm volatile("wgmma.mma_async.sync.aligned.m64n192k16.f16.f16.f16 "
               "{%0, %1, %2, %3, %4, %5, %6, %7, %8, %9, %10, %11, %12, %13, %14, %15, "
               "%16, %17, %18, %19, %20, %21, %22, %23, %24, %25, %26, %27, %28, %29, %30, %31, "
               "%32, %33, %34, %35, %36, %37, %38, %39, %40, %41, %42, %43, %44, %45, %46, %47}, "
               "{%48, %49, %50, %51}, %52, 1, 1, 1, 0;\n"
               : "+r"(d[0]), "+r"(d[1]), "+r"(d[2]), "+r"(d[3]), "+r"(d[4]), "+r"(d[5]), "+r"(d[6]), "+r"(d[7]),
                 "+r"(d[8]), "+r"(d[9]), "+r"(d[10]), "+r"(d[11]), "+r"(d[12]), "+r"(d[13]), "+r"(d[14]), "+r"(d[15]),
                 "+r"(d[16]), "+r"(d[17]), "+r"(d[18]), "+r"(d[19]), "+r"(d[20]), "+r"(d[21]), "+r"(d[22]), "+r"(d[23]),
                 "+r"(d[24]), "+r"(d[25]), "+r"(d[26]), "+r"(d[27]), "+r"(d[28]), "+r"(d[29]), "+r"(d[30]), "+r"(d[31]),
                 "+r"(d[32]), "+r"(d[33]), "+r"(d[34]), "+r"(d[35]), "+r"(d[36]), "+r"(d[37]), "+r"(d[38]), "+r"(d[39]),
                 "+r"(d[40]), "+r"(d[41]), "+r"(d[42]), "+r"(d[43]), "+r"(d[44]), "+r"(d[45]), "+r"(d[46]), "+r"(d[47])
               : "r"(a0), "r"(a1), "r"(a2), "r"(a3), "l"(desc));
}

__device__ __forceinline__ void wg_fence() { asm volatile("wgmma.fence.sync.aligned;\n" ::: "memory"); }
__device__ __forceinline__ void wg_commit() { asm volatile("wgmma.commit_group.sync.aligned;\n" ::: "memory"); }
template <int N> __device__ __forceinline__ void wg_wait() { asm volatile("wgmma.wait_group.sync.aligned %0;\n" ::"n"(N) : "memory"); }
__device__ __forceinline__ uint64_t make_desc(uint32_t addr, uint32_t lbo, uint32_t sbo) {
  return (uint64_t)((addr & 0x3FFFF) >> 4) | ((uint64_t)(lbo >> 4) << 16) | ((uint64_t)(sbo >> 4) << 32);
}
__device__ __forceinline__ uint64_t desc_add(uint64_t d, uint32_t bytes) { return d + (bytes >> 4); }
__device__ __forceinline__ uint64_t desc_at(uint64_t d, uint32_t bytes) {
  uint64_t r;
  asm volatile("mov.b64 %0, %1;" : "=l"(r) : "l"(d));
  return desc_add(r, bytes);
}

__device__ __forceinline__ void mbar_init(uint32_t bar, uint32_t count) {
  asm volatile("mbarrier.init.shared::cta.b64 [%0], %1;" ::"r"(bar), "r"(count) : "memory");
}
__device__ __forceinline__ void mbar_expect_tx(uint32_t bar, uint32_t bytes) {
  asm volatile("mbarrier.arrive.expect_tx.shared::cta.b64 _, [%0], %1;" ::"r"(bar), "r"(bytes) : "memory");
}
__device__ __forceinline__ void mbar_wait(uint32_t bar, uint32_t parity) {
  asm volatile("{\n.reg .pred p;\n.reg .u32 c;\n"
               "mbarrier.try_wait.parity.shared::cta.b64 p, [%0], %1;\n"
               "@p bra DONE;\n"
               "mov.u32 c, 0;\n"
               "SPIN:\n"
               "mbarrier.try_wait.parity.shared::cta.b64 p, [%0], %1, 4000;\n"
               "@p bra DONE;\n"
               "add.u32 c, c, 1;\n"
               "setp.lt.u32 p, c, 1048576;\n"
               "@!p trap;\n"
               "bra SPIN;\n"
               "DONE:\n}" ::"r"(bar), "r"(parity) : "memory");
}
__device__ __forceinline__ void bar_sync(uint32_t id) { asm volatile("bar.sync %0, 128;" ::"r"(id) : "memory"); }
__device__ __forceinline__ void mbar_arrive(uint32_t bar) { asm volatile("mbarrier.arrive.shared::cta.b64 _, [%0];" ::"r"(bar) : "memory"); }
__device__ __forceinline__ void warp_arrive(uint32_t bar, bool first) {
  __syncwarp();
  if (first) mbar_arrive(bar);
}
__device__ __forceinline__ void arrive_elected(uint32_t bar) {
  asm volatile("{\n.reg .pred p;\nelect.sync _|p, 0xffffffff;\n@p mbarrier.arrive.shared::cta.b64 _, [%0];\n}" ::"r"(bar) : "memory");
}
__device__ __forceinline__ void fence_async() { asm volatile("fence.proxy.async.shared::cta;" ::: "memory"); }
__device__ __forceinline__ uint32_t lds32(uint32_t a) {
  uint32_t v;
  asm volatile("ld.shared.b32 %0, [%1];" : "=r"(v) : "r"(a) : "memory");
  return v;
}
__device__ __forceinline__ void lds64(uint32_t a, uint32_t& v0, uint32_t& v1) {
  asm volatile("ld.shared.v2.b32 {%0, %1}, [%2];" : "=r"(v0), "=r"(v1) : "r"(a) : "memory");
}
__device__ __forceinline__ void sts32(uint32_t a, uint32_t v) { asm volatile("st.shared.b32 [%0], %1;" ::"r"(a), "r"(v) : "memory"); }
__device__ __forceinline__ void sts64(uint32_t a, uint32_t v0, uint32_t v1) {
  asm volatile("st.shared.v2.b32 [%0], {%1, %2};" ::"r"(a), "r"(v0), "r"(v1) : "memory");
}
__device__ __forceinline__ void sts32_if(bool on, uint32_t a, uint32_t v) {
  asm volatile("{\n.reg .pred p;\nsetp.ne.u32 p, %2, 0;\n@p st.shared.b32 [%0], %1;\n}" ::"r"(a), "r"(v), "r"((uint32_t)on) : "memory");
}
__device__ __forceinline__ void ldsm4(uint32_t a, uint32_t& r0, uint32_t& r1, uint32_t& r2, uint32_t& r3) {
  asm volatile("ldmatrix.sync.aligned.m8n8.x4.shared.b16 {%0, %1, %2, %3}, [%4];" : "=r"(r0), "=r"(r1), "=r"(r2), "=r"(r3) : "r"(a) : "memory");
}
__device__ __forceinline__ void stsm4(uint32_t a, uint32_t r0, uint32_t r1, uint32_t r2, uint32_t r3) {
  asm volatile("stmatrix.sync.aligned.m8n8.x4.shared.b16 [%0], {%1, %2, %3, %4};" ::"r"(a), "r"(r0), "r"(r1), "r"(r2), "r"(r3) : "memory");
}
__device__ __forceinline__ void stsm4_t(uint32_t a, uint32_t r0, uint32_t r1, uint32_t r2, uint32_t r3) {
  asm volatile("stmatrix.sync.aligned.m8n8.x4.trans.shared.b16 [%0], {%1, %2, %3, %4};" ::"r"(a), "r"(r0), "r"(r1), "r"(r2), "r"(r3) : "memory");
}
__device__ __forceinline__ uint32_t pack_bf16(float lo, float hi) {
  uint32_t r;
  asm("cvt.rn.bf16x2.f32 %0, %1, %2;" : "=r"(r) : "f"(hi), "f"(lo));
  return r;
}
__device__ __forceinline__ uint32_t pack_f16(float lo, float hi) {
  uint32_t r;
  asm("cvt.rn.f16x2.f32 %0, %1, %2;" : "=r"(r) : "f"(hi), "f"(lo));
  return r;
}
__device__ __forceinline__ float bf_lo(uint32_t v) { return __uint_as_float(v << 16); }
__device__ __forceinline__ float bf_hi(uint32_t v) { return __uint_as_float(v & 0xffff0000u); }
__device__ __forceinline__ float h_lo(uint32_t v) {
  float r;
  asm("{\n.reg .b16 l, h;\nmov.b32 {l, h}, %1;\ncvt.f32.f16 %0, l;\n}" : "=f"(r) : "r"(v));
  return r;
}
__device__ __forceinline__ float h_hi(uint32_t v) {
  float r;
  asm("{\n.reg .b16 l, h;\nmov.b32 {l, h}, %1;\ncvt.f32.f16 %0, h;\n}" : "=f"(r) : "r"(v));
  return r;
}
__device__ __forceinline__ uint32_t bf16x2_to_f16x2(uint32_t v) { return pack_f16(bf_lo(v), bf_hi(v)); }
__device__ __forceinline__ uint32_t f16x2_to_bf16x2(uint32_t v) { return pack_bf16(h_lo(v), h_hi(v)); }
__device__ __forceinline__ uint32_t bmul2(uint32_t a, uint32_t b) {
  uint32_t r;
  asm("mul.rn.bf16x2 %0, %1, %2;" : "=r"(r) : "r"(a), "r"(b));
  return r;
}
__device__ __forceinline__ uint32_t badd2(uint32_t a, uint32_t b) {
  uint32_t r;
  asm("add.rn.bf16x2 %0, %1, %2;" : "=r"(r) : "r"(a), "r"(b));
  return r;
}
__device__ __forceinline__ uint32_t bfma2(uint32_t a, uint32_t b, uint32_t c) {
  uint32_t r;
  asm("fma.rn.bf16x2 %0, %1, %2, %3;" : "=r"(r) : "r"(a), "r"(b), "r"(c));
  return r;
}
__device__ __forceinline__ uint32_t hadd2(uint32_t a, uint32_t b) {
  uint32_t d;
  asm("add.rn.f16x2 %0, %1, %2;" : "=r"(d) : "r"(a), "r"(b));
  return d;
}
__device__ __forceinline__ uint32_t hmax2(uint32_t a, uint32_t b) {
  uint32_t d;
  asm("max.f16x2 %0, %1, %2;" : "=r"(d) : "r"(a), "r"(b));
  return d;
}
__device__ __forceinline__ uint32_t hmul2(uint32_t a, uint32_t b) {
  uint32_t d;
  asm("mul.rn.f16x2 %0, %1, %2;" : "=r"(d) : "r"(a), "r"(b));
  return d;
}
__device__ __forceinline__ uint32_t hmul2_lo(uint32_t a, uint32_t r) {
  uint32_t d;
  asm("{\n.reg .b16 l, h;\n.reg .b32 t;\nmov.b32 {l, h}, %2;\nmov.b32 t, {l, l};\nmul.rn.f16x2 %0, %1, t;\n}" : "=r"(d) : "r"(a), "r"(r));
  return d;
}
__device__ __forceinline__ uint32_t hmul2_hi(uint32_t a, uint32_t r) {
  uint32_t d;
  asm("{\n.reg .b16 l, h;\n.reg .b32 t;\nmov.b32 {l, h}, %2;\nmov.b32 t, {h, h};\nmul.rn.f16x2 %0, %1, t;\n}" : "=r"(d) : "r"(a), "r"(r));
  return d;
}
__device__ __forceinline__ float rcp(float x) {
  float r;
  asm("rcp.approx.ftz.f32 %0, %1;" : "=f"(r) : "f"(x));
  return r;
}
__device__ __forceinline__ float rsqrt_fast(float x) {
  float r;
  asm("rsqrt.approx.ftz.f32 %0, %1;" : "=f"(r) : "f"(x));
  return r;
}
template <int N> __device__ __forceinline__ void fence_regs(uint32_t (&d)[N]) {
#pragma unroll
  for (int i = 0; i < N; i++) asm volatile("" : "+r"(d[i])::"memory");
}

__device__ __forceinline__ void row_stats(const uint32_t (&x)[48], bool odd, float& sum, float& squares) {
  float s0 = 0.f, q0 = 0.f, s1 = 0.f, q1 = 0.f;
#pragma unroll
  for (int i = 0; i < 48; i++) {
    const float lo = h_lo(x[i]), hi = h_hi(x[i]);
    if (i & 1) {
      s1 += lo; q1 = fmaf(lo, lo, q1);
      s1 += hi; q1 = fmaf(hi, hi, q1);
    } else {
      s0 += lo; q0 = fmaf(lo, lo, q0);
      s0 += hi; q0 = fmaf(hi, hi, q0);
    }
  }
  sum = (odd ? s1 : s0) + __shfl_xor_sync(0xffffffffu, odd ? s0 : s1, 1);
  squares = (odd ? q1 : q0) + __shfl_xor_sync(0xffffffffu, odd ? q0 : q1, 1);
  sum += __shfl_xor_sync(0xffffffffu, sum, 2);
  squares += __shfl_xor_sync(0xffffffffu, squares, 2);
}
__device__ __forceinline__ void lane_stats_packed(const uint32_t (&x)[48], uint32_t (&t)[2]) {
  uint32_t s[4] = {x[0], x[1], x[2], x[3]}, q[4];
#pragma unroll
  for (int r = 0; r < 4; r++) q[r] = hmul2(x[r], x[r]);
#pragma unroll
  for (int i = 4; i < 48; i++) {
    asm("add.rn.f16x2 %0, %0, %1;" : "+r"(s[i & 3]) : "r"(x[i]));
    asm("fma.rn.f16x2 %0, %1, %1, %0;" : "+r"(q[i & 3]) : "r"(x[i]));
  }
#pragma unroll
  for (int r = 0; r < 2; r++) {
    const uint32_t a = hadd2(s[r], s[r + 2]), b = hadd2(q[r], q[r + 2]);
    t[r] = hadd2(__byte_perm(a, b, 0x5410), __byte_perm(a, b, 0x7632));
  }
}
__device__ __forceinline__ uint32_t quad_stats_packed(const uint32_t (&t)[2], bool odd) {
  const uint32_t u = hadd2(__shfl_xor_sync(0xffffffffu, odd ? t[0] : t[1], 1), odd ? t[1] : t[0]);
  return hadd2(u, __shfl_xor_sync(0xffffffffu, u, 2));
}

__device__ __forceinline__ void store_k(const uint32_t (&k)[24], uint32_t k_st, bool full, bool first_row, uint32_t r) {
  if (full) {
#pragma unroll
    for (int j = 0; j < 12; j += 2)
      stsm4(k_st + (j / 6) * A_K1 + (j % 6) * K_CHUNK, hmul2_lo(k[2 * j], r), hmul2_hi(k[2 * j + 1], r), hmul2_lo(k[2 * j + 2], r),
            hmul2_hi(k[2 * j + 3], r));
  } else {
#pragma unroll
    for (int j = 0; j < 12; j++) sts32_if(first_row, k_st + (j / 6) * A_K1 + (j % 6) * K_CHUNK, hmul2_lo(k[2 * j], r));
    __syncwarp();
  }
}
template <int HALF> __device__ __forceinline__ uint32_t both(uint32_t v) {
  uint32_t d;
  if (HALF == 0) asm("{\n.reg .b16 l, h;\nmov.b32 {l, h}, %1;\nmov.b32 %0, {l, l};\n}" : "=r"(d) : "r"(v));
  else asm("{\n.reg .b16 l, h;\nmov.b32 {l, h}, %1;\nmov.b32 %0, {h, h};\n}" : "=r"(d) : "r"(v));
  return d;
}
__device__ __forceinline__ uint32_t exp2_scaled(uint32_t s, uint32_t c, uint32_t off) {
  uint32_t d;
  asm("{\n.reg .b32 t;\nfma.rn.f16x2 t, %1, %2, %3;\nex2.approx.f16x2 %0, t;\n}" : "=r"(d) : "r"(s), "r"(c), "r"(off));
  return d;
}
__device__ __forceinline__ uint32_t softmax_top(const uint32_t (&s)[14], uint32_t lane, uint32_t c, uint32_t& last) {
  last = __shfl_sync(0xffffffffu, __byte_perm(s[12], s[13], 0x5410), lane & 28);
  const uint32_t a = hmax2(hmax2(hmax2(s[0], s[2]), s[4]), hmax2(hmax2(s[6], s[8]), s[10]));
  const uint32_t b = hmax2(hmax2(hmax2(s[1], s[3]), s[5]), hmax2(hmax2(s[7], s[9]), s[11]));
  uint32_t m = hmax2(__byte_perm(a, b, 0x5410), __byte_perm(a, b, 0x7632));
  m = hmax2(m, __shfl_xor_sync(0xffffffffu, m, 1));
  m = hmax2(hmax2(m, last), __shfl_xor_sync(0xffffffffu, m, 2));
  return hmul2(m, c);
}
__device__ __forceinline__ void lds128(uint32_t a, uint32_t* v) {
  asm volatile("ld.shared.v4.b32 {%0, %1, %2, %3}, [%4];" : "=r"(v[0]), "=r"(v[1]), "=r"(v[2]), "=r"(v[3]) : "r"(a) : "memory");
}
template <int SUM, int VAL>
__device__ __forceinline__ void softmax_rows(const uint32_t (&s)[14], uint32_t top, uint32_t last, uint32_t c, uint32_t pad,
                                             uint32_t v_last, uint32_t (&pa)[12], uint32_t (&ov)[14]) {
  uint32_t off, v[6];
  lds128(v_last, v);
  lds64(v_last + 16, v[4], v[5]);
  asm("sub.rn.f16x2 %0, %1, %2;" : "=r"(off) : "r"(pad), "r"(top));
#pragma unroll
  for (int j = 0; j < 6; j++) {
    pa[2 * j] = exp2_scaled(s[2 * j], both<0>(c), both<0>(off));
    pa[2 * j + 1] = exp2_scaled(s[2 * j + 1], both<1>(c), both<1>(off));
  }
  const uint32_t p = exp2_scaled(last, c, off);
#pragma unroll
  for (int j = 0; j < 6; j++) {
    ov[VAL + 2 * j] = hmul2_lo(v[j], p);
    ov[VAL + 2 * j + 1] = hmul2_hi(v[j], p);
  }
  ov[SUM] = __byte_perm(p, p, 0x1010);
  ov[SUM + 1] = __byte_perm(p, p, 0x3232);
}
__device__ __forceinline__ void issue_pv(uint32_t (&ov)[14], const uint32_t (&pa)[12], uint64_t v_desc) {
#pragma unroll
  for (int k = 0; k < 3; k++) hmma_n56(ov, pa[4 * k], pa[4 * k + 1], pa[4 * k + 2], pa[4 * k + 3], desc_add(v_desc, k * 256));
}
__device__ __forceinline__ void sts128_if(bool on, uint32_t a, uint32_t v0, uint32_t v1, uint32_t v2, uint32_t v3) {
  asm volatile("{\n.reg .pred p;\nsetp.ne.u32 p, %5, 0;\n@p st.shared.v4.b32 [%0], {%1, %2, %3, %4};\n}"
               ::"r"(a), "r"(v0), "r"(v1), "r"(v2), "r"(v3), "r"((uint32_t)on) : "memory");
}
__device__ __forceinline__ void store_v(const uint32_t (&v)[24], uint32_t v_st, uint32_t v_last, bool full, bool first_row, uint32_t r) {
  if (full) {
#pragma unroll
    for (int j = 0; j < 12; j += 2)
      stsm4_t(v_st + (j / 6) * (A_V1 - A_V0) + (j % 6) * V_GROUP, hmul2_lo(v[2 * j], r), hmul2_hi(v[2 * j + 1], r), hmul2_lo(v[2 * j + 2], r),
              hmul2_hi(v[2 * j + 3], r));
  } else {
#pragma unroll
    for (int h = 0; h < 2; h++) {
      sts128_if(first_row, v_last + h * 128, hmul2_lo(v[12 * h], r), hmul2_lo(v[12 * h + 2], r), hmul2_lo(v[12 * h + 4], r),
                hmul2_lo(v[12 * h + 6], r));
      sts128_if(first_row, v_last + h * 128 + 16, hmul2_lo(v[12 * h + 8], r), hmul2_lo(v[12 * h + 10], r), 0u, 0u);
    }
    __syncwarp();
  }
}
__device__ __forceinline__ void issue_s(uint32_t (&s)[14], const uint32_t* qa, uint64_t k_desc) {
  hmma_n56_first(s, qa[0], qa[1], qa[2], qa[3], k_desc);
#pragma unroll
  for (int k = 1; k < 3; k++) hmma_n56(s, qa[4 * k], qa[4 * k + 1], qa[4 * k + 2], qa[4 * k + 3], desc_add(k_desc, k * 2 * K_CHUNK));
}
template <int SUM, int VAL>
__device__ __forceinline__ void pack_o(const uint32_t (&ov)[14], uint32_t* o) {
  const uint32_t p = pack_f16(rcp(fmaxf(h_lo(ov[SUM]), 0.5f)), rcp(fmaxf(h_lo(ov[SUM + 1]), 0.5f)));
#pragma unroll
  for (int j = 0; j < 6; j++) {
    o[2 * j] = hmul2_lo(ov[VAL + 2 * j], p);
    o[2 * j + 1] = hmul2_hi(ov[VAL + 2 * j + 1], p);
  }
}
template <bool OVER>
__device__ __forceinline__ void issue_proj(uint32_t (&d)[24], const uint32_t (&x)[48], uint64_t desc) {
  if (OVER) hmma_n96_over(d, x[0], x[1], x[2], x[3], desc);
  else hmma_n96_first(d, x[0], x[1], x[2], x[3], desc);
#pragma unroll
  for (int s = 1; s < 12; s++) hmma_n96(d, x[4 * s], x[4 * s + 1], x[4 * s + 2], x[4 * s + 3], desc_add(desc, s * W_STEP));
}
template <int FIRST>
__device__ __forceinline__ void issue_half(uint32_t (&d)[24], const uint32_t (&x)[48], uint64_t desc) {
  if (FIRST == 2) hmma_n96_over(d, x[0], x[1], x[2], x[3], desc);
  if (FIRST == 1) hmma_n96_first(d, x[0], x[1], x[2], x[3], desc);
#pragma unroll
  for (int s = FIRST ? 1 : 6; s < (FIRST ? 6 : 12); s++) hmma_n96(d, x[4 * s], x[4 * s + 1], x[4 * s + 2], x[4 * s + 3], desc_add(desc, s * W_STEP));
}
template <int N>
__device__ __forceinline__ void issue_out(uint32_t (&d)[48], const uint32_t* o, uint64_t desc) {
#pragma unroll
  for (int s = 0; s < N; s++) hmma_n192(d, o[4 * s], o[4 * s + 1], o[4 * s + 2], o[4 * s + 3], desc_add(desc, s * WO_STEP));
}

__device__ __forceinline__ void mma_bf16(float (&c)[4], uint32_t a0, uint32_t a1, uint32_t a2, uint32_t a3, uint32_t b0, uint32_t b1) {
  asm("mma.sync.aligned.m16n8k16.row.col.f32.bf16.bf16.f32 {%0, %1, %2, %3}, {%4, %5, %6, %7}, {%8, %9}, {%0, %1, %2, %3};"
      : "+f"(c[0]), "+f"(c[1]), "+f"(c[2]), "+f"(c[3]) : "r"(a0), "r"(a1), "r"(a2), "r"(a3), "r"(b0), "r"(b1));
}
__device__ __forceinline__ void mma_bf16_k8(float (&d)[4], uint32_t a0, uint32_t a1, uint32_t b, const float (&c)[4]) {
  asm("mma.sync.aligned.m16n8k8.row.col.f32.bf16.bf16.f32 {%0, %1, %2, %3}, {%4, %5}, {%6}, {%7, %8, %9, %10};"
      : "=f"(d[0]), "=f"(d[1]), "=f"(d[2]), "=f"(d[3]) : "r"(a0), "r"(a1), "r"(b), "f"(c[0]), "f"(c[1]), "f"(c[2]), "f"(c[3]));
}
__device__ __forceinline__ bool on_diagonal(uint32_t lane) { return (lane & 3) == (lane >> 3); }
__device__ __forceinline__ float column_stats(const uint32_t (&v)[24], uint32_t lane, uint32_t& hi, uint32_t& lo) {
  float sum[2][4] = {}, sq[2][4] = {}, sr[2][4] = {};
#pragma unroll
  for (int c = 0; c < 24; c += 4) mma_bf16(sum[(c >> 2) & 1], v[c], v[c + 1], v[c + 2], v[c + 3], 0x3F803F80u, 0x3F803F80u);
#pragma unroll
  for (int c = 0; c < 24; c += 2) {
    mma_bf16_k8(sq[(c >> 1) & 1], v[c], v[c + 1], v[c], sq[(c >> 1) & 1]);
    mma_bf16_k8(sr[(c >> 1) & 1], v[c], v[c + 1], v[c + 1], sr[(c >> 1) & 1]);
  }
  const float total = (sum[0][0] + sum[0][2]) + (sum[1][0] + sum[1][2]), mean = total * (1.f / 192.f);
  const bool diag = on_diagonal(lane);
  const float n2 = (lane & 4) ? (sq[0][1] + sq[1][1]) + (sr[0][3] + sr[1][3]) : (sq[0][0] + sq[1][0]) + (sr[0][2] + sr[1][2]);
  hi = diag ? __float_as_uint(n2) : 0u;
  lo = __float_as_uint((diag && n2 > 0.f) ? fmaxf(fmaf(-total, mean, n2), 0.f) : INFINITY);
  return mean;
}
__device__ __forceinline__ uint32_t warp_max_abs(const uint32_t (&v)[8]) {
  uint32_t m = v[0];
#pragma unroll
  for (int c = 1; c < 8; c++) asm("max.NaN.xorsign.abs.bf16x2 %0, %0, %1;" : "+r"(m) : "r"(v[c]));
  return __reduce_max_sync(0xffffffffu, max(m & 0x7fffu, (m >> 16) & 0x7fffu));
}
__device__ __forceinline__ bool norms_in_range(uint32_t hi, uint32_t lo) {
  return hi - 0x08800000u <= 0x7B000000u - 0x08800000u && lo >= hi - (12u << 23);
}
__device__ __forceinline__ int norm_exponent(uint32_t n2) { return (int)(0x453B8000u - n2) >> 24; }
__device__ __forceinline__ void scale_to_f16(uint32_t (&v)[8], uint32_t lane, int e, float mean) {
  const uint32_t ident = on_diagonal(lane) ? (uint32_t)(e + 127) << ((lane & 4) ? 23 : 7) : 0u;
  const float c0 = -mean * __uint_as_float((uint32_t)(e + 127) << 23), c[4] = {c0, c0, c0, c0};
#pragma unroll
  for (int i = 0; i < 8; i += 2) {
    float d[4];
    mma_bf16_k8(d, v[i], v[i + 1], ident, c);
    v[i] = pack_f16(d[0], d[1]);
    v[i + 1] = pack_f16(d[2], d[3]);
  }
}
__device__ __forceinline__ float pow2(int e) { return __uint_as_float((uint32_t)(min(max(e, -126), 127) + 127) << 23); }

constexpr uint32_t kUnits = 24;
constexpr uint32_t RAW_O = W_PART, RAW_RED = RAW_O + 32 * 384;
__device__ __forceinline__ void bulk_load(uint32_t dst, const void* src, uint32_t bytes, uint32_t bar) {
  asm volatile("cp.async.bulk.shared::cluster.global.mbarrier::complete_tx::bytes [%0], [%1], %2, [%3];"
               ::"r"(dst), "l"(src), "r"(bytes), "r"(bar) : "memory");
}
__device__ __forceinline__ void tile_load(uint32_t dst, const CUtensorMap* tm, uint32_t c0, uint32_t c1, uint32_t bar) {
  asm volatile("cp.async.bulk.tensor.2d.shared::cluster.global.tile.mbarrier::complete_tx::bytes [%0], [%1, {%2, %3}], [%4];"
               ::"r"(dst), "l"(tm), "r"(c0), "r"(c1), "r"(bar) : "memory");
}
__device__ __forceinline__ void request_unit(uint32_t u, uint32_t raw, uint32_t bar, const CUtensorMap* tmw, const CUtensorMap* tmwo) {
  const bool is_o = (u & 7) >= 6;
  const uint32_t pair = is_o ? u & 1 : (u & 7) / 3, part = is_o ? 1 : (u & 7) % 3;
  mbar_expect_tx(bar, is_o ? W_PART + 32 * 384 : W_PART);
#pragma unroll
  for (uint32_t i = 0; i < 3; i++) tile_load(raw + i * (192 * 64), tmw, ((part + 1) % 3) * 192 + pair * 96 + 32 * i, 0, bar);
  if (is_o) {
#pragma unroll
    for (uint32_t i = 0; i < 6; i++) tile_load(raw + RAW_O + i * (32 * 64), tmwo, 32 * i, pair * 96 + (u >> 3) * 32, bar);
  }
}
__device__ __forceinline__ void ldsm4_t(uint32_t a, uint32_t* v) {
  asm volatile("ldmatrix.sync.aligned.m8n8.x4.trans.shared.b16 {%0, %1, %2, %3}, [%4];" : "=r"(v[0]), "=r"(v[1]), "=r"(v[2]), "=r"(v[3]) : "r"(a) : "memory");
}
__device__ __forceinline__ void prepare_unit(uint32_t u, uint32_t wid, uint32_t lane, uint32_t raw, Scratch* scr) {
  const bool is_o = (u & 7) >= 6;
  const uint32_t third = u >> 3;
  uint32_t v[24], w[8];
  const uint32_t src = raw + (wid >> 2) * (192 * 64) + lane * 64 + (((wid ^ (lane >> 1)) & 3) << 4);
#pragma unroll
  for (int m = 0; m < 6; m++) ldsm4_t(src + m * (32 * 64), &v[4 * m]);
  uint32_t hi, lo, top = 0;
  const float mean = column_stats(v, lane, hi, lo);
  if (is_o) {
#pragma unroll
    for (int m = 0; m < 2; m++)
      ldsm4_t(raw + RAW_O + (wid >> 1) * (32 * 64) + lane * 64 + ((((2 * wid + m) ^ (lane >> 1)) & 3) << 4), &w[4 * m]);
    top = warp_max_abs(w);
  } else {
#pragma unroll
    for (int m = 0; m < 2; m++) ldsm4_t(src + (2 * third + m) * (32 * 64), &w[4 * m]);
  }
  hi = __reduce_max_sync(0xffffffffu, hi);
  lo = __reduce_min_sync(0xffffffffu, lo);
  if (lane == 0) {
    sts64(raw + RAW_RED + wid * 16, hi, lo);
    sts32(raw + RAW_RED + wid * 16 + 8, top);
  }
  asm volatile("bar.sync 4, 384;" ::: "memory");
  lds64(raw + RAW_RED + (lane % 12) * 16, hi, lo);
  top = lds32(raw + RAW_RED + (lane % 12) * 16 + 8);
  hi = __reduce_max_sync(0xffffffffu, hi);
  lo = __reduce_min_sync(0xffffffffu, lo);
  top = __reduce_max_sync(0xffffffffu, top);
  const int e = norm_exponent(hi);
  scale_to_f16(w, lane, is_o ? -e : e - 4, is_o ? 0.f : mean);
  const uint32_t mat = lane >> 3, at = (mat & 1) * 128 + (lane & 7) * 16;
#pragma unroll
  for (int m = 0; m < 2; m++)
    stsm4(raw + at + (is_o ? (mat >> 1) * WO_STEP + (2 * wid + m) * 256 : (2 * m + (mat >> 1)) * W_STEP + wid * 256), w[4 * m], w[4 * m + 1],
          w[4 * m + 2], w[4 * m + 3]);
  fence_async();
  asm volatile("bar.sync 4, 384;" ::: "memory");
  if (wid == 0 && lane == 0) {
    asm volatile("cp.async.bulk.global.shared::cta.bulk_group [%0], [%1], %2;\ncp.async.bulk.commit_group;"
                 ::"l"(scr->weights + (u & 7) * W_PART + third * (W_PART / 3)), "r"(raw), "n"(W_PART / 3) : "memory");
    const bool bad = is_o ? !(__uint_as_float(top << 16) * pow2(-e) <= 0.25f) : !norms_in_range(hi, lo);
    const uint32_t exponent = (!is_o && third == 0 && u % 3 != 1) ? (uint32_t)(e + 64) << (u < 3 ? 10 : 19) : 0u;
    asm volatile("cp.async.bulk.wait_group 0;" ::: "memory");
    asm volatile("red.relaxed.gpu.global.add.u32 [%0], %1;" ::"l"(&scr->ready), "r"(bad ? 33u : 1u + exponent) : "memory");
  }
  __syncwarp();
}

constexpr uint32_t REDO_BYTES = 75776;
static_assert(3 * REDO_BYTES <= OFF_TAIL && (3 * 49 * 192 + 49 * 144) * 2 <= REDO_BYTES, "redo scratch");
__device__ __forceinline__ float round_bf16(float x) { return __bfloat162float(__float2bfloat16(x)); }
__device__ __forceinline__ void redo_window(int c0, int y0, int t, uint32_t bar, uint8_t* scratch, const __nv_bfloat16* x,
                                            const __nv_bfloat16* dw, const __nv_bfloat16* wqkv, const __nv_bfloat16* wo,
                                            __nv_bfloat16* out) {
  __nv_bfloat16* x0 = reinterpret_cast<__nv_bfloat16*>(scratch);
  __nv_bfloat16* h = x0 + 49 * 192;
  __nv_bfloat16* o = h + 49 * 192;
  __nv_bfloat16* qkv = o + 49 * 192;
  bar_sync(bar);
#pragma unroll 1
  for (int i = t; i < 49 * 192; i += 128) {
    const int tok = i / 192, c = i % 192, y = y0 + tok / 7, xx = c0 + tok % 7;
    float pe = 0.f;
#pragma unroll 1
    for (int k = 0; k < 9; k++) {
      const int yy = y + k / 3 - 1, xj = xx + k % 3 - 1;
      const bool in = (uint32_t)yy < kImg && (uint32_t)xj < kImg;
      const float v = in ? __bfloat162float(x[((size_t)yy * kImg + xj) * kCh + c]) : 0.f;
      pe = round_bf16(pe + round_bf16(v * __bfloat162float(dw[k * kCh + c])));
    }
    x0[i] = __float2bfloat16(__bfloat162float(x[((size_t)y * kImg + xx) * kCh + c]) + pe);
  }
  bar_sync(bar);
  if (t < 49) {
    float s = 0.f, v = 0.f;
#pragma unroll 1
    for (int c = 0; c < 192; c++) s += __bfloat162float(x0[t * 192 + c]);
    const float mean = s * (1.f / 192.f);
#pragma unroll 1
    for (int c = 0; c < 192; c++) {
      const float d = __bfloat162float(x0[t * 192 + c]) - mean;
      v = fmaf(d, d, v);
    }
    const float m = round_bf16(mean), sd = round_bf16(sqrtf(round_bf16(round_bf16(v * (1.f / 192.f)) + 1e-5f)));
#pragma unroll 1
    for (int c = 0; c < 192; c++) h[t * 192 + c] = __float2bfloat16(round_bf16(__bfloat162float(x0[t * 192 + c]) - m) / sd);
  }
#pragma unroll 1
  for (int head = 0; head < 4; head++) {
    bar_sync(bar);
#pragma unroll 1
    for (int i = t; i < 49 * 144; i += 128) {
      const int tok = i / 144, n = i % 144, col = (n / 48) * 192 + head * 48 + n % 48;
      float a = 0.f;
#pragma unroll 4
      for (int c = 0; c < 192; c++) a = fmaf(__bfloat162float(h[tok * 192 + c]), __bfloat162float(wqkv[c * 576 + col]), a);
      qkv[i] = __float2bfloat16(a);
    }
    bar_sync(bar);
    if (t < 49) {
      float p[49], m = -INFINITY, s = 0.f;
#pragma unroll
      for (int b = 0; b < 49; b++) {
        float a = 0.f;
#pragma unroll 4
        for (int d = 0; d < 48; d++) a = fmaf(__bfloat162float(qkv[t * 144 + d]), __bfloat162float(qkv[b * 144 + 48 + d]), a);
        p[b] = round_bf16(round_bf16(a) * 0.14433757f);
        m = fmaxf(m, p[b]);
      }
#pragma unroll
      for (int b = 0; b < 49; b++) {
        p[b] = expf(p[b] - m);
        s += p[b];
      }
#pragma unroll
      for (int b = 0; b < 49; b++) p[b] = round_bf16(p[b] / s);
#pragma unroll 1
      for (int d = 0; d < 48; d++) {
        float a = 0.f;
#pragma unroll
        for (int b = 0; b < 49; b++) a = fmaf(p[b], __bfloat162float(qkv[b * 144 + 96 + d]), a);
        o[t * 192 + head * 48 + d] = __float2bfloat16(a);
      }
    }
  }
  bar_sync(bar);
#pragma unroll 1
  for (int i = t; i < 49 * 192; i += 128) {
    const int tok = i / 192, n = i % 192;
    float a = 0.f;
#pragma unroll 4
    for (int c = 0; c < 192; c++) a = fmaf(__bfloat162float(o[tok * 192 + c]), __bfloat162float(wo[c * kCh + n]), a);
    out[((size_t)(y0 + tok / 7) * kImg + c0 + tok % 7) * kCh + n] = __float2bfloat16(__bfloat162float(x0[tok * 192 + n]) + round_bf16(a));
  }
}

__device__ __forceinline__ uint32_t fresh_tid() {
  uint32_t t;
  asm volatile("mov.u32 %0, %%tid.x;" : "=r"(t));
  return t;
}
struct Split {
  uint32_t top, rows, alone, share, fewer;
  uint32_t magic[2];
};
struct Windows {
  uint32_t first, count, alone, jump, height, row0, magic;
  __device__ __forceinline__ explicit Windows(const Split& s) {
    uint32_t b;
    asm volatile("mov.u32 %0, %%ctaid.x;" : "=r"(b));
    const bool upper = b < s.top;
    const uint32_t i = upper ? 0 : b - s.top;
    height = upper ? s.rows : kWinPerCol - s.rows;
    row0 = upper ? 0 : s.rows;
    magic = upper ? s.magic[0] : s.magic[1];
    alone = upper ? s.rows : s.alone;
    first = upper ? b * s.rows : i * s.alone;
    count = upper ? s.rows : s.alone + s.share + max(i + 1, s.fewer) - max(i, s.fewer);
    jump = (gridDim.x - s.top - 1 - i) * s.alone + i * s.share + max(i, s.fewer) - s.fewer;
  }
  __device__ __forceinline__ bool at(uint32_t j, uint32_t& col, uint32_t& row) const {
    const uint32_t v = first + j + (j >= alone ? jump : 0);
    col = (v * magic) >> 20;
    row = v - col * height + row0;
    return row == row0 || j == alone;
  }
};
template <uint32_t BYTES>
__device__ __forceinline__ void load_rows(uint32_t dst, const CUtensorMap* tm, uint32_t ch, int x, int y, uint32_t bar) {
  asm volatile("{\n.reg .pred p;\nelect.sync _|p, 0xffffffff;\n"
               "@p mbarrier.arrive.expect_tx.shared::cta.b64 _, [%5], %6;\n"
               "@p cp.async.bulk.tensor.3d.shared::cluster.global.tile.mbarrier::complete_tx::bytes [%0], [%1, {%2, %3, %4}], [%5];\n}"
               ::"r"(dst), "l"(tm), "r"(ch), "r"(x), "r"(y), "r"(bar), "n"(BYTES) : "memory");
}
__device__ __forceinline__ void prefetch_box(const CUtensorMap* tm, int x, int y) {
  asm volatile("cp.async.bulk.prefetch.tensor.3d.L2.global.tile [%0, {%1, %2, %3}];" ::"l"(tm), "r"(0), "r"(x), "r"(y) : "memory");
}
__device__ __forceinline__ void prefetch_rows(const CUtensorMap* tm, int x, int y) {
  asm volatile("{\n.reg .pred p;\nelect.sync _|p, 0xffffffff;\n"
               "@p cp.async.bulk.prefetch.tensor.3d.L2.global.tile [%0, {%1, %2, %3}];\n}" ::"l"(tm), "r"(0), "r"(x), "r"(y) : "memory");
}
__device__ __forceinline__ void store_group(const CUtensorMap* tm, uint32_t src, uint32_t ch, uint32_t x, uint32_t y) {
  asm volatile("cp.async.bulk.tensor.3d.global.shared::cta.tile.bulk_group [%0, {%2, %3, %4}], [%1];"
               ::"l"(tm), "r"(src), "r"(ch), "r"(x), "r"(y) : "memory");
}

template <int N> struct Int { static constexpr int value = N; };
struct Conv {
  uint32_t wt[9], prev[9], acc[7];
  __device__ __forceinline__ void begin(const uint32_t (&cur)[9]) {
#pragma unroll
    for (int x = 0; x < 7; x++) {
      uint32_t a = bmul2(prev[x], wt[0]);
      a = bfma2(prev[x + 1], wt[1], a);
      a = bfma2(prev[x + 2], wt[2], a);
#pragma unroll
      for (int t = 0; t < 3; t++) a = bfma2(cur[x + t], wt[3 + t], a);
      acc[x] = a;
    }
#pragma unroll
    for (int x = 0; x < 9; x++) prev[x] = cur[x];
  }
  __device__ __forceinline__ void start_column(uint32_t slot0, uint32_t bar0, uint32_t parity0, uint32_t slot1, uint32_t bar1,
                                               uint32_t parity1, uint32_t lane, uint32_t dump, bool request, const CUtensorMap* tm,
                                               uint32_t ch, int x, int y) {
    uint32_t cur[9];
    mbar_wait(bar0, parity0);
#pragma unroll
    for (int i = 0; i < 9; i++) prev[i] = lds32(slot0 + lane * 4 + i * 128);
    sts32(dump, prev[0] ^ prev[1] ^ prev[2] ^ prev[3] ^ prev[4] ^ prev[5] ^ prev[6] ^ prev[7] ^ prev[8]);
    if (request) load_rows<HALO_ROW>(slot0, tm, ch, x, y, bar0);
    mbar_wait(bar1, parity1);
#pragma unroll
    for (int i = 0; i < 9; i++) cur[i] = lds32(slot1 + lane * 4 + i * 128);
    begin(cur);
    sts32(dump, acc[0] ^ acc[3] ^ acc[6]);
    if (request) load_rows<HALO_ROW>(slot1, tm, ch, x, y + 1, bar1);
  }
  __device__ __forceinline__ void row_at(uint32_t src, uint32_t dst, uint32_t t) {
    uint32_t cur[9];
#pragma unroll
    for (int x = 0; x < 9; x++) cur[x] = lds32(src + x * 128);
#pragma unroll
    for (int x = 0; x < 7; x++) {
      uint32_t a = acc[x];
#pragma unroll
      for (int i = 0; i < 3; i++) a = bfma2(cur[x + i], wt[6 + i], a);
      sts32((dst ^ (((t + x) & 7) << 4)) + x * 128, bf16x2_to_f16x2(badd2(prev[x + 1], a)));
    }
    begin(cur);
  }
  template <int R>
  __device__ __forceinline__ void row(uint32_t src, uint32_t dst, uint32_t at) {
    uint32_t cur[9];
#pragma unroll
    for (int x = 0; x < 9; x++) cur[x] = lds32(src + x * 128);
#pragma unroll
    for (int x = 0; x < 7; x++) {
      uint32_t a = acc[x];
#pragma unroll
      for (int t = 0; t < 3; t++) a = bfma2(cur[x + t], wt[6 + t], a);
      sts32((dst ^ (((R * 7 + x) & 7) << 4)) + at + x * 128, bf16x2_to_f16x2(badd2(prev[x + 1], a)));
    }
    begin(cur);
  }
};

__global__ void __launch_bounds__(512, 1)
davit_window_attn_kernel(const __grid_constant__ CUtensorMap tm1, const __grid_constant__ CUtensorMap tm7c,
                         const __grid_constant__ CUtensorMap tm7, const __grid_constant__ CUtensorMap tmo,
                         const __grid_constant__ CUtensorMap tmw, const __grid_constant__ CUtensorMap tmwo,
                         const __nv_bfloat16* __restrict__ dw, const __nv_bfloat16* __restrict__ x_raw,
                         const __nv_bfloat16* __restrict__ wqkv_raw, const __nv_bfloat16* __restrict__ wo_raw,
                         __nv_bfloat16* __restrict__ out, Scratch* __restrict__ scr, const Split split) {
  extern __shared__ __align__(1024) uint8_t smem_raw[];
  const uint32_t sb = (uint32_t)__cvta_generic_to_shared(smem_raw);
  const uint32_t tail = sb + OFF_TAIL;
  uint32_t wt[9];
  {
    const uint32_t tid = threadIdx.x;
    const uint32_t wid = __shfl_sync(0xffffffffu, tid >> 5, 0), lane = tid & 31;
    if (wid > 12) {
      const uint32_t chunk = wid - 13, hbar = tail + T_HALO + 24 * chunk, rbar = tail + T_ROW + 16 * chunk;
      if (lane == 0) {
        mbar_init(hbar, 1);
        mbar_init(hbar + 8, 1);
        mbar_init(hbar + 16, 1);
        mbar_init(rbar, 1);
        mbar_init(rbar + 8, 1);
        if (wid == 13) mbar_init(tail + T_RAW, 1);
        fence_async();
      }
      __syncwarp();
      if (blockIdx.x < kUnits) {
        if (wid == 13 && lane == 0) request_unit(blockIdx.x, sb + OFF_RING, tail + T_RAW, &tmw, &tmwo);
        asm volatile("bar.sync 5, 96;" ::: "memory");
      }
      uint32_t col, row;
      Windows(split).at(0, col, row);
      const int x = (int)col * 7 - 1, y = (int)row * 7;
      const uint32_t halo = sb + OFF_HALO + chunk * 3 * HALO_ROW;
      load_rows<HALO_ROW>(halo, &tm1, chunk * 64, x, y - 1, hbar);
      load_rows<HALO_ROW>(halo + HALO_ROW, &tm1, chunk * 64, x, y, hbar + 8);
      load_rows<7 * HALO_ROW>(sb + OFF_KV + chunk * 7 * HALO_ROW, &tm7c, chunk * 64, x, y + 1, rbar);
#pragma unroll
      for (int i = 0; i < 9; i++) wt[i] = __ldg(reinterpret_cast<const uint32_t*>(dw) + i * (kCh / 2) + chunk * 32 + lane);
    } else {
      if (lane == 0) {
        if (wid < 12) {
          const uint32_t i = 2 * wid, counts = (uint32_t)((wid < 8 ? 0x4144444333CCC111ull >> (8 * wid) : 0x11444144u >> (8 * wid - 64)));
          mbar_init(tail + 8 * (i < 11 ? i : i + 9), counts & 15);
          if (wid < 11)
          mbar_init(tail + 8 * (i < 10 ? i + 1 : i + 10), (counts >> 4) & 15);
          fence_async();
        }
      }
      if (wid == 12) {
        for (uint32_t line = blockIdx.x + gridDim.x * lane; line < 2304; line += gridDim.x * 32) {
          const uint8_t* p = (line < 1728) ? reinterpret_cast<const uint8_t*>(wqkv_raw) + line * 128
                                           : reinterpret_cast<const uint8_t*>(wo_raw) + (line - 1728) * 128;
          asm volatile("prefetch.global.L2 [%0];" ::"l"(p));
        }
        if (lane < 7) sts32(tail + T_ZERO + 4 * lane, 0u);
      }
    }
    __syncthreads();
    if (wid < 12) {
#pragma unroll 1
      for (uint32_t u = blockIdx.x, i = 0; u < kUnits; u += gridDim.x, i++) {
        if (i) {
          asm volatile("bar.sync 4, 384;" ::: "memory");
          if (tid == 0) request_unit(u, sb + OFF_RING, tail + T_RAW, &tmw, &tmwo);
        }
        mbar_wait(tail + T_RAW, i & 1);
        prepare_unit(u, wid, lane, sb + OFF_RING, scr);
      }
    }
  }

  if (threadIdx.x >= 384) {
    asm volatile("setmaxnreg.dec.sync.aligned.u32 %0;" ::"n"(56));
    const uint32_t tid = fresh_tid();
    const uint32_t warp = __shfl_sync(0xffffffffu, (tid >> 5) & 3, 0), lane = tid & 31;
    if (warp == 0) {
      if (lane == 0) {
        const Windows win(split);
        uint32_t spins = 0, seen;
        while (true) {
          asm volatile("ld.acquire.gpu.global.u32 %0, [%1];" : "=r"(seen) : "l"(&scr->ready) : "memory");
          if ((seen & 31) == kUnits) break;
          if (++spins > (1u << 22)) __trap();
        }
        asm volatile("fence.proxy.async.global;" ::: "memory");
        const uint8_t* w = scr->weights;
        {
          const int e0 = (int)((seen >> 10) & 511) - 128, e1 = (int)(seen >> 19) - 128;
          sts32(tail + T_SCALE, pack_f16(fmaxf(0.20823509f * pow2(9 - e0), 0x1p-24f), fmaxf(0.20823509f * pow2(9 - e1), 0x1p-24f)));
          if ((seen & 0x3E0u) || e0 < 1 || e1 < 1) sts32(tail + T_ALL, 1u);
        }
#pragma unroll
        for (uint32_t s = 0; s < 3; s++) {
          mbar_expect_tx(tail + T_FULL + 8 * s, W_PART);
          bulk_load(sb + OFF_RING + s * W_PART, w + s * W_PART, W_PART, tail + T_FULL + 8 * s);
        }
#pragma unroll 1
        for (uint32_t j = 2; j < 4 && j < win.count; j++) {
          uint32_t col, row;
          const bool fresh = win.at(j, col, row);
          if (j == 3 || fresh) prefetch_box(&tm7, 7 * col - 1, 7 * row + 1);
          if (fresh) prefetch_box(&tm7, 7 * col - 1, 7 * row - 1);
        }
        if (atomicInc(&scr->passed, gridDim.x - 1) == gridDim.x - 1) scr->ready = 0;
        const uint32_t uses = 8 * ((win.count + 2) / 3);
        uint32_t s = 0, parity = 0;
#pragma unroll 1
        for (uint32_t u = 3; u < uses; u++) {
          mbar_wait(tail + T_EMPTY + 8 * s, parity);
          mbar_expect_tx(tail + T_FULL + 8 * s, W_PART);
          bulk_load(sb + OFF_RING + s * W_PART, w + (u & 7) * W_PART, W_PART, tail + T_FULL + 8 * s);
          s = (s == 2) ? 0 : s + 1;
          parity ^= (s == 0);
        }
      }
    } else {
      Conv cv;
#pragma unroll
      for (int i = 0; i < 9; i++) cv.wt[i] = wt[i];
      {
        const uint32_t chunk = warp - 1, halo = sb + OFF_HALO + chunk * 3 * HALO_ROW, hbar = tail + T_HALO + 24 * chunk;
        const Windows win(split);
        uint32_t col, row, cn, rn;
        const uint32_t staged = (win.count > 1 && !win.at(1, col, row)) ? 2 : 1;
        const bool fresh = win.at(staged, cn, rn);
        const int xn = 7 * cn - 1, yn = fresh ? 7 * rn - 1 : 7 * rn + 1;
        if (staged < win.count) load_rows<HALO_ROW>(halo + 2 * HALO_ROW, &tm1, chunk * 64, xn, yn, hbar + 16);
        cv.start_column(halo, hbar, 0, halo + HALO_ROW, hbar + 8, 0, lane, tail + T_DUMP, staged < win.count, &tm1, chunk * 64, xn, yn + 1);
        if (staged == 2)
          load_rows<7 * HALO_ROW>(sb + OFF_KV + (3 + chunk) * 7 * HALO_ROW, &tm7c, chunk * 64, 7 * col - 1, 7 * row + 1,
                                  tail + T_ROW + 16 * chunk + 8);
#pragma unroll 1
        for (uint32_t i = 0; i < staged; i++) {
          mbar_wait(tail + T_ROW + 16 * chunk + 8 * i, 0);
#pragma unroll 1
          for (uint32_t r = 0; r < 7; r++)
            cv.row_at(sb + OFF_KV + ((3 * i + chunk) * 7 + r) * HALO_ROW + lane * 4,
                      sb + OFF_X0 + chunk * X0_CHUNK + lane * 4 + (7 * i + r) * X0_ROW, 7 * r);
          __syncwarp();
          arrive_elected(tail + T_X0FULL + 8 * i);
          if (i == 0 && chunk == 0 && staged < win.count) prefetch_rows(&tm7, xn, yn + 3);
        }
      }
      const uint32_t chunk = __shfl_sync(0xffffffffu, (fresh_tid() >> 5) & 3, 0) - 1, ch = chunk * 64;
      const uint32_t halo = sb + OFF_HALO + chunk * 3 * HALO_ROW, hbar = tail + T_HALO + 24 * chunk;
      const uint32_t src = halo + lane * 4, dst = sb + OFF_X0 + chunk * X0_CHUNK + lane * 4;
      const Windows win(split);
      const uint32_t count = win.count;
      uint32_t col, row;
      const uint32_t staged = (count > 1 && !win.at(1, col, row)) ? 2 : 1;
      bool fresh = win.at(staged, col, row);
      uint32_t s0 = 2, p0 = 0;
#pragma unroll 1
      for (uint32_t j = staged; j < count; j++) {
        int x = (int)col * 7 - 1, y = (int)row * 7;
        uint32_t at = 7 * j % kRows * X0_ROW;
        if (fresh) {
          const uint32_t s1 = (s0 == 2) ? 0 : s0 + 1;
          cv.start_column(halo + s0 * HALO_ROW, hbar + 8 * s0, p0, halo + s1 * HALO_ROW, hbar + 8 * s1, p0 ^ (s0 == 2), lane, tail + T_DUMP, true,
                          &tm1, ch, x, y + 2);
          p0 ^= (s0 != 0);
          s0 = (s0 == 0) ? 2 : s0 - 1;
        }
        const uint32_t slot[3] = {s0, (s0 == 2) ? 0 : s0 + 1, (s0 == 0) ? 2 : s0 - 1}, parity[3] = {p0, p0 ^ (s0 == 2), p0 ^ (s0 != 0)};
        const bool more = j + 1 < count;
        if (chunk == 0 && j + 2 < count) {
          if (win.at(j + 2, col, row)) prefetch_rows(&tm7, 7 * col - 1, 7 * row - 1);
          prefetch_rows(&tm7, 7 * col - 1, 7 * row + 1);
        }
        fresh = win.at(j + 1, col, row);
        auto step = [&](auto r) {
          constexpr int R = decltype(r)::value;
          if (R == kRows - 14) {
            mbar_wait(tail + T_X0FREE + 8 * (j & 1), ((j >> 1) & 1) ^ 1);
          }
          if (R == 4) {
            x = (int)col * 7 - 1;
            y = (int)row * 7 - (fresh ? 9 : 7);
          }
          mbar_wait(hbar + 8 * slot[R % 3], parity[R % 3] ^ ((R / 3) & 1));
          cv.template row<R>(src + slot[R % 3] * HALO_ROW, dst, at);
          if (R < 4 || more) load_rows<HALO_ROW>(halo + slot[R % 3] * HALO_ROW, &tm1, ch, x, y + R + 4, hbar + 8 * slot[R % 3]);
          at = (at == (kRows - 1) * X0_ROW) ? 0 : at + X0_ROW;
        };
        step(Int<0>()); step(Int<1>()); step(Int<2>()); step(Int<3>()); step(Int<4>()); step(Int<5>()); step(Int<6>());
        __syncwarp();
        arrive_elected(tail + T_X0FULL + 8 * (j % 3));
        s0 = slot[1];
        p0 = parity[1];
      }
    }
    __syncwarp();
    asm volatile("bar.sync 0, 512;" ::: "memory");
  } else {
    asm volatile("setmaxnreg.inc.sync.aligned.u32 %0;" ::"n"(152));
    const uint32_t wid = __shfl_sync(0xffffffffu, fresh_tid() >> 5, 0);
    const uint32_t wg = wid >> 2, warp = wid & 3;
    uint32_t lane;
    asm volatile("mov.u32 %0, %%laneid;" : "=r"(lane));
    const uint32_t count = Windows(split).count;
    const uint32_t q = lane & 3, mat = lane >> 3, row = lane & 7;
    const uint32_t area = sb + OFF_KV + wg * KV_SIZE;
    const uint32_t bars = tail + T_WG + 32 * wg;
    const bool full = warp < 3;
    const bool valid = full || lane < 4;
    const bool lead = lane == 0;
    uint32_t k_st, v_st, x_ld, x_mask, x_row, o_st;
    {
      const uint32_t rowg = full ? 2 * warp + (mat & 1) : 6, colg = full ? (mat >> 1) : (mat & 1);
      k_st = full ? area + A_K0 + colg * K_CHUNK + rowg * 128 + row * 16 : area + A_K0 + 768 + q * 4;
      v_st = full ? area + A_V0 + colg * V_GROUP + rowg * 128 + row * 16 : area + A_ONES + lane * 16;
      const uint32_t t = 16 * warp + row + 8 * (mat & 1);
      x_ld = (t < 49) ? sb + OFF_X0 + t * 128 + (((mat >> 1) ^ row) << 4) : tail + T_ZERO;
      x_mask = (t < 49) ? ~0u : 0u;
      x_row = t / 7;
      const uint32_t a = area + (full ? t : 48) * 64;
      o_st = a + (((full ? (mat >> 1) : 0) ^ ((a >> 7) & 3)) << 4) + (full ? 0 : 4 * q);
    }
    const uint32_t v_last = area + A_LAST + q * 32;
    const uint32_t pad = (valid ? 0u : 0xFC00u) | (full ? 0u : 0xFC000000u);
    const uint64_t k_desc = make_desc(area + A_K0, K_CHUNK, 128);
    const uint64_t v_desc = make_desc(area + A_V0, 128, V_GROUP);
    const uint64_t w_desc = make_desc(sb + OFF_RING, 128, 256);
    if (wg == 2) asm volatile("bar.arrive 8, 256;" ::: "memory");
    auto send_output = [&](uint32_t j, uint32_t parity) {
      uint32_t col, row;
      Windows(split).at(j, col, row);
      mbar_wait(bars + B_OUTRDY, parity);
#pragma unroll
      for (int i = 0; i < 6; i++) store_group(&tmo, area + i * OUT_GROUP, 32 * i, 7 * col, 7 * row);
      asm volatile("cp.async.bulk.commit_group;" ::: "memory");
    };
    uint32_t round = 0;
#pragma unroll 1
    for (; 3 * round + wg < count; round++) {
      const uint32_t r = __shfl_sync(0xffffffffu, round, 0), j = 3 * r + wg, ph = r & 1;
      const uint32_t m = 8 * r / 3, rot = 8 * r - 3 * m;
      const uint32_t ra = 8 * rot, rb = (rot == 2) ? 0 : ra + 8, rc = (rot == 0) ? 16 : ra - 8;
      const uint32_t pa = m & 1, pb = pa ^ (rot == 2), pc = pa ^ (rot != 0);
      uint32_t x[48], ka[24], va[24], oa[24], ob[24], rr, scales;
      uint32_t (&qa)[24] = ka;
      uint32_t sc0[14], sc1[14], pa0[12], pa1[12], ov0[14], ov1[14];
      mbar_wait(tail + T_X0FULL + 8 * wg, ph);
      {
        asm volatile("" : "+r"(x_mask));
        const uint32_t at = 7 * j % kRows;
        const uint32_t a = x_ld + ((at * X0_ROW - (x_row >= kRows - at ? X0_CHUNK : 0)) & x_mask);
#pragma unroll
        for (int s = 0; s < 12; s++)
          ldsm4((a ^ (((s & 3) << 5) & x_mask)) + ((s >> 2) * X0_CHUNK & x_mask), x[4 * s], x[4 * s + 1], x[4 * s + 2], x[4 * s + 3]);
      }
      warp_arrive(tail + T_X0FREE + 8 * (j & 1), lead);
#pragma unroll
      for (int p = 0; p < 2; p++) {
        asm volatile("bar.sync %0, 256;" ::"r"(8 + wg) : "memory");
        mbar_wait(tail + T_FULL + ra, pa ^ p);
        wg_fence();
        issue_proj<false>(ka, x, desc_at(w_desc, ra * (W_PART / 8)));
        wg_commit();
        if (p == 0) {
          if (!full && lead && r > 0) send_output(j - 3, ph ^ 1);
          __syncwarp();
        }
        if (p == 1) {
          wg_wait<1>();
          fence_regs(ov1);
          if (lead) mbar_arrive(bars + B_KVFREE);
          pack_o<0, 2>(ov1, &oa[12]);
        }
        mbar_wait(tail + T_FULL + rb, pb ^ p);
        wg_fence();
        {
          const uint64_t d = desc_at(w_desc, rb * (W_PART / 8));
          issue_half<1>(va, x, d);
          wg_commit();
          wg_wait<1>();
          if (lead) mbar_arrive(tail + T_EMPTY + ra);
          __syncwarp();
          issue_half<0>(va, x, d);
          wg_commit();
        }
        asm volatile("bar.arrive %0, 256;" ::"r"(wg == 2 ? 8 : 9 + wg) : "memory");
        if (p == 0) {
          scales = __shfl_sync(0xffffffffu, lds32(tail + T_SCALE), 0);
          const bool odd = q & 1;
          uint32_t lane_sums[2];
          lane_stats_packed(x, lane_sums);
          const uint32_t packed = quad_stats_packed(lane_sums, odd);
          float sum = h_lo(packed), squares = h_hi(packed);
          const bool fine = (squares >= 0.1875f || (pad & (odd ? 0xFC000000u : 0xFC00u))) & (squares <= 65504.f) & (sum * sum <= 96.f * squares);
          const bool exact = !__all_sync(0xffffffffu, fine);
          if (exact) {
            wg_wait<0>();
            row_stats(x, odd, sum, squares);
          }
          const float mean = sum * (1.f / 192.f);
          const float rs = 16.f * rsqrt_fast(fmaxf(fmaf(squares, 1.f / 192.f, -mean * mean), 0.f) + 1e-5f);
          if (exact) {
            const uint32_t range = __reduce_max_sync(0xffffffffu, __float_as_uint(squares * fmaxf(rs * rs, 1.f)));
            if ((range > 0x4D400000u || (range != 0u && range < 0x4585A800u)) && lead) {
              scr->redo[blockIdx.x + gridDim.x * j] = 1;
              sts32(tail + T_ANY, 1u);
            }
          }
          const float o = __shfl_xor_sync(0xffffffffu, rs, 1);
          rr = pack_f16(odd ? o : rs, odd ? rs : o);
          if (!full && lead) {
            asm volatile("cp.async.bulk.wait_group.read 0;" ::: "memory");
            mbar_arrive(bars + B_OUTFREE);
          }
          __syncwarp();
          mbar_wait(bars + B_OUTFREE, ph);
        } else {
          mbar_wait(bars + B_KVFREE, 0);
        }
        fence_regs(ka);
        store_k(ka, k_st, full, lane < 4, rr);
        mbar_wait(tail + T_FULL + rc, pc ^ p);
        wg_fence();
        {
          const uint64_t d = desc_at(w_desc, rc * (W_PART / 8));
          issue_half<2>(qa, x, d);
          wg_commit();
          wg_wait<1>();
          if (lead) mbar_arrive(tail + T_EMPTY + rb);
          __syncwarp();
          issue_half<0>(qa, x, d);
          wg_commit();
        }
        fence_regs(va);
        if (p == 0 && !full) {
          sts128_if(true, v_st, 0x3C003C00u, 0x3C003C00u, 0x3C003C00u, 0x3C003C00u);
          sts128_if(lane < 16, v_st + 512, 0x3C003C00u, 0x3C003C00u, 0x3C003C00u, 0x3C003C00u);
        }
        store_v(va, v_st, v_last, full, lane < 4, rr);
        fence_async();
        warp_arrive(bars + B_KVRDY, lead);
        wg_wait<0>();
        fence_regs(qa);
        if (lead) mbar_arrive(tail + T_EMPTY + rc);
        {
          const uint32_t rq = hmul2(rr, 0x18001800u);
#pragma unroll
          for (int i = 0; i < 24; i += 2) {
            qa[i] = hmul2_lo(qa[i], rq);
            qa[i + 1] = hmul2_hi(qa[i + 1], rq);
          }
        }
        const uint32_t cr = (p == 0) ? both<0>(scales) : both<1>(scales);
        mbar_wait(bars + B_KVRDY, p);

        wg_fence();
        issue_s(sc0, &qa[0], desc_at(k_desc, 0));
        wg_commit();
        uint32_t top0, top1, last0, last1;
        if (p == 0) {
          issue_s(sc1, &qa[12], desc_at(k_desc, A_K1));
          wg_commit();
          wg_wait<1>();
          fence_regs(sc0);
          top0 = softmax_top(sc0, lane, cr, last0);
          softmax_rows<12, 0>(sc0, top0, last0, cr, pad, v_last, pa0, ov0);
          wg_fence();
          issue_pv(ov0, pa0, desc_at(v_desc, 0));
          wg_commit();
          wg_wait<1>();
          fence_regs(sc1);
          top1 = softmax_top(sc1, lane, cr, last1);
          softmax_rows<0, 2>(sc1, top1, last1, cr, pad, v_last + 128, pa1, ov1);
        } else {
          wg_wait<0>();
          fence_regs(sc0);
          wg_fence();
          issue_s(sc1, &qa[12], desc_at(k_desc, A_K1));
          wg_commit();
          top0 = softmax_top(sc0, lane, cr, last0);
          wg_wait<0>();
          fence_regs(sc1);
          softmax_rows<12, 0>(sc0, top0, last0, cr, pad, v_last, pa0, ov0);
          mbar_wait(tail + T_FULL + ra, pa);
          wg_fence();
          issue_pv(ov0, pa0, desc_at(v_desc, 0));
          wg_commit();
          issue_out<6>(x, oa, desc_at(w_desc, ra * (W_PART / 8)));
          wg_commit();
          top1 = softmax_top(sc1, lane, cr, last1);
          wg_wait<1>();
          fence_regs(ov0);
          softmax_rows<0, 2>(sc1, top1, last1, cr, pad, v_last + 128, pa1, ov1);
        }
        wg_fence();
        issue_pv(ov1, pa1, desc_at(v_desc, A_ONES - A_V0));
        wg_commit();
        wg_wait<1>();
        if (p == 0) fence_regs(ov0);
        else if (lead) mbar_arrive(tail + T_EMPTY + ra);
        {
          uint32_t big;
          asm("{\n.reg .pred p, q;\n.reg .b32 t;\nmax.xorsign.abs.f16x2 t, %1, %2;\nabs.f16x2 t, t;\nsetp.gt.f16x2 p|q, t, %3;\n"
              "or.pred p, p, q;\nselp.u32 %0, 1, 0, p;\n}" : "=r"(big) : "r"(top0), "r"(top1), "r"(0x60006000u));
          if (__any_sync(0xffffffffu, big) && lead) {
            scr->redo[blockIdx.x + gridDim.x * j] = 1;
            sts32(tail + T_ANY, 1u);
          }
          __syncwarp();
        }
        uint32_t (&o)[24] = (p == 0) ? oa : ob;
        pack_o<12, 0>(ov0, &o[0]);
        if (p == 1) {
          mbar_wait(tail + T_FULL + rb, pb);
          wg_fence();
          issue_out<3>(x, &ob[0], desc_at(w_desc, rb * (W_PART / 8)));
          wg_commit();
          wg_wait<1>();
          fence_regs(ov1);
          if (lead) mbar_arrive(bars + B_KVFREE);
          pack_o<0, 2>(ov1, &o[12]);
        }
      }
      wg_fence();
      issue_out<3>(x, &ob[12], desc_at(w_desc, rb * (W_PART / 8) + 3 * WO_STEP));
      wg_commit();
      mbar_wait(bars + B_KVFREE, 1);
      wg_wait<0>();
      fence_regs(x);
      if (lead) mbar_arrive(tail + T_EMPTY + rb);
      asm volatile("" : "+r"(o_st));
      if (full) {
#pragma unroll
        for (int s = 0; s < 12; s++)
          stsm4((o_st ^ (((s ^ (s >> 1)) & 1) << 5)) + (s >> 1) * OUT_GROUP, f16x2_to_bf16x2(x[4 * s]), f16x2_to_bf16x2(x[4 * s + 1]),
                f16x2_to_bf16x2(x[4 * s + 2]), f16x2_to_bf16x2(x[4 * s + 3]));
        fence_async();
        warp_arrive(bars + B_OUTRDY, lead);
      } else {
#pragma unroll
        for (int i = 0; i < 24; i++)
          sts32_if(lane < 4, (o_st ^ (((i ^ ((i >> 1) & 2)) & 3) << 4)) + (i >> 2) * OUT_GROUP, f16x2_to_bf16x2(x[2 * i]));
        fence_async();
        warp_arrive(bars + B_OUTRDY, lead);
      }
    }
    if (!full && lead && round > 0) send_output(3 * round + wg - 3, (round & 1) ^ 1);
    __syncwarp();
    if (3 * round < count) {
#pragma unroll 1
      for (uint32_t i = 0; i < 5; i++) {
        if (i % 3 == 0) {
          asm volatile("bar.sync %0, 256;" ::"r"(8 + wg) : "memory");
          asm volatile("bar.arrive %0, 256;" ::"r"(wg == 2 ? 8 : 9 + wg) : "memory");
        }
        const uint32_t u = 8 * round + i;
        mbar_wait(tail + T_FULL + 8 * (u % 3), (u / 3) & 1);
        if (lead) mbar_arrive(tail + T_EMPTY + 8 * (u % 3));
        __syncwarp();
      }
    }
    if (!full && lead) asm volatile("cp.async.bulk.wait_group.read 0;" ::: "memory");
    __syncwarp();
    asm volatile("bar.sync 0, 512;" ::: "memory");
    const uint32_t redo_all = lds32(tail + T_ALL);
    if (redo_all | lds32(tail + T_ANY)) {
      const uint32_t t = fresh_tid(), c = t >> 7;
      if ((t & 127) == 96) asm volatile("cp.async.bulk.wait_group 0;\nfence.proxy.async.global;" ::: "memory");
      __syncwarp();
      const Windows win(split);
      for (uint32_t j = c; j < win.count; j += 3) {
        uint8_t* flag = &scr->redo[blockIdx.x + gridDim.x * j];
        if (!redo_all && !*reinterpret_cast<volatile uint8_t*>(flag)) continue;
        uint32_t col, row;
        win.at(j, col, row);
        redo_window(7 * col, 7 * row, t & 127, 1 + c, smem_raw + c * REDO_BYTES, x_raw, dw, wqkv_raw, wo_raw, out);
        if ((t & 127) == 0) *flag = 0;
      }
    }
  }
}

typedef CUresult (*EncodeTiledFn)(CUtensorMap*, CUtensorMapDataType, cuuint32_t, void*, const cuuint64_t*, const cuuint64_t*,
                                  const cuuint32_t*, const cuuint32_t*, CUtensorMapInterleave, CUtensorMapSwizzle,
                                  CUtensorMapL2promotion, CUtensorMapFloatOOBfill);

}

extern "C" void kernel_launch(void* const* d_in, const int* in_sizes, int n_in, void* d_out, int out_size) {
  (void)in_sizes; (void)n_in; (void)out_size;
  static EncodeTiledFn encode = nullptr;
  static int grid = 0;
  static void* scratch = nullptr;
  if (!encode) {
    void* fn = nullptr;
    cudaDriverEntryPointQueryResult st;
    cudaGetDriverEntryPoint("cuTensorMapEncodeTiled", &fn, cudaEnableDefault, &st);
    encode = (EncodeTiledFn)fn;
    cudaFuncSetAttribute(davit_window_attn_kernel, cudaFuncAttributeMaxDynamicSharedMemorySize, SMEM_BYTES);
    cudaGetSymbolAddress(&scratch, g_scratch);
    int dev = 0;
    cudaGetDevice(&dev);
    cudaDeviceGetAttribute(&grid, cudaDevAttrMultiProcessorCount, dev);
  }
  Split split = {};
  {
    const uint32_t g = grid, n = kNumWin / g;
    if (g > kWinPerCol && g <= 2 * kWinPerCol && kWinPerCol - n <= n) {
      const uint32_t below = (kWinPerCol - n) * kWinPerCol;
      split.top = kWinPerCol;
      split.rows = (below > (n + 1) * (g - kWinPerCol) && n + 1 < kWinPerCol) ? n + 1 : n;
      split.alone = kWinPerCol - split.rows;
    }
    const uint32_t others = g - split.top, rest = kNumWin - split.top * split.rows - others * split.alone;
    split.share = rest / others;
    split.fewer = others - rest % others;
    split.magic[0] = split.rows ? ((1u << 20) + split.rows - 1) / split.rows : 0;
    split.magic[1] = ((1u << 20) + kWinPerCol - split.rows - 1) / (kWinPerCol - split.rows);
  }
  auto image_map = [&](void* base, cuuint32_t c, cuuint32_t w, cuuint32_t h, CUtensorMapSwizzle swizzle) {
    CUtensorMap tm;
    const cuuint64_t dims[3] = {(cuuint64_t)kCh, (cuuint64_t)kImg, (cuuint64_t)kImg};
    const cuuint64_t strides[2] = {(cuuint64_t)kCh * 2, (cuuint64_t)kCh * 2 * kImg};
    const cuuint32_t box[3] = {c, w, h};
    const cuuint32_t estr[3] = {1, 1, 1};
    encode(&tm, CU_TENSOR_MAP_DATA_TYPE_BFLOAT16, 3, base, dims, strides, box, estr, CU_TENSOR_MAP_INTERLEAVE_NONE, swizzle,
           CU_TENSOR_MAP_L2_PROMOTION_L2_128B, CU_TENSOR_MAP_FLOAT_OOB_FILL_NONE);
    return tm;
  };
  auto weight_map = [&](void* base, cuuint64_t cols, cuuint32_t rows) {
    CUtensorMap tm;
    const cuuint64_t dims[2] = {cols, (cuuint64_t)kCh};
    const cuuint64_t strides[1] = {cols * 2};
    const cuuint32_t box[2] = {32, rows};
    const cuuint32_t estr[2] = {1, 1};
    encode(&tm, CU_TENSOR_MAP_DATA_TYPE_BFLOAT16, 2, base, dims, strides, box, estr, CU_TENSOR_MAP_INTERLEAVE_NONE,
           CU_TENSOR_MAP_SWIZZLE_64B, CU_TENSOR_MAP_L2_PROMOTION_L2_128B, CU_TENSOR_MAP_FLOAT_OOB_FILL_NONE);
    return tm;
  };
  davit_window_attn_kernel<<<grid, 512, SMEM_BYTES, cudaStreamPerThread>>>(
      image_map(d_in[0], 64, 9, 1, CU_TENSOR_MAP_SWIZZLE_NONE), image_map(d_in[0], 64, 9, 7, CU_TENSOR_MAP_SWIZZLE_NONE),
      image_map(d_in[0], 192, 9, 7, CU_TENSOR_MAP_SWIZZLE_NONE), image_map(d_out, 32, 7, 7, CU_TENSOR_MAP_SWIZZLE_64B),
      weight_map(d_in[2], 576, 192), weight_map(d_in[3], 192, 32),
      (const __nv_bfloat16*)d_in[1], (const __nv_bfloat16*)d_in[0], (const __nv_bfloat16*)d_in[2], (const __nv_bfloat16*)d_in[3],
      (__nv_bfloat16*)d_out, (Scratch*)scratch, split);
}
```

```cpp
#include <cuda.h>
#include <cuda_bf16.h>
#include <cuda_runtime.h>
#include <stdint.h>

namespace {

constexpr int kImg = 511;
constexpr int kCh = 192;
constexpr int kWinPerCol = 73;
constexpr int kNumWin = 73 * 73;

constexpr uint32_t W_PART = 36864;
constexpr uint32_t W_STEP = 3072;
constexpr uint32_t WO_STEP = 6144;
constexpr uint32_t W_BYTES = 8 * W_PART;

struct Scratch {
  uint8_t weights[W_BYTES];
  uint32_t ready;
  uint32_t passed;
  uint32_t claims;
  uint8_t redo[2 * kNumWin];
};
__device__ __align__(128) Scratch g_scratch;

constexpr uint32_t OFF_RING = 0;
constexpr uint32_t OFF_X0 = 3 * W_PART;
constexpr uint32_t kRows = 19;
constexpr uint32_t X0_ROW = 7 * 128;
constexpr uint32_t X0_CHUNK = kRows * X0_ROW;
constexpr uint32_t OFF_HALO = OFF_X0 + 3 * X0_CHUNK;
constexpr uint32_t HALO_ROW = 9 * 128;
constexpr uint32_t OFF_KV = OFF_HALO + 9 * HALO_ROW;
constexpr uint32_t K_CHUNK = 784;
constexpr uint32_t V_GROUP = 768;
constexpr uint32_t A_K0 = 0;
constexpr uint32_t A_V0 = 6 * K_CHUNK;
constexpr uint32_t A_ONES = A_V0 + 6 * V_GROUP;
constexpr uint32_t A_V1 = A_ONES + V_GROUP;
constexpr uint32_t A_K1 = A_V1 + 6 * V_GROUP;
constexpr uint32_t A_LAST = A_K1 + 6 * K_CHUNK;
constexpr uint32_t KV_SIZE = 19840;
constexpr uint32_t OUT_GROUP = 3328;
static_assert(A_LAST + 256 <= KV_SIZE && 5 * OUT_GROUP + 3136 <= KV_SIZE && KV_SIZE % 128 == 0 && 42 * HALO_ROW <= 3 * KV_SIZE &&
              21 * HALO_ROW >= KV_SIZE, "consumer area");
constexpr uint32_t OFF_TAIL = OFF_KV + 3 * KV_SIZE;
constexpr uint32_t SMEM_BYTES = OFF_TAIL + 360;
static_assert(SMEM_BYTES <= 232448, "shared memory");

constexpr uint32_t T_FULL = 0;
constexpr uint32_t T_EMPTY = 24;
constexpr uint32_t T_X0FULL = 48;
constexpr uint32_t T_X0FREE = 72;
constexpr uint32_t T_HALO = 88;
constexpr uint32_t T_WG = 160;
constexpr uint32_t B_KVRDY = 0;
constexpr uint32_t B_KVFREE = 8;
constexpr uint32_t B_OUTRDY = 16;
constexpr uint32_t B_OUTFREE = 24;
constexpr uint32_t T_RAW = 256;
constexpr uint32_t T_CLAIM = 264;
constexpr uint32_t T_ZERO = 272;
constexpr uint32_t T_SCALE = 288;
constexpr uint32_t T_ALL = 292;
constexpr uint32_t T_ANY = 296;
constexpr uint32_t T_DUMP = 300;
constexpr uint32_t T_EXTRA = 352;
constexpr uint32_t T_ROW = 304;

__device__ __forceinline__ void hmma_n96_first(uint32_t (&d)[24], uint32_t a0, uint32_t a1, uint32_t a2, uint32_t a3, uint64_t desc) {
  asm volatile("wgmma.mma_async.sync.aligned.m64n96k16.f16.f16.f16 "
               "{%0, %1, %2, %3, %4, %5, %6, %7, %8, %9, %10, %11, %12, %13, %14, %15, "
               "%16, %17, %18, %19, %20, %21, %22, %23}, "
               "{%24, %25, %26, %27}, %28, 0, 1, 1, 0;\n"
               : "=r"(d[0]), "=r"(d[1]), "=r"(d[2]), "=r"(d[3]), "=r"(d[4]), "=r"(d[5]), "=r"(d[6]), "=r"(d[7]),
                 "=r"(d[8]), "=r"(d[9]), "=r"(d[10]), "=r"(d[11]), "=r"(d[12]), "=r"(d[13]), "=r"(d[14]), "=r"(d[15]),
                 "=r"(d[16]), "=r"(d[17]), "=r"(d[18]), "=r"(d[19]), "=r"(d[20]), "=r"(d[21]), "=r"(d[22]), "=r"(d[23])
               : "r"(a0), "r"(a1), "r"(a2), "r"(a3), "l"(desc));
}
__device__ __forceinline__ void hmma_n96(uint32_t (&d)[24], uint32_t a0, uint32_t a1, uint32_t a2, uint32_t a3, uint64_t desc) {
  asm volatile("wgmma.mma_async.sync.aligned.m64n96k16.f16.f16.f16 "
               "{%0, %1, %2, %3, %4, %5, %6, %7, %8, %9, %10, %11, %12, %13, %14, %15, "
               "%16, %17, %18, %19, %20, %21, %22, %23}, "
               "{%24, %25, %26, %27}, %28, 1, 1, 1, 0;\n"
               : "+r"(d[0]), "+r"(d[1]), "+r"(d[2]), "+r"(d[3]), "+r"(d[4]), "+r"(d[5]), "+r"(d[6]), "+r"(d[7]),
                 "+r"(d[8]), "+r"(d[9]), "+r"(d[10]), "+r"(d[11]), "+r"(d[12]), "+r"(d[13]), "+r"(d[14]), "+r"(d[15]),
                 "+r"(d[16]), "+r"(d[17]), "+r"(d[18]), "+r"(d[19]), "+r"(d[20]), "+r"(d[21]), "+r"(d[22]), "+r"(d[23])
               : "r"(a0), "r"(a1), "r"(a2), "r"(a3), "l"(desc));
}
__device__ __forceinline__ void hmma_n96_over(uint32_t (&d)[24], uint32_t a0, uint32_t a1, uint32_t a2, uint32_t a3, uint64_t desc) {
  asm volatile("wgmma.mma_async.sync.aligned.m64n96k16.f16.f16.f16 "
               "{%0, %1, %2, %3, %4, %5, %6, %7, %8, %9, %10, %11, %12, %13, %14, %15, "
               "%16, %17, %18, %19, %20, %21, %22, %23}, "
               "{%24, %25, %26, %27}, %28, 0, 1, 1, 0;\n"
               : "+r"(d[0]), "+r"(d[1]), "+r"(d[2]), "+r"(d[3]), "+r"(d[4]), "+r"(d[5]), "+r"(d[6]), "+r"(d[7]),
                 "+r"(d[8]), "+r"(d[9]), "+r"(d[10]), "+r"(d[11]), "+r"(d[12]), "+r"(d[13]), "+r"(d[14]), "+r"(d[15]),
                 "+r"(d[16]), "+r"(d[17]), "+r"(d[18]), "+r"(d[19]), "+r"(d[20]), "+r"(d[21]), "+r"(d[22]), "+r"(d[23])
               : "r"(a0), "r"(a1), "r"(a2), "r"(a3), "l"(desc));
}
__device__ __forceinline__ void hmma_n56_first(uint32_t (&d)[14], uint32_t a0, uint32_t a1, uint32_t a2, uint32_t a3, uint64_t desc) {
  asm volatile("wgmma.mma_async.sync.aligned.m64n56k16.f16.f16.f16 "
               "{%0, %1, %2, %3, %4, %5, %6, %7, %8, %9, %10, %11, %12, %13}, "
               "{%14, %15, %16, %17}, %18, 0, 1, 1, 0;\n"
               : "=r"(d[0]), "=r"(d[1]), "=r"(d[2]), "=r"(d[3]), "=r"(d[4]), "=r"(d[5]), "=r"(d[6]), "=r"(d[7]),
                 "=r"(d[8]), "=r"(d[9]), "=r"(d[10]), "=r"(d[11]), "=r"(d[12]), "=r"(d[13])
               : "r"(a0), "r"(a1), "r"(a2), "r"(a3), "l"(desc));
}
__device__ __forceinline__ void hmma_n56(uint32_t (&d)[14], uint32_t a0, uint32_t a1, uint32_t a2, uint32_t a3, uint64_t desc) {
  asm volatile("wgmma.mma_async.sync.aligned.m64n56k16.f16.f16.f16 "
               "{%0, %1, %2, %3, %4, %5, %6, %7, %8, %9, %10, %11, %12, %13}, "
               "{%14, %15, %16, %17}, %18, 1, 1, 1, 0;\n"
               : "+r"(d[0]), "+r"(d[1]), "+r"(d[2]), "+r"(d[3]), "+r"(d[4]), "+r"(d[5]), "+r"(d[6]), "+r"(d[7]),
                 "+r"(d[8]), "+r"(d[9]), "+r"(d[10]), "+r"(d[11]), "+r"(d[12]), "+r"(d[13])
               : "r"(a0), "r"(a1), "r"(a2), "r"(a3), "l"(desc));
}
__device__ __forceinline__ void hmma_n192(uint32_t (&d)[48], uint32_t a0, uint32_t a1, uint32_t a2, uint32_t a3, uint64_t desc) {
  asm volatile("wgmma.mma_async.sync.aligned.m64n192k16.f16.f16.f16 "
               "{%0, %1, %2, %3, %4, %5, %6, %7, %8, %9, %10, %11, %12, %13, %14, %15, "
               "%16, %17, %18, %19, %20, %21, %22, %23, %24, %25, %26, %27, %28, %29, %30, %31, "
               "%32, %33, %34, %35, %36, %37, %38, %39, %40, %41, %42, %43, %44, %45, %46, %47}, "
               "{%48, %49, %50, %51}, %52, 1, 1, 1, 0;\n"
               : "+r"(d[0]), "+r"(d[1]), "+r"(d[2]), "+r"(d[3]), "+r"(d[4]), "+r"(d[5]), "+r"(d[6]), "+r"(d[7]),
                 "+r"(d[8]), "+r"(d[9]), "+r"(d[10]), "+r"(d[11]), "+r"(d[12]), "+r"(d[13]), "+r"(d[14]), "+r"(d[15]),
                 "+r"(d[16]), "+r"(d[17]), "+r"(d[18]), "+r"(d[19]), "+r"(d[20]), "+r"(d[21]), "+r"(d[22]), "+r"(d[23]),
                 "+r"(d[24]), "+r"(d[25]), "+r"(d[26]), "+r"(d[27]), "+r"(d[28]), "+r"(d[29]), "+r"(d[30]), "+r"(d[31]),
                 "+r"(d[32]), "+r"(d[33]), "+r"(d[34]), "+r"(d[35]), "+r"(d[36]), "+r"(d[37]), "+r"(d[38]), "+r"(d[39]),
                 "+r"(d[40]), "+r"(d[41]), "+r"(d[42]), "+r"(d[43]), "+r"(d[44]), "+r"(d[45]), "+r"(d[46]), "+r"(d[47])
               : "r"(a0), "r"(a1), "r"(a2), "r"(a3), "l"(desc));
}

__device__ __forceinline__ void wg_fence() { asm volatile("wgmma.fence.sync.aligned;\n" ::: "memory"); }
__device__ __forceinline__ void wg_commit() { asm volatile("wgmma.commit_group.sync.aligned;\n" ::: "memory"); }
template <int N> __device__ __forceinline__ void wg_wait() { asm volatile("wgmma.wait_group.sync.aligned %0;\n" ::"n"(N) : "memory"); }
__device__ __forceinline__ uint64_t make_desc(uint32_t addr, uint32_t lbo, uint32_t sbo) {
  return (uint64_t)((addr & 0x3FFFF) >> 4) | ((uint64_t)(lbo >> 4) << 16) | ((uint64_t)(sbo >> 4) << 32);
}
__device__ __forceinline__ uint64_t desc_add(uint64_t d, uint32_t bytes) { return d + (bytes >> 4); }
__device__ __forceinline__ uint64_t desc_at(uint64_t d, uint32_t bytes) {
  uint64_t r;
  asm volatile("mov.b64 %0, %1;" : "=l"(r) : "l"(d));
  return desc_add(r, bytes);
}

__device__ __forceinline__ void mbar_init(uint32_t bar, uint32_t count) {
  asm volatile("mbarrier.init.shared::cta.b64 [%0], %1;" ::"r"(bar), "r"(count) : "memory");
}
__device__ __forceinline__ void mbar_expect_tx(uint32_t bar, uint32_t bytes) {
  asm volatile("mbarrier.arrive.expect_tx.shared::cta.b64 _, [%0], %1;" ::"r"(bar), "r"(bytes) : "memory");
}
__device__ __forceinline__ void mbar_wait(uint32_t bar, uint32_t parity) {
  asm volatile("{\n.reg .pred p;\n.reg .u32 c;\n"
               "mbarrier.try_wait.parity.shared::cta.b64 p, [%0], %1;\n"
               "@p bra DONE;\n"
               "mov.u32 c, 0;\n"
               "SPIN:\n"
               "mbarrier.try_wait.parity.shared::cta.b64 p, [%0], %1, 4000;\n"
               "@p bra DONE;\n"
               "add.u32 c, c, 1;\n"
               "setp.lt.u32 p, c, 1048576;\n"
               "@!p trap;\n"
               "bra SPIN;\n"
               "DONE:\n}" ::"r"(bar), "r"(parity) : "memory");
}
__device__ __forceinline__ void bar_sync(uint32_t id) { asm volatile("bar.sync %0, 128;" ::"r"(id) : "memory"); }
__device__ __forceinline__ void mbar_arrive(uint32_t bar) { asm volatile("mbarrier.arrive.shared::cta.b64 _, [%0];" ::"r"(bar) : "memory"); }
__device__ __forceinline__ void warp_arrive(uint32_t bar, bool first) {
  __syncwarp();
  if (first) mbar_arrive(bar);
}
__device__ __forceinline__ void arrive_elected(uint32_t bar) {
  asm volatile("{\n.reg .pred p;\nelect.sync _|p, 0xffffffff;\n@p mbarrier.arrive.shared::cta.b64 _, [%0];\n}" ::"r"(bar) : "memory");
}
__device__ __forceinline__ void fence_async() { asm volatile("fence.proxy.async.shared::cta;" ::: "memory"); }
__device__ __forceinline__ uint32_t lds32(uint32_t a) {
  uint32_t v;
  asm volatile("ld.shared.b32 %0, [%1];" : "=r"(v) : "r"(a) : "memory");
  return v;
}
__device__ __forceinline__ void lds64(uint32_t a, uint32_t& v0, uint32_t& v1) {
  asm volatile("ld.shared.v2.b32 {%0, %1}, [%2];" : "=r"(v0), "=r"(v1) : "r"(a) : "memory");
}
__device__ __forceinline__ void sts32(uint32_t a, uint32_t v) { asm volatile("st.shared.b32 [%0], %1;" ::"r"(a), "r"(v) : "memory"); }
__device__ __forceinline__ void sts64(uint32_t a, uint32_t v0, uint32_t v1) {
  asm volatile("st.shared.v2.b32 [%0], {%1, %2};" ::"r"(a), "r"(v0), "r"(v1) : "memory");
}
__device__ __forceinline__ void sts32_if(bool on, uint32_t a, uint32_t v) {
  asm volatile("{\n.reg .pred p;\nsetp.ne.u32 p, %2, 0;\n@p st.shared.b32 [%0], %1;\n}" ::"r"(a), "r"(v), "r"((uint32_t)on) : "memory");
}
__device__ __forceinline__ void ldsm4(uint32_t a, uint32_t& r0, uint32_t& r1, uint32_t& r2, uint32_t& r3) {
  asm volatile("ldmatrix.sync.aligned.m8n8.x4.shared.b16 {%0, %1, %2, %3}, [%4];" : "=r"(r0), "=r"(r1), "=r"(r2), "=r"(r3) : "r"(a) : "memory");
}
__device__ __forceinline__ void stsm4(uint32_t a, uint32_t r0, uint32_t r1, uint32_t r2, uint32_t r3) {
  asm volatile("stmatrix.sync.aligned.m8n8.x4.shared.b16 [%0], {%1, %2, %3, %4};" ::"r"(a), "r"(r0), "r"(r1), "r"(r2), "r"(r3) : "memory");
}
__device__ __forceinline__ void stsm4_t(uint32_t a, uint32_t r0, uint32_t r1, uint32_t r2, uint32_t r3) {
  asm volatile("stmatrix.sync.aligned.m8n8.x4.trans.shared.b16 [%0], {%1, %2, %3, %4};" ::"r"(a), "r"(r0), "r"(r1), "r"(r2), "r"(r3) : "memory");
}
__device__ __forceinline__ uint32_t pack_bf16(float lo, float hi) {
  uint32_t r;
  asm("cvt.rn.bf16x2.f32 %0, %1, %2;" : "=r"(r) : "f"(hi), "f"(lo));
  return r;
}
__device__ __forceinline__ uint32_t pack_f16(float lo, float hi) {
  uint32_t r;
  asm("cvt.rn.f16x2.f32 %0, %1, %2;" : "=r"(r) : "f"(hi), "f"(lo));
  return r;
}
__device__ __forceinline__ float bf_lo(uint32_t v) { return __uint_as_float(v << 16); }
__device__ __forceinline__ float bf_hi(uint32_t v) { return __uint_as_float(v & 0xffff0000u); }
__device__ __forceinline__ float h_lo(uint32_t v) {
  float r;
  asm("{\n.reg .b16 l, h;\nmov.b32 {l, h}, %1;\ncvt.f32.f16 %0, l;\n}" : "=f"(r) : "r"(v));
  return r;
}
__device__ __forceinline__ float h_hi(uint32_t v) {
  float r;
  asm("{\n.reg .b16 l, h;\nmov.b32 {l, h}, %1;\ncvt.f32.f16 %0, h;\n}" : "=f"(r) : "r"(v));
  return r;
}
__device__ __forceinline__ uint32_t bf16x2_to_f16x2(uint32_t v) { return pack_f16(bf_lo(v), bf_hi(v)); }
__device__ __forceinline__ uint32_t f16x2_to_bf16x2(uint32_t v) { return pack_bf16(h_lo(v), h_hi(v)); }
__device__ __forceinline__ uint32_t bmul2(uint32_t a, uint32_t b) {
  uint32_t r;
  asm("mul.rn.bf16x2 %0, %1, %2;" : "=r"(r) : "r"(a), "r"(b));
  return r;
}
__device__ __forceinline__ uint32_t badd2(uint32_t a, uint32_t b) {
  uint32_t r;
  asm("add.rn.bf16x2 %0, %1, %2;" : "=r"(r) : "r"(a), "r"(b));
  return r;
}
__device__ __forceinline__ uint32_t bfma2(uint32_t a, uint32_t b, uint32_t c) {
  uint32_t r;
  asm("fma.rn.bf16x2 %0, %1, %2, %3;" : "=r"(r) : "r"(a), "r"(b), "r"(c));
  return r;
}
__device__ __forceinline__ uint32_t hadd2(uint32_t a, uint32_t b) {
  uint32_t d;
  asm("add.rn.f16x2 %0, %1, %2;" : "=r"(d) : "r"(a), "r"(b));
  return d;
}
__device__ __forceinline__ uint32_t hmax2(uint32_t a, uint32_t b) {
  uint32_t d;
  asm("max.f16x2 %0, %1, %2;" : "=r"(d) : "r"(a), "r"(b));
  return d;
}
__device__ __forceinline__ uint32_t hmul2(uint32_t a, uint32_t b) {
  uint32_t d;
  asm("mul.rn.f16x2 %0, %1, %2;" : "=r"(d) : "r"(a), "r"(b));
  return d;
}
__device__ __forceinline__ uint32_t hmul2_lo(uint32_t a, uint32_t r) {
  uint32_t d;
  asm("{\n.reg .b16 l, h;\n.reg .b32 t;\nmov.b32 {l, h}, %2;\nmov.b32 t, {l, l};\nmul.rn.f16x2 %0, %1, t;\n}" : "=r"(d) : "r"(a), "r"(r));
  return d;
}
__device__ __forceinline__ uint32_t hmul2_hi(uint32_t a, uint32_t r) {
  uint32_t d;
  asm("{\n.reg .b16 l, h;\n.reg .b32 t;\nmov.b32 {l, h}, %2;\nmov.b32 t, {h, h};\nmul.rn.f16x2 %0, %1, t;\n}" : "=r"(d) : "r"(a), "r"(r));
  return d;
}
__device__ __forceinline__ float rcp(float x) {
  float r;
  asm("rcp.approx.ftz.f32 %0, %1;" : "=f"(r) : "f"(x));
  return r;
}
__device__ __forceinline__ float rsqrt_fast(float x) {
  float r;
  asm("rsqrt.approx.ftz.f32 %0, %1;" : "=f"(r) : "f"(x));
  return r;
}
template <int N> __device__ __forceinline__ void fence_regs(uint32_t (&d)[N]) {
#pragma unroll
  for (int i = 0; i < N; i++) asm volatile("" : "+r"(d[i])::"memory");
}

__device__ __forceinline__ void row_stats(const uint32_t (&x)[48], bool odd, float& sum, float& squares) {
  float s0 = 0.f, q0 = 0.f, s1 = 0.f, q1 = 0.f;
#pragma unroll
  for (int i = 0; i < 48; i++) {
    const float lo = h_lo(x[i]), hi = h_hi(x[i]);
    if (i & 1) {
      s1 += lo; q1 = fmaf(lo, lo, q1);
      s1 += hi; q1 = fmaf(hi, hi, q1);
    } else {
      s0 += lo; q0 = fmaf(lo, lo, q0);
      s0 += hi; q0 = fmaf(hi, hi, q0);
    }
  }
  sum = (odd ? s1 : s0) + __shfl_xor_sync(0xffffffffu, odd ? s0 : s1, 1);
  squares = (odd ? q1 : q0) + __shfl_xor_sync(0xffffffffu, odd ? q0 : q1, 1);
  sum += __shfl_xor_sync(0xffffffffu, sum, 2);
  squares += __shfl_xor_sync(0xffffffffu, squares, 2);
}
__device__ __forceinline__ void lane_stats_packed(const uint32_t (&x)[48], uint32_t (&t)[2]) {
  uint32_t s[4] = {x[0], x[1], x[2], x[3]}, q[4];
#pragma unroll
  for (int r = 0; r < 4; r++) q[r] = hmul2(x[r], x[r]);
#pragma unroll
  for (int i = 4; i < 48; i++) {
    asm("add.rn.f16x2 %0, %0, %1;" : "+r"(s[i & 3]) : "r"(x[i]));
    asm("fma.rn.f16x2 %0, %1, %1, %0;" : "+r"(q[i & 3]) : "r"(x[i]));
  }
#pragma unroll
  for (int r = 0; r < 2; r++) {
    const uint32_t a = hadd2(s[r], s[r + 2]), b = hadd2(q[r], q[r + 2]);
    t[r] = hadd2(__byte_perm(a, b, 0x5410), __byte_perm(a, b, 0x7632));
  }
}
__device__ __forceinline__ uint32_t quad_stats_packed(const uint32_t (&t)[2], bool odd) {
  const uint32_t u = hadd2(__shfl_xor_sync(0xffffffffu, odd ? t[0] : t[1], 1), odd ? t[1] : t[0]);
  return hadd2(u, __shfl_xor_sync(0xffffffffu, u, 2));
}

__device__ __forceinline__ void store_k(const uint32_t (&k)[24], uint32_t k_st, bool full, bool first_row, uint32_t r) {
  if (full) {
#pragma unroll
    for (int j = 0; j < 12; j += 2)
      stsm4(k_st + (j / 6) * A_K1 + (j % 6) * K_CHUNK, hmul2_lo(k[2 * j], r), hmul2_hi(k[2 * j + 1], r), hmul2_lo(k[2 * j + 2], r),
            hmul2_hi(k[2 * j + 3], r));
  } else {
#pragma unroll
    for (int j = 0; j < 12; j++) sts32_if(first_row, k_st + (j / 6) * A_K1 + (j % 6) * K_CHUNK, hmul2_lo(k[2 * j], r));
    __syncwarp();
  }
}
template <int HALF> __device__ __forceinline__ uint32_t both(uint32_t v) {
  uint32_t d;
  if (HALF == 0) asm("{\n.reg .b16 l, h;\nmov.b32 {l, h}, %1;\nmov.b32 %0, {l, l};\n}" : "=r"(d) : "r"(v));
  else asm("{\n.reg .b16 l, h;\nmov.b32 {l, h}, %1;\nmov.b32 %0, {h, h};\n}" : "=r"(d) : "r"(v));
  return d;
}
__device__ __forceinline__ uint32_t exp2_scaled(uint32_t s, uint32_t c, uint32_t off) {
  uint32_t d;
  asm("{\n.reg .b32 t;\nfma.rn.f16x2 t, %1, %2, %3;\nex2.approx.f16x2 %0, t;\n}" : "=r"(d) : "r"(s), "r"(c), "r"(off));
  return d;
}
__device__ __forceinline__ uint32_t softmax_top(const uint32_t (&s)[14], uint32_t lane, uint32_t c, uint32_t& last) {
  last = __shfl_sync(0xffffffffu, __byte_perm(s[12], s[13], 0x5410), lane & 28);
  const uint32_t a = hmax2(hmax2(hmax2(s[0], s[2]), s[4]), hmax2(hmax2(s[6], s[8]), s[10]));
  const uint32_t b = hmax2(hmax2(hmax2(s[1], s[3]), s[5]), hmax2(hmax2(s[7], s[9]), s[11]));
  uint32_t m = hmax2(__byte_perm(a, b, 0x5410), __byte_perm(a, b, 0x7632));
  m = hmax2(m, __shfl_xor_sync(0xffffffffu, m, 1));
  m = hmax2(hmax2(m, last), __shfl_xor_sync(0xffffffffu, m, 2));
  return hmul2(m, c);
}
__device__ __forceinline__ void lds128(uint32_t a, uint32_t* v) {
  asm volatile("ld.shared.v4.b32 {%0, %1, %2, %3}, [%4];" : "=r"(v[0]), "=r"(v[1]), "=r"(v[2]), "=r"(v[3]) : "r"(a) : "memory");
}
template <int SUM, int VAL>
__device__ __forceinline__ void softmax_rows(const uint32_t (&s)[14], uint32_t top, uint32_t last, uint32_t c, uint32_t pad,
                                             uint32_t v_last, uint32_t (&pa)[12], uint32_t (&ov)[14]) {
  uint32_t off, v[6];
  lds128(v_last, v);
  lds64(v_last + 16, v[4], v[5]);
  asm("sub.rn.f16x2 %0, %1, %2;" : "=r"(off) : "r"(pad), "r"(top));
#pragma unroll
  for (int j = 0; j < 6; j++) {
    pa[2 * j] = exp2_scaled(s[2 * j], both<0>(c), both<0>(off));
    pa[2 * j + 1] = exp2_scaled(s[2 * j + 1], both<1>(c), both<1>(off));
  }
  const uint32_t p = exp2_scaled(last, c, off);
#pragma unroll
  for (int j = 0; j < 6; j++) {
    ov[VAL + 2 * j] = hmul2_lo(v[j], p);
    ov[VAL + 2 * j + 1] = hmul2_hi(v[j], p);
  }
  ov[SUM] = __byte_perm(p, p, 0x1010);
  ov[SUM + 1] = __byte_perm(p, p, 0x3232);
}
__device__ __forceinline__ void issue_pv(uint32_t (&ov)[14], const uint32_t (&pa)[12], uint64_t v_desc) {
#pragma unroll
  for (int k = 0; k < 3; k++) hmma_n56(ov, pa[4 * k], pa[4 * k + 1], pa[4 * k + 2], pa[4 * k + 3], desc_add(v_desc, k * 256));
}
__device__ __forceinline__ void sts128_if(bool on, uint32_t a, uint32_t v0, uint32_t v1, uint32_t v2, uint32_t v3) {
  asm volatile("{\n.reg .pred p;\nsetp.ne.u32 p, %5, 0;\n@p st.shared.v4.b32 [%0], {%1, %2, %3, %4};\n}"
               ::"r"(a), "r"(v0), "r"(v1), "r"(v2), "r"(v3), "r"((uint32_t)on) : "memory");
}
__device__ __forceinline__ void store_v(const uint32_t (&v)[24], uint32_t v_st, uint32_t v_last, bool full, bool first_row, uint32_t r) {
  if (full) {
#pragma unroll
    for (int j = 0; j < 12; j += 2)
      stsm4_t(v_st + (j / 6) * (A_V1 - A_V0) + (j % 6) * V_GROUP, hmul2_lo(v[2 * j], r), hmul2_hi(v[2 * j + 1], r), hmul2_lo(v[2 * j + 2], r),
              hmul2_hi(v[2 * j + 3], r));
  } else {
#pragma unroll
    for (int h = 0; h < 2; h++) {
      sts128_if(first_row, v_last + h * 128, hmul2_lo(v[12 * h], r), hmul2_lo(v[12 * h + 2], r), hmul2_lo(v[12 * h + 4], r),
                hmul2_lo(v[12 * h + 6], r));
      sts128_if(first_row, v_last + h * 128 + 16, hmul2_lo(v[12 * h + 8], r), hmul2_lo(v[12 * h + 10], r), 0u, 0u);
    }
    __syncwarp();
  }
}
__device__ __forceinline__ void issue_s(uint32_t (&s)[14], const uint32_t* qa, uint64_t k_desc) {
  hmma_n56_first(s, qa[0], qa[1], qa[2], qa[3], k_desc);
#pragma unroll
  for (int k = 1; k < 3; k++) hmma_n56(s, qa[4 * k], qa[4 * k + 1], qa[4 * k + 2], qa[4 * k + 3], desc_add(k_desc, k * 2 * K_CHUNK));
}
template <int SUM, int VAL>
__device__ __forceinline__ void pack_o(const uint32_t (&ov)[14], uint32_t* o) {
  const uint32_t p = pack_f16(rcp(fmaxf(h_lo(ov[SUM]), 0.5f)), rcp(fmaxf(h_lo(ov[SUM + 1]), 0.5f)));
#pragma unroll
  for (int j = 0; j < 6; j++) {
    o[2 * j] = hmul2_lo(ov[VAL + 2 * j], p);
    o[2 * j + 1] = hmul2_hi(ov[VAL + 2 * j + 1], p);
  }
}
template <bool OVER>
__device__ __forceinline__ void issue_proj(uint32_t (&d)[24], const uint32_t (&x)[48], uint64_t desc) {
  if (OVER) hmma_n96_over(d, x[0], x[1], x[2], x[3], desc);
  else hmma_n96_first(d, x[0], x[1], x[2], x[3], desc);
#pragma unroll
  for (int s = 1; s < 12; s++) hmma_n96(d, x[4 * s], x[4 * s + 1], x[4 * s + 2], x[4 * s + 3], desc_add(desc, s * W_STEP));
}
template <int FIRST>
__device__ __forceinline__ void issue_half(uint32_t (&d)[24], const uint32_t (&x)[48], uint64_t desc) {
  if (FIRST == 2) hmma_n96_over(d, x[0], x[1], x[2], x[3], desc);
  if (FIRST == 1) hmma_n96_first(d, x[0], x[1], x[2], x[3], desc);
#pragma unroll
  for (int s = FIRST ? 1 : 6; s < (FIRST ? 6 : 12); s++) hmma_n96(d, x[4 * s], x[4 * s + 1], x[4 * s + 2], x[4 * s + 3], desc_add(desc, s * W_STEP));
}
template <int N>
__device__ __forceinline__ void issue_out(uint32_t (&d)[48], const uint32_t* o, uint64_t desc) {
#pragma unroll
  for (int s = 0; s < N; s++) hmma_n192(d, o[4 * s], o[4 * s + 1], o[4 * s + 2], o[4 * s + 3], desc_add(desc, s * WO_STEP));
}

__device__ __forceinline__ void mma_bf16(float (&c)[4], uint32_t a0, uint32_t a1, uint32_t a2, uint32_t a3, uint32_t b0, uint32_t b1) {
  asm("mma.sync.aligned.m16n8k16.row.col.f32.bf16.bf16.f32 {%0, %1, %2, %3}, {%4, %5, %6, %7}, {%8, %9}, {%0, %1, %2, %3};"
      : "+f"(c[0]), "+f"(c[1]), "+f"(c[2]), "+f"(c[3]) : "r"(a0), "r"(a1), "r"(a2), "r"(a3), "r"(b0), "r"(b1));
}
__device__ __forceinline__ void mma_bf16_k8(float (&d)[4], uint32_t a0, uint32_t a1, uint32_t b, const float (&c)[4]) {
  asm("mma.sync.aligned.m16n8k8.row.col.f32.bf16.bf16.f32 {%0, %1, %2, %3}, {%4, %5}, {%6}, {%7, %8, %9, %10};"
      : "=f"(d[0]), "=f"(d[1]), "=f"(d[2]), "=f"(d[3]) : "r"(a0), "r"(a1), "r"(b), "f"(c[0]), "f"(c[1]), "f"(c[2]), "f"(c[3]));
}
__device__ __forceinline__ bool on_diagonal(uint32_t lane) { return (lane & 3) == (lane >> 3); }
__device__ __forceinline__ float column_stats(const uint32_t (&v)[24], uint32_t lane, uint32_t& hi, uint32_t& lo) {
  float sum[2][4] = {}, sq[2][4] = {}, sr[2][4] = {};
#pragma unroll
  for (int c = 0; c < 24; c += 4) mma_bf16(sum[(c >> 2) & 1], v[c], v[c + 1], v[c + 2], v[c + 3], 0x3F803F80u, 0x3F803F80u);
#pragma unroll
  for (int c = 0; c < 24; c += 2) {
    mma_bf16_k8(sq[(c >> 1) & 1], v[c], v[c + 1], v[c], sq[(c >> 1) & 1]);
    mma_bf16_k8(sr[(c >> 1) & 1], v[c], v[c + 1], v[c + 1], sr[(c >> 1) & 1]);
  }
  const float total = (sum[0][0] + sum[0][2]) + (sum[1][0] + sum[1][2]), mean = total * (1.f / 192.f);
  const bool diag = on_diagonal(lane);
  const float n2 = (lane & 4) ? (sq[0][1] + sq[1][1]) + (sr[0][3] + sr[1][3]) : (sq[0][0] + sq[1][0]) + (sr[0][2] + sr[1][2]);
  hi = diag ? __float_as_uint(n2) : 0u;
  lo = __float_as_uint((diag && n2 > 0.f) ? fmaxf(fmaf(-total, mean, n2), 0.f) : INFINITY);
  return mean;
}
__device__ __forceinline__ uint32_t warp_max_abs(const uint32_t (&v)[8]) {
  uint32_t m = v[0];
#pragma unroll
  for (int c = 1; c < 8; c++) asm("max.NaN.xorsign.abs.bf16x2 %0, %0, %1;" : "+r"(m) : "r"(v[c]));
  return __reduce_max_sync(0xffffffffu, max(m & 0x7fffu, (m >> 16) & 0x7fffu));
}
__device__ __forceinline__ bool norms_in_range(uint32_t hi, uint32_t lo) {
  return hi - 0x08800000u <= 0x7B000000u - 0x08800000u && lo >= hi - (12u << 23);
}
__device__ __forceinline__ int norm_exponent(uint32_t n2) { return (int)(0x453B8000u - n2) >> 24; }
__device__ __forceinline__ void scale_to_f16(uint32_t (&v)[8], uint32_t lane, int e, float mean) {
  const uint32_t ident = on_diagonal(lane) ? (uint32_t)(e + 127) << ((lane & 4) ? 23 : 7) : 0u;
  const float c0 = -mean * __uint_as_float((uint32_t)(e + 127) << 23), c[4] = {c0, c0, c0, c0};
#pragma unroll
  for (int i = 0; i < 8; i += 2) {
    float d[4];
    mma_bf16_k8(d, v[i], v[i + 1], ident, c);
    v[i] = pack_f16(d[0], d[1]);
    v[i + 1] = pack_f16(d[2], d[3]);
  }
}
__device__ __forceinline__ float pow2(int e) { return __uint_as_float((uint32_t)(min(max(e, -126), 127) + 127) << 23); }

constexpr uint32_t kUnits = 24;
constexpr uint32_t RAW_O = W_PART, RAW_RED = RAW_O + 32 * 384;
__device__ __forceinline__ void bulk_load(uint32_t dst, const void* src, uint32_t bytes, uint32_t bar) {
  asm volatile("cp.async.bulk.shared::cluster.global.mbarrier::complete_tx::bytes [%0], [%1], %2, [%3];"
               ::"r"(dst), "l"(src), "r"(bytes), "r"(bar) : "memory");
}
__device__ __forceinline__ void tile_load(uint32_t dst, const CUtensorMap* tm, uint32_t c0, uint32_t c1, uint32_t bar) {
  asm volatile("cp.async.bulk.tensor.2d.shared::cluster.global.tile.mbarrier::complete_tx::bytes [%0], [%1, {%2, %3}], [%4];"
               ::"r"(dst), "l"(tm), "r"(c0), "r"(c1), "r"(bar) : "memory");
}
__device__ __forceinline__ void request_unit(uint32_t u, uint32_t raw, uint32_t bar, const CUtensorMap* tmw, const CUtensorMap* tmwo) {
  const bool is_o = (u & 7) >= 6;
  const uint32_t pair = is_o ? u & 1 : (u & 7) / 3, part = is_o ? 1 : (u & 7) % 3;
  mbar_expect_tx(bar, is_o ? W_PART + 32 * 384 : W_PART);
#pragma unroll
  for (uint32_t i = 0; i < 3; i++) tile_load(raw + i * (192 * 64), tmw, ((part + 1) % 3) * 192 + pair * 96 + 32 * i, 0, bar);
  if (is_o) {
#pragma unroll
    for (uint32_t i = 0; i < 6; i++) tile_load(raw + RAW_O + i * (32 * 64), tmwo, 32 * i, pair * 96 + (u >> 3) * 32, bar);
  }
}
__device__ __forceinline__ void ldsm4_t(uint32_t a, uint32_t* v) {
  asm volatile("ldmatrix.sync.aligned.m8n8.x4.trans.shared.b16 {%0, %1, %2, %3}, [%4];" : "=r"(v[0]), "=r"(v[1]), "=r"(v[2]), "=r"(v[3]) : "r"(a) : "memory");
}
__device__ __forceinline__ void prepare_unit(uint32_t u, uint32_t wid, uint32_t lane, uint32_t raw, Scratch* scr) {
  const bool is_o = (u & 7) >= 6;
  const uint32_t third = u >> 3;
  uint32_t v[24], w[8];
  const uint32_t src = raw + (wid >> 2) * (192 * 64) + lane * 64 + (((wid ^ (lane >> 1)) & 3) << 4);
#pragma unroll
  for (int m = 0; m < 6; m++) ldsm4_t(src + m * (32 * 64), &v[4 * m]);
  uint32_t hi, lo, top = 0;
  const float mean = column_stats(v, lane, hi, lo);
  if (is_o) {
#pragma unroll
    for (int m = 0; m < 2; m++)
      ldsm4_t(raw + RAW_O + (wid >> 1) * (32 * 64) + lane * 64 + ((((2 * wid + m) ^ (lane >> 1)) & 3) << 4), &w[4 * m]);
    top = warp_max_abs(w);
  } else {
#pragma unroll
    for (int m = 0; m < 2; m++) ldsm4_t(src + (2 * third + m) * (32 * 64), &w[4 * m]);
  }
  hi = __reduce_max_sync(0xffffffffu, hi);
  lo = __reduce_min_sync(0xffffffffu, lo);
  if (lane == 0) {
    sts64(raw + RAW_RED + wid * 16, hi, lo);
    sts32(raw + RAW_RED + wid * 16 + 8, top);
  }
  asm volatile("bar.sync 4, 384;" ::: "memory");
  lds64(raw + RAW_RED + (lane % 12) * 16, hi, lo);
  top = lds32(raw + RAW_RED + (lane % 12) * 16 + 8);
  hi = __reduce_max_sync(0xffffffffu, hi);
  lo = __reduce_min_sync(0xffffffffu, lo);
  top = __reduce_max_sync(0xffffffffu, top);
  const int e = norm_exponent(hi);
  scale_to_f16(w, lane, is_o ? -e : e - 4, is_o ? 0.f : mean);
  const uint32_t mat = lane >> 3, at = (mat & 1) * 128 + (lane & 7) * 16;
#pragma unroll
  for (int m = 0; m < 2; m++)
    stsm4(raw + at + (is_o ? (mat >> 1) * WO_STEP + (2 * wid + m) * 256 : (2 * m + (mat >> 1)) * W_STEP + wid * 256), w[4 * m], w[4 * m + 1],
          w[4 * m + 2], w[4 * m + 3]);
  fence_async();
  asm volatile("bar.sync 4, 384;" ::: "memory");
  if (wid == 0 && lane == 0) {
    asm volatile("cp.async.bulk.global.shared::cta.bulk_group [%0], [%1], %2;\ncp.async.bulk.commit_group;"
                 ::"l"(scr->weights + (u & 7) * W_PART + third * (W_PART / 3)), "r"(raw), "n"(W_PART / 3) : "memory");
    const bool bad = is_o ? !(__uint_as_float(top << 16) * pow2(-e) <= 0.25f) : !norms_in_range(hi, lo);
    const uint32_t exponent = (!is_o && third == 0 && u % 3 != 1) ? (uint32_t)(e + 64) << (u < 3 ? 10 : 19) : 0u;
    asm volatile("cp.async.bulk.wait_group 0;" ::: "memory");
    asm volatile("red.relaxed.gpu.global.add.u32 [%0], %1;" ::"l"(&scr->ready), "r"(bad ? 33u : 1u + exponent) : "memory");
  }
  __syncwarp();
}

constexpr uint32_t REDO_BYTES = 75776;
static_assert(3 * REDO_BYTES <= OFF_TAIL && (3 * 49 * 192 + 49 * 144) * 2 <= REDO_BYTES, "redo scratch");
__device__ __forceinline__ float round_bf16(float x) { return __bfloat162float(__float2bfloat16(x)); }
__device__ __forceinline__ void redo_window(int c0, int y0, int t, uint32_t bar, uint8_t* scratch, const __nv_bfloat16* x,
                                            const __nv_bfloat16* dw, const __nv_bfloat16* wqkv, const __nv_bfloat16* wo,
                                            __nv_bfloat16* out) {
  __nv_bfloat16* x0 = reinterpret_cast<__nv_bfloat16*>(scratch);
  __nv_bfloat16* h = x0 + 49 * 192;
  __nv_bfloat16* o = h + 49 * 192;
  __nv_bfloat16* qkv = o + 49 * 192;
  bar_sync(bar);
#pragma unroll 1
  for (int i = t; i < 49 * 192; i += 128) {
    const int tok = i / 192, c = i % 192, y = y0 + tok / 7, xx = c0 + tok % 7;
    float pe = 0.f;
#pragma unroll 1
    for (int k = 0; k < 9; k++) {
      const int yy = y + k / 3 - 1, xj = xx + k % 3 - 1;
      const bool in = (uint32_t)yy < kImg && (uint32_t)xj < kImg;
      const float v = in ? __bfloat162float(x[((size_t)yy * kImg + xj) * kCh + c]) : 0.f;
      pe = round_bf16(pe + round_bf16(v * __bfloat162float(dw[k * kCh + c])));
    }
    x0[i] = __float2bfloat16(__bfloat162float(x[((size_t)y * kImg + xx) * kCh + c]) + pe);
  }
  bar_sync(bar);
  if (t < 49) {
    float s = 0.f, v = 0.f;
#pragma unroll 1
    for (int c = 0; c < 192; c++) s += __bfloat162float(x0[t * 192 + c]);
    const float mean = s * (1.f / 192.f);
#pragma unroll 1
    for (int c = 0; c < 192; c++) {
      const float d = __bfloat162float(x0[t * 192 + c]) - mean;
      v = fmaf(d, d, v);
    }
    const float m = round_bf16(mean), sd = round_bf16(sqrtf(round_bf16(round_bf16(v * (1.f / 192.f)) + 1e-5f)));
#pragma unroll 1
    for (int c = 0; c < 192; c++) h[t * 192 + c] = __float2bfloat16(round_bf16(__bfloat162float(x0[t * 192 + c]) - m) / sd);
  }
#pragma unroll 1
  for (int head = 0; head < 4; head++) {
    bar_sync(bar);
#pragma unroll 1
    for (int i = t; i < 49 * 144; i += 128) {
      const int tok = i / 144, n = i % 144, col = (n / 48) * 192 + head * 48 + n % 48;
      float a = 0.f;
#pragma unroll 4
      for (int c = 0; c < 192; c++) a = fmaf(__bfloat162float(h[tok * 192 + c]), __bfloat162float(wqkv[c * 576 + col]), a);
      qkv[i] = __float2bfloat16(a);
    }
    bar_sync(bar);
    if (t < 49) {
      float p[49], m = -INFINITY, s = 0.f;
#pragma unroll
      for (int b = 0; b < 49; b++) {
        float a = 0.f;
#pragma unroll 4
        for (int d = 0; d < 48; d++) a = fmaf(__bfloat162float(qkv[t * 144 + d]), __bfloat162float(qkv[b * 144 + 48 + d]), a);
        p[b] = round_bf16(round_bf16(a) * 0.14433757f);
        m = fmaxf(m, p[b]);
      }
#pragma unroll
      for (int b = 0; b < 49; b++) {
        p[b] = expf(p[b] - m);
        s += p[b];
      }
#pragma unroll
      for (int b = 0; b < 49; b++) p[b] = round_bf16(p[b] / s);
#pragma unroll 1
      for (int d = 0; d < 48; d++) {
        float a = 0.f;
#pragma unroll
        for (int b = 0; b < 49; b++) a = fmaf(p[b], __bfloat162float(qkv[b * 144 + 96 + d]), a);
        o[t * 192 + head * 48 + d] = __float2bfloat16(a);
      }
    }
  }
  bar_sync(bar);
#pragma unroll 1
  for (int i = t; i < 49 * 192; i += 128) {
    const int tok = i / 192, n = i % 192;
    float a = 0.f;
#pragma unroll 4
    for (int c = 0; c < 192; c++) a = fmaf(__bfloat162float(o[tok * 192 + c]), __bfloat162float(wo[c * kCh + n]), a);
    out[((size_t)(y0 + tok / 7) * kImg + c0 + tok % 7) * kCh + n] = __float2bfloat16(__bfloat162float(x0[tok * 192 + n]) + round_bf16(a));
  }
}

__device__ __forceinline__ uint32_t fresh_tid() {
  uint32_t t;
  asm volatile("mov.u32 %0, %%tid.x;" : "=r"(t));
  return t;
}
struct Split {
  uint32_t top, rows, alone, share, pool;
  uint32_t magic[2];
};
struct Windows {
  uint32_t first, count, alone, jump, height, row0, magic;
  __device__ __forceinline__ explicit Windows(const Split& s) {
    uint32_t b;
    asm volatile("mov.u32 %0, %%ctaid.x;" : "=r"(b));
    const bool upper = b < s.top;
    const uint32_t i = upper ? 0 : b - s.top;
    height = upper ? s.rows : kWinPerCol - s.rows;
    row0 = upper ? 0 : s.rows;
    magic = upper ? s.magic[0] : s.magic[1];
    alone = upper ? s.rows : s.alone;
    first = upper ? b * s.rows : i * s.alone;
    count = upper ? s.rows : s.alone + s.share;
    jump = (gridDim.x - s.top - 1 - i) * s.alone + i * s.share;
  }
  __device__ __forceinline__ bool at(uint32_t j, uint32_t& col, uint32_t& row) const {
    const uint32_t v = first + j + (j >= alone ? jump : 0);
    col = (v * magic) >> 20;
    row = v - col * height + row0;
    return row == row0 || j == alone;
  }
  __device__ __forceinline__ void at(uint32_t j, uint32_t& col, uint32_t& row, uint32_t extra) const {
    at(j, col, row);
    if (j == count) {
      col = extra & 255;
      row = extra >> 8;
    }
  }
};
template <uint32_t BYTES>
__device__ __forceinline__ void load_rows(uint32_t dst, const CUtensorMap* tm, uint32_t ch, int x, int y, uint32_t bar) {
  asm volatile("{\n.reg .pred p;\nelect.sync _|p, 0xffffffff;\n"
               "@p mbarrier.arrive.expect_tx.shared::cta.b64 _, [%5], %6;\n"
               "@p cp.async.bulk.tensor.3d.shared::cluster.global.tile.mbarrier::complete_tx::bytes [%0], [%1, {%2, %3, %4}], [%5];\n}"
               ::"r"(dst), "l"(tm), "r"(ch), "r"(x), "r"(y), "r"(bar), "n"(BYTES) : "memory");
}
__device__ __forceinline__ void prefetch_box(const CUtensorMap* tm, int x, int y) {
  asm volatile("cp.async.bulk.prefetch.tensor.3d.L2.global.tile [%0, {%1, %2, %3}];" ::"l"(tm), "r"(0), "r"(x), "r"(y) : "memory");
}
__device__ __forceinline__ void prefetch_rows(const CUtensorMap* tm, int x, int y) {
  asm volatile("{\n.reg .pred p;\nelect.sync _|p, 0xffffffff;\n"
               "@p cp.async.bulk.prefetch.tensor.3d.L2.global.tile [%0, {%1, %2, %3}];\n}" ::"l"(tm), "r"(0), "r"(x), "r"(y) : "memory");
}
__device__ __forceinline__ void store_group(const CUtensorMap* tm, uint32_t src, uint32_t ch, uint32_t x, uint32_t y) {
  asm volatile("cp.async.bulk.tensor.3d.global.shared::cta.tile.bulk_group [%0, {%2, %3, %4}], [%1];"
               ::"l"(tm), "r"(src), "r"(ch), "r"(x), "r"(y) : "memory");
}

template <int N> struct Int { static constexpr int value = N; };
struct Conv {
  uint32_t wt[9], prev[9], acc[7];
  __device__ __forceinline__ void begin(const uint32_t (&cur)[9]) {
#pragma unroll
    for (int x = 0; x < 7; x++) {
      uint32_t a = bmul2(prev[x], wt[0]);
      a = bfma2(prev[x + 1], wt[1], a);
      a = bfma2(prev[x + 2], wt[2], a);
#pragma unroll
      for (int t = 0; t < 3; t++) a = bfma2(cur[x + t], wt[3 + t], a);
      acc[x] = a;
    }
#pragma unroll
    for (int x = 0; x < 9; x++) prev[x] = cur[x];
  }
  __device__ __forceinline__ void start_column(uint32_t slot0, uint32_t bar0, uint32_t parity0, uint32_t slot1, uint32_t bar1,
                                               uint32_t parity1, uint32_t lane, uint32_t dump, bool request, const CUtensorMap* tm,
                                               uint32_t ch, int x, int y) {
    uint32_t cur[9];
    mbar_wait(bar0, parity0);
#pragma unroll
    for (int i = 0; i < 9; i++) prev[i] = lds32(slot0 + lane * 4 + i * 128);
    sts32(dump, prev[0] ^ prev[1] ^ prev[2] ^ prev[3] ^ prev[4] ^ prev[5] ^ prev[6] ^ prev[7] ^ prev[8]);
    if (request) load_rows<HALO_ROW>(slot0, tm, ch, x, y, bar0);
    mbar_wait(bar1, parity1);
#pragma unroll
    for (int i = 0; i < 9; i++) cur[i] = lds32(slot1 + lane * 4 + i * 128);
    begin(cur);
    sts32(dump, acc[0] ^ acc[3] ^ acc[6]);
    if (request) load_rows<HALO_ROW>(slot1, tm, ch, x, y + 1, bar1);
  }
  __device__ __forceinline__ void row_at(uint32_t src, uint32_t dst, uint32_t t) {
    uint32_t cur[9];
#pragma unroll
    for (int x = 0; x < 9; x++) cur[x] = lds32(src + x * 128);
#pragma unroll
    for (int x = 0; x < 7; x++) {
      uint32_t a = acc[x];
#pragma unroll
      for (int i = 0; i < 3; i++) a = bfma2(cur[x + i], wt[6 + i], a);
      sts32((dst ^ (((t + x) & 7) << 4)) + x * 128, bf16x2_to_f16x2(badd2(prev[x + 1], a)));
    }
    begin(cur);
  }
  template <int R>
  __device__ __forceinline__ void row(uint32_t src, uint32_t dst, uint32_t at) {
    uint32_t cur[9];
#pragma unroll
    for (int x = 0; x < 9; x++) cur[x] = lds32(src + x * 128);
#pragma unroll
    for (int x = 0; x < 7; x++) {
      uint32_t a = acc[x];
#pragma unroll
      for (int t = 0; t < 3; t++) a = bfma2(cur[x + t], wt[6 + t], a);
      sts32((dst ^ (((R * 7 + x) & 7) << 4)) + at + x * 128, bf16x2_to_f16x2(badd2(prev[x + 1], a)));
    }
    begin(cur);
  }
};

__global__ void __launch_bounds__(512, 1)
davit_window_attn_kernel(const __grid_constant__ CUtensorMap tm1, const __grid_constant__ CUtensorMap tm7c,
                         const __grid_constant__ CUtensorMap tm7, const __grid_constant__ CUtensorMap tmo,
                         const __grid_constant__ CUtensorMap tmw, const __grid_constant__ CUtensorMap tmwo,
                         const __nv_bfloat16* __restrict__ dw, const __nv_bfloat16* __restrict__ x_raw,
                         const __nv_bfloat16* __restrict__ wqkv_raw, const __nv_bfloat16* __restrict__ wo_raw,
                         __nv_bfloat16* __restrict__ out, Scratch* __restrict__ scr, const Split split) {
  extern __shared__ __align__(1024) uint8_t smem_raw[];
  const uint32_t sb = (uint32_t)__cvta_generic_to_shared(smem_raw);
  const uint32_t tail = sb + OFF_TAIL;
  uint32_t wt[9];
  {
    const uint32_t tid = threadIdx.x;
    const uint32_t wid = __shfl_sync(0xffffffffu, tid >> 5, 0), lane = tid & 31;
    if (wid > 12) {
      const uint32_t chunk = wid - 13, hbar = tail + T_HALO + 24 * chunk, rbar = tail + T_ROW + 16 * chunk;
      if (lane == 0) {
        mbar_init(hbar, 1);
        mbar_init(hbar + 8, 1);
        mbar_init(hbar + 16, 1);
        mbar_init(rbar, 1);
        mbar_init(rbar + 8, 1);
        if (wid == 13) mbar_init(tail + T_RAW, 1);
        if (wid == 14) mbar_init(tail + T_CLAIM, 1);
        fence_async();
      }
      __syncwarp();
      if (blockIdx.x < kUnits) {
        if (wid == 13 && lane == 0) request_unit(blockIdx.x, sb + OFF_RING, tail + T_RAW, &tmw, &tmwo);
        asm volatile("bar.sync 5, 96;" ::: "memory");
      }
      uint32_t col, row;
      Windows(split).at(0, col, row);
      const int x = (int)col * 7 - 1, y = (int)row * 7;
      const uint32_t halo = sb + OFF_HALO + chunk * 3 * HALO_ROW;
      load_rows<HALO_ROW>(halo, &tm1, chunk * 64, x, y - 1, hbar);
      load_rows<HALO_ROW>(halo + HALO_ROW, &tm1, chunk * 64, x, y, hbar + 8);
      load_rows<7 * HALO_ROW>(sb + OFF_KV + chunk * 7 * HALO_ROW, &tm7c, chunk * 64, x, y + 1, rbar);
#pragma unroll
      for (int i = 0; i < 9; i++) wt[i] = __ldg(reinterpret_cast<const uint32_t*>(dw) + i * (kCh / 2) + chunk * 32 + lane);
    } else {
      if (lane == 0) {
        if (wid < 12) {
          const uint32_t i = 2 * wid, counts = (uint32_t)((wid < 8 ? 0x4144444333CCC111ull >> (8 * wid) : 0x11444144u >> (8 * wid - 64)));
          mbar_init(tail + 8 * (i < 11 ? i : i + 9), counts & 15);
          if (wid < 11)
          mbar_init(tail + 8 * (i < 10 ? i + 1 : i + 10), (counts >> 4) & 15);
          fence_async();
        }
      }
      if (wid == 12) {
        for (uint32_t line = blockIdx.x + gridDim.x * lane; line < 2304; line += gridDim.x * 32) {
          const uint8_t* p = (line < 1728) ? reinterpret_cast<const uint8_t*>(wqkv_raw) + line * 128
                                           : reinterpret_cast<const uint8_t*>(wo_raw) + (line - 1728) * 128;
          asm volatile("prefetch.global.L2 [%0];" ::"l"(p));
        }
        if (lane < 7) sts32(tail + T_ZERO + 4 * lane, 0u);
      }
    }
    __syncthreads();
    if (wid < 12) {
#pragma unroll 1
      for (uint32_t u = blockIdx.x, i = 0; u < kUnits; u += gridDim.x, i++) {
        if (i) {
          asm volatile("bar.sync 4, 384;" ::: "memory");
          if (tid == 0) request_unit(u, sb + OFF_RING, tail + T_RAW, &tmw, &tmwo);
        }
        mbar_wait(tail + T_RAW, i & 1);
        prepare_unit(u, wid, lane, sb + OFF_RING, scr);
      }
    }
  }

  if (threadIdx.x >= 384) {
    asm volatile("setmaxnreg.dec.sync.aligned.u32 %0;" ::"n"(56));
    const uint32_t tid = fresh_tid();
    const uint32_t warp = __shfl_sync(0xffffffffu, (tid >> 5) & 3, 0), lane = tid & 31;
    if (warp == 0) {
      if (lane == 0) {
        const Windows win(split);
        uint32_t spins = 0, seen;
        while (true) {
          asm volatile("ld.acquire.gpu.global.u32 %0, [%1];" : "=r"(seen) : "l"(&scr->ready) : "memory");
          if ((seen & 31) == kUnits) break;
          if (++spins > (1u << 22)) __trap();
        }
        asm volatile("fence.proxy.async.global;" ::: "memory");
        const uint8_t* w = scr->weights;
        {
          const int e0 = (int)((seen >> 10) & 511) - 128, e1 = (int)(seen >> 19) - 128;
          sts32(tail + T_SCALE, pack_f16(fmaxf(0.20823509f * pow2(9 - e0), 0x1p-24f), fmaxf(0.20823509f * pow2(9 - e1), 0x1p-24f)));
          if ((seen & 0x3E0u) || e0 < 1 || e1 < 1) sts32(tail + T_ALL, 1u);
        }
#pragma unroll
        for (uint32_t s = 0; s < 3; s++) {
          mbar_expect_tx(tail + T_FULL + 8 * s, W_PART);
          bulk_load(sb + OFF_RING + s * W_PART, w + s * W_PART, W_PART, tail + T_FULL + 8 * s);
        }
#pragma unroll 1
        for (uint32_t j = 2; j < 4 && j < win.count; j++) {
          uint32_t col, row;
          const bool fresh = win.at(j, col, row);
          if (j == 3 || fresh) prefetch_box(&tm7, 7 * col - 1, 7 * row + 1);
          if (fresh) prefetch_box(&tm7, 7 * col - 1, 7 * row - 1);
        }
        if (atomicInc(&scr->passed, gridDim.x - 1) == gridDim.x - 1) scr->ready = 0;
        const uint32_t uses = 8 * (win.count / 3 + 1);
        uint32_t s = 0, parity = 0;
#pragma unroll 1
        for (uint32_t u = 3; u < uses; u++) {
          mbar_wait(tail + T_EMPTY + 8 * s, parity);
          mbar_expect_tx(tail + T_FULL + 8 * s, W_PART);
          bulk_load(sb + OFF_RING + s * W_PART, w + (u & 7) * W_PART, W_PART, tail + T_FULL + 8 * s);
          s = (s == 2) ? 0 : s + 1;
          parity ^= (s == 0);
        }
      }
    } else {
      Conv cv;
#pragma unroll
      for (int i = 0; i < 9; i++) cv.wt[i] = wt[i];
      {
        const uint32_t chunk = warp - 1, halo = sb + OFF_HALO + chunk * 3 * HALO_ROW, hbar = tail + T_HALO + 24 * chunk;
        const Windows win(split);
        uint32_t col, row, cn, rn;
        const uint32_t staged = (win.count > 1 && !win.at(1, col, row)) ? 2 : 1;
        const bool fresh = win.at(staged, cn, rn);
        const int xn = 7 * cn - 1, yn = fresh ? 7 * rn - 1 : 7 * rn + 1;
        if (staged < win.count) load_rows<HALO_ROW>(halo + 2 * HALO_ROW, &tm1, chunk * 64, xn, yn, hbar + 16);
        cv.start_column(halo, hbar, 0, halo + HALO_ROW, hbar + 8, 0, lane, tail + T_DUMP, staged < win.count, &tm1, chunk * 64, xn, yn + 1);
        if (staged == 2)
          load_rows<7 * HALO_ROW>(sb + OFF_KV + (3 + chunk) * 7 * HALO_ROW, &tm7c, chunk * 64, 7 * col - 1, 7 * row + 1,
                                  tail + T_ROW + 16 * chunk + 8);
#pragma unroll 1
        for (uint32_t i = 0; i < staged; i++) {
          mbar_wait(tail + T_ROW + 16 * chunk + 8 * i, 0);
#pragma unroll 1
          for (uint32_t r = 0; r < 7; r++)
            cv.row_at(sb + OFF_KV + ((3 * i + chunk) * 7 + r) * HALO_ROW + lane * 4,
                      sb + OFF_X0 + chunk * X0_CHUNK + lane * 4 + (7 * i + r) * X0_ROW, 7 * r);
          __syncwarp();
          arrive_elected(tail + T_X0FULL + 8 * i);
          if (i == 0 && chunk == 0 && staged < win.count) prefetch_rows(&tm7, xn, yn + 3);
        }
      }
      const uint32_t chunk = __shfl_sync(0xffffffffu, (fresh_tid() >> 5) & 3, 0) - 1, ch = chunk * 64;
      const uint32_t halo = sb + OFF_HALO + chunk * 3 * HALO_ROW, hbar = tail + T_HALO + 24 * chunk;
      const uint32_t src = halo + lane * 4, dst = sb + OFF_X0 + chunk * X0_CHUNK + lane * 4;
      const Windows win(split);
      uint32_t count = win.count;
      uint32_t col, row;
      const uint32_t staged = (count > 1 && !win.at(1, col, row)) ? 2 : 1;
      bool fresh = win.at(staged, col, row);
      uint32_t s0 = 2, p0 = 0;
#pragma unroll 1
      for (uint32_t j = staged; j < count; j++) {
        int x = (int)col * 7 - 1, y = (int)row * 7;
        uint32_t at = 7 * j % kRows * X0_ROW;
        if (fresh) {
          const uint32_t s1 = (s0 == 2) ? 0 : s0 + 1;
          cv.start_column(halo + s0 * HALO_ROW, hbar + 8 * s0, p0, halo + s1 * HALO_ROW, hbar + 8 * s1, p0 ^ (s0 == 2), lane, tail + T_DUMP, true,
                          &tm1, ch, x, y + 2);
          p0 ^= (s0 != 0);
          s0 = (s0 == 0) ? 2 : s0 - 1;
        }
        const uint32_t slot[3] = {s0, (s0 == 2) ? 0 : s0 + 1, (s0 == 0) ? 2 : s0 - 1}, parity[3] = {p0, p0 ^ (s0 == 2), p0 ^ (s0 != 0)};
        if (chunk == 0 && j + 1 == win.count) {
          if (lane == 0) {
            const uint32_t i = atomicInc(&scr->claims, gridDim.x - 1);
            uint32_t extra = ~0u;
            if (i < split.pool) {
              const uint32_t v = kWinPerCol * (kWinPerCol - split.rows) - split.pool + i, c = (v * split.magic[1]) >> 20;
              extra = c + 256 * (v - c * (kWinPerCol - split.rows) + split.rows);
              prefetch_box(&tm7, 7 * c - 1, 7 * (extra >> 8) - 1);
              prefetch_box(&tm7, 7 * c - 1, 7 * (extra >> 8) + 1);
            }
            sts32(tail + T_EXTRA, extra);
            mbar_arrive(tail + T_CLAIM);
          }
          __syncwarp();
        }
        if (chunk == 0 && j + 2 < win.count) {
          if (win.at(j + 2, col, row)) prefetch_rows(&tm7, 7 * col - 1, 7 * row - 1);
          prefetch_rows(&tm7, 7 * col - 1, 7 * row + 1);
        }
        fresh = win.at(j + 1, col, row);
        auto step = [&](auto r) {
          constexpr int R = decltype(r)::value;
          if (R == kRows - 14) {
            mbar_wait(tail + T_X0FREE + 8 * (j & 1), ((j >> 1) & 1) ^ 1);
          }
          if (R == 4) {
            if (j + 1 == win.count) {
              mbar_wait(tail + T_CLAIM, 0);
              const uint32_t extra = __shfl_sync(0xffffffffu, lds32(tail + T_EXTRA), 0);
              count += (extra != ~0u);
              col = extra & 255;
              row = extra >> 8;
              fresh = true;
            }
            x = (int)col * 7 - 1;
            y = (int)row * 7 - (fresh ? 9 : 7);
          }
          mbar_wait(hbar + 8 * slot[R % 3], parity[R % 3] ^ ((R / 3) & 1));
          cv.template row<R>(src + slot[R % 3] * HALO_ROW, dst, at);
          if (R < 4 || j + 1 < count) load_rows<HALO_ROW>(halo + slot[R % 3] * HALO_ROW, &tm1, ch, x, y + R + 4, hbar + 8 * slot[R % 3]);
          at = (at == (kRows - 1) * X0_ROW) ? 0 : at + X0_ROW;
        };
        step(Int<0>()); step(Int<1>()); step(Int<2>()); step(Int<3>()); step(Int<4>()); step(Int<5>()); step(Int<6>());
        __syncwarp();
        arrive_elected(tail + T_X0FULL + 8 * (j % 3));
        s0 = slot[1];
        p0 = parity[1];
      }
    }
    __syncwarp();
    asm volatile("bar.sync 0, 512;" ::: "memory");
  } else {
    asm volatile("setmaxnreg.inc.sync.aligned.u32 %0;" ::"n"(152));
    const uint32_t wid = __shfl_sync(0xffffffffu, fresh_tid() >> 5, 0);
    const uint32_t wg = wid >> 2, warp = wid & 3;
    uint32_t lane;
    asm volatile("mov.u32 %0, %%laneid;" : "=r"(lane));
    const uint32_t count = Windows(split).count;
    const uint32_t q = lane & 3, mat = lane >> 3, row = lane & 7;
    const uint32_t area = sb + OFF_KV + wg * KV_SIZE;
    const uint32_t bars = tail + T_WG + 32 * wg;
    const bool full = warp < 3;
    const bool valid = full || lane < 4;
    const bool lead = lane == 0;
    uint32_t k_st, v_st, x_ld, x_mask, x_row, o_st;
    {
      const uint32_t rowg = full ? 2 * warp + (mat & 1) : 6, colg = full ? (mat >> 1) : (mat & 1);
      k_st = full ? area + A_K0 + colg * K_CHUNK + rowg * 128 + row * 16 : area + A_K0 + 768 + q * 4;
      v_st = full ? area + A_V0 + colg * V_GROUP + rowg * 128 + row * 16 : area + A_ONES + lane * 16;
      const uint32_t t = 16 * warp + row + 8 * (mat & 1);
      x_ld = (t < 49) ? sb + OFF_X0 + t * 128 + (((mat >> 1) ^ row) << 4) : tail + T_ZERO;
      x_mask = (t < 49) ? ~0u : 0u;
      x_row = t / 7;
      const uint32_t a = area + (full ? t : 48) * 64;
      o_st = a + (((full ? (mat >> 1) : 0) ^ ((a >> 7) & 3)) << 4) + (full ? 0 : 4 * q);
    }
    const uint32_t v_last = area + A_LAST + q * 32;
    const uint32_t pad = (valid ? 0u : 0xFC00u) | (full ? 0u : 0xFC000000u);
    const uint64_t k_desc = make_desc(area + A_K0, K_CHUNK, 128);
    const uint64_t v_desc = make_desc(area + A_V0, 128, V_GROUP);
    const uint64_t w_desc = make_desc(sb + OFF_RING, 128, 256);
    if (wg == 2) asm volatile("bar.arrive 8, 256;" ::: "memory");
    auto send_output = [&](uint32_t j, uint32_t parity, bool last) {
      uint32_t col, row;
      if (last) Windows(split).at(j, col, row, lds32(tail + T_EXTRA));
      else Windows(split).at(j, col, row);
      mbar_wait(bars + B_OUTRDY, parity);
#pragma unroll
      for (int i = 0; i < 6; i++) store_group(&tmo, area + i * OUT_GROUP, 32 * i, 7 * col, 7 * row);
      asm volatile("cp.async.bulk.commit_group;" ::: "memory");
    };
    uint32_t round = 0;
#pragma unroll 1
    for (; 3 * round + wg <= count; round++) {
      const uint32_t r = __shfl_sync(0xffffffffu, round, 0), j = 3 * r + wg, ph = r & 1;
      if (j == count) {
        mbar_wait(tail + T_CLAIM, 0);
        if (__shfl_sync(0xffffffffu, lds32(tail + T_EXTRA), 0) == ~0u) break;
      }
      const uint32_t m = 8 * r / 3, rot = 8 * r - 3 * m;
      const uint32_t ra = 8 * rot, rb = (rot == 2) ? 0 : ra + 8, rc = (rot == 0) ? 16 : ra - 8;
      const uint32_t pa = m & 1, pb = pa ^ (rot == 2), pc = pa ^ (rot != 0);
      uint32_t x[48], ka[24], va[24], oa[24], ob[24], rr, scales;
      uint32_t (&qa)[24] = ka;
      uint32_t sc0[14], sc1[14], pa0[12], pa1[12], ov0[14], ov1[14];
      mbar_wait(tail + T_X0FULL + 8 * wg, ph);
      {
        asm volatile("" : "+r"(x_mask));
        const uint32_t at = 7 * j % kRows;
        const uint32_t a = x_ld + ((at * X0_ROW - (x_row >= kRows - at ? X0_CHUNK : 0)) & x_mask);
#pragma unroll
        for (int s = 0; s < 12; s++)
          ldsm4((a ^ (((s & 3) << 5) & x_mask)) + ((s >> 2) * X0_CHUNK & x_mask), x[4 * s], x[4 * s + 1], x[4 * s + 2], x[4 * s + 3]);
      }
      warp_arrive(tail + T_X0FREE + 8 * (j & 1), lead);
#pragma unroll
      for (int p = 0; p < 2; p++) {
        asm volatile("bar.sync %0, 256;" ::"r"(8 + wg) : "memory");
        mbar_wait(tail + T_FULL + ra, pa ^ p);
        wg_fence();
        issue_proj<false>(ka, x, desc_at(w_desc, ra * (W_PART / 8)));
        wg_commit();
        if (p == 0) {
          if (!full && lead && r > 0) send_output(j - 3, ph ^ 1, false);
          __syncwarp();
        }
        if (p == 1) {
          wg_wait<1>();
          fence_regs(ov1);
          if (lead) mbar_arrive(bars + B_KVFREE);
          pack_o<0, 2>(ov1, &oa[12]);
        }
        mbar_wait(tail + T_FULL + rb, pb ^ p);
        wg_fence();
        {
          const uint64_t d = desc_at(w_desc, rb * (W_PART / 8));
          issue_half<1>(va, x, d);
          wg_commit();
          wg_wait<1>();
          if (lead) mbar_arrive(tail + T_EMPTY + ra);
          __syncwarp();
          issue_half<0>(va, x, d);
          wg_commit();
        }
        asm volatile("bar.arrive %0, 256;" ::"r"(wg == 2 ? 8 : 9 + wg) : "memory");
        if (p == 0) {
          scales = __shfl_sync(0xffffffffu, lds32(tail + T_SCALE), 0);
          const bool odd = q & 1;
          uint32_t lane_sums[2];
          lane_stats_packed(x, lane_sums);
          const uint32_t packed = quad_stats_packed(lane_sums, odd);
          float sum = h_lo(packed), squares = h_hi(packed);
          const bool fine = (squares >= 0.1875f || (pad & (odd ? 0xFC000000u : 0xFC00u))) & (squares <= 65504.f) & (sum * sum <= 96.f * squares);
          const bool exact = !__all_sync(0xffffffffu, fine);
          if (exact) {
            wg_wait<0>();
            row_stats(x, odd, sum, squares);
          }
          const float mean = sum * (1.f / 192.f);
          const float rs = 16.f * rsqrt_fast(fmaxf(fmaf(squares, 1.f / 192.f, -mean * mean), 0.f) + 1e-5f);
          if (exact) {
            const uint32_t range = __reduce_max_sync(0xffffffffu, __float_as_uint(squares * fmaxf(rs * rs, 1.f)));
            if ((range > 0x4D400000u || (range != 0u && range < 0x4585A800u)) && lead) {
              scr->redo[blockIdx.x + gridDim.x * j] = 1;
              sts32(tail + T_ANY, 1u);
            }
          }
          const float o = __shfl_xor_sync(0xffffffffu, rs, 1);
          rr = pack_f16(odd ? o : rs, odd ? rs : o);
          if (!full && lead) {
            asm volatile("cp.async.bulk.wait_group.read 0;" ::: "memory");
            mbar_arrive(bars + B_OUTFREE);
          }
          __syncwarp();
          mbar_wait(bars + B_OUTFREE, ph);
        } else {
          mbar_wait(bars + B_KVFREE, 0);
        }
        fence_regs(ka);
        store_k(ka, k_st, full, lane < 4, rr);
        mbar_wait(tail + T_FULL + rc, pc ^ p);
        wg_fence();
        {
          const uint64_t d = desc_at(w_desc, rc * (W_PART / 8));
          issue_half<2>(qa, x, d);
          wg_commit();
          wg_wait<1>();
          if (lead) mbar_arrive(tail + T_EMPTY + rb);
          __syncwarp();
          issue_half<0>(qa, x, d);
          wg_commit();
        }
        fence_regs(va);
        if (p == 0 && !full) {
          sts128_if(true, v_st, 0x3C003C00u, 0x3C003C00u, 0x3C003C00u, 0x3C003C00u);
          sts128_if(lane < 16, v_st + 512, 0x3C003C00u, 0x3C003C00u, 0x3C003C00u, 0x3C003C00u);
        }
        store_v(va, v_st, v_last, full, lane < 4, rr);
        fence_async();
        warp_arrive(bars + B_KVRDY, lead);
        wg_wait<0>();
        fence_regs(qa);
        if (lead) mbar_arrive(tail + T_EMPTY + rc);
        {
          const uint32_t rq = hmul2(rr, 0x18001800u);
#pragma unroll
          for (int i = 0; i < 24; i += 2) {
            qa[i] = hmul2_lo(qa[i], rq);
            qa[i + 1] = hmul2_hi(qa[i + 1], rq);
          }
        }
        const uint32_t cr = (p == 0) ? both<0>(scales) : both<1>(scales);
        mbar_wait(bars + B_KVRDY, p);

        wg_fence();
        issue_s(sc0, &qa[0], desc_at(k_desc, 0));
        wg_commit();
        uint32_t top0, top1, last0, last1;
        if (p == 0) {
          issue_s(sc1, &qa[12], desc_at(k_desc, A_K1));
          wg_commit();
          wg_wait<1>();
          fence_regs(sc0);
          top0 = softmax_top(sc0, lane, cr, last0);
          softmax_rows<12, 0>(sc0, top0, last0, cr, pad, v_last, pa0, ov0);
          wg_fence();
          issue_pv(ov0, pa0, desc_at(v_desc, 0));
          wg_commit();
          wg_wait<1>();
          fence_regs(sc1);
          top1 = softmax_top(sc1, lane, cr, last1);
          softmax_rows<0, 2>(sc1, top1, last1, cr, pad, v_last + 128, pa1, ov1);
        } else {
          wg_wait<0>();
          fence_regs(sc0);
          wg_fence();
          issue_s(sc1, &qa[12], desc_at(k_desc, A_K1));
          wg_commit();
          top0 = softmax_top(sc0, lane, cr, last0);
          wg_wait<0>();
          fence_regs(sc1);
          softmax_rows<12, 0>(sc0, top0, last0, cr, pad, v_last, pa0, ov0);
          mbar_wait(tail + T_FULL + ra, pa);
          wg_fence();
          issue_pv(ov0, pa0, desc_at(v_desc, 0));
          wg_commit();
          issue_out<6>(x, oa, desc_at(w_desc, ra * (W_PART / 8)));
          wg_commit();
          top1 = softmax_top(sc1, lane, cr, last1);
          wg_wait<1>();
          fence_regs(ov0);
          softmax_rows<0, 2>(sc1, top1, last1, cr, pad, v_last + 128, pa1, ov1);
        }
        wg_fence();
        issue_pv(ov1, pa1, desc_at(v_desc, A_ONES - A_V0));
        wg_commit();
        wg_wait<1>();
        if (p == 0) fence_regs(ov0);
        else if (lead) mbar_arrive(tail + T_EMPTY + ra);
        {
          uint32_t big;
          asm("{\n.reg .pred p, q;\n.reg .b32 t;\nmax.xorsign.abs.f16x2 t, %1, %2;\nabs.f16x2 t, t;\nsetp.gt.f16x2 p|q, t, %3;\n"
              "or.pred p, p, q;\nselp.u32 %0, 1, 0, p;\n}" : "=r"(big) : "r"(top0), "r"(top1), "r"(0x60006000u));
          if (__any_sync(0xffffffffu, big) && lead) {
            scr->redo[blockIdx.x + gridDim.x * j] = 1;
            sts32(tail + T_ANY, 1u);
          }
          __syncwarp();
        }
        uint32_t (&o)[24] = (p == 0) ? oa : ob;
        pack_o<12, 0>(ov0, &o[0]);
        if (p == 1) {
          mbar_wait(tail + T_FULL + rb, pb);
          wg_fence();
          issue_out<3>(x, &ob[0], desc_at(w_desc, rb * (W_PART / 8)));
          wg_commit();
          wg_wait<1>();
          fence_regs(ov1);
          if (lead) mbar_arrive(bars + B_KVFREE);
          pack_o<0, 2>(ov1, &o[12]);
        }
      }
      wg_fence();
      issue_out<3>(x, &ob[12], desc_at(w_desc, rb * (W_PART / 8) + 3 * WO_STEP));
      wg_commit();
      mbar_wait(bars + B_KVFREE, 1);
      wg_wait<0>();
      fence_regs(x);
      if (lead) mbar_arrive(tail + T_EMPTY + rb);
      asm volatile("" : "+r"(o_st));
      if (full) {
#pragma unroll
        for (int s = 0; s < 12; s++)
          stsm4((o_st ^ (((s ^ (s >> 1)) & 1) << 5)) + (s >> 1) * OUT_GROUP, f16x2_to_bf16x2(x[4 * s]), f16x2_to_bf16x2(x[4 * s + 1]),
                f16x2_to_bf16x2(x[4 * s + 2]), f16x2_to_bf16x2(x[4 * s + 3]));
        fence_async();
        warp_arrive(bars + B_OUTRDY, lead);
      } else {
#pragma unroll
        for (int i = 0; i < 24; i++)
          sts32_if(lane < 4, (o_st ^ (((i ^ ((i >> 1) & 2)) & 3) << 4)) + (i >> 2) * OUT_GROUP, f16x2_to_bf16x2(x[2 * i]));
        fence_async();
        warp_arrive(bars + B_OUTRDY, lead);
      }
    }
    if (!full && lead && round > 0) send_output(3 * round + wg - 3, (round & 1) ^ 1, true);
    __syncwarp();
    if (3 * round <= count) {
#pragma unroll 1
      for (uint32_t i = 0; i < 5; i++) {
        if (i % 3 == 0) {
          asm volatile("bar.sync %0, 256;" ::"r"(8 + wg) : "memory");
          asm volatile("bar.arrive %0, 256;" ::"r"(wg == 2 ? 8 : 9 + wg) : "memory");
        }
        const uint32_t u = 8 * round + i;
        mbar_wait(tail + T_FULL + 8 * (u % 3), (u / 3) & 1);
        if (lead) mbar_arrive(tail + T_EMPTY + 8 * (u % 3));
        __syncwarp();
      }
    }
    if (!full && lead) asm volatile("cp.async.bulk.wait_group.read 0;" ::: "memory");
    __syncwarp();
    asm volatile("bar.sync 0, 512;" ::: "memory");
    const uint32_t redo_all = lds32(tail + T_ALL);
    if (redo_all | lds32(tail + T_ANY)) {
      const uint32_t t = fresh_tid(), c = t >> 7;
      if ((t & 127) == 96) asm volatile("cp.async.bulk.wait_group 0;\nfence.proxy.async.global;" ::: "memory");
      __syncwarp();
      const Windows win(split);
      const uint32_t extra = lds32(tail + T_EXTRA);
      for (uint32_t j = c; j < win.count + (extra != ~0u); j += 3) {
        uint8_t* flag = &scr->redo[blockIdx.x + gridDim.x * j];
        if (!redo_all && !*reinterpret_cast<volatile uint8_t*>(flag)) continue;
        uint32_t col, row;
        win.at(j, col, row, extra);
        redo_window(7 * col, 7 * row, t & 127, 1 + c, smem_raw + c * REDO_BYTES, x_raw, dw, wqkv_raw, wo_raw, out);
        if ((t & 127) == 0) *flag = 0;
      }
    }
  }
}

typedef CUresult (*EncodeTiledFn)(CUtensorMap*, CUtensorMapDataType, cuuint32_t, void*, const cuuint64_t*, const cuuint64_t*,
                                  const cuuint32_t*, const cuuint32_t*, CUtensorMapInterleave, CUtensorMapSwizzle,
                                  CUtensorMapL2promotion, CUtensorMapFloatOOBfill);

}

extern "C" void kernel_launch(void* const* d_in, const int* in_sizes, int n_in, void* d_out, int out_size) {
  (void)in_sizes; (void)n_in; (void)out_size;
  static EncodeTiledFn encode = nullptr;
  static int grid = 0;
  static void* scratch = nullptr;
  if (!encode) {
    void* fn = nullptr;
    cudaDriverEntryPointQueryResult st;
    cudaGetDriverEntryPoint("cuTensorMapEncodeTiled", &fn, cudaEnableDefault, &st);
    encode = (EncodeTiledFn)fn;
    cudaFuncSetAttribute(davit_window_attn_kernel, cudaFuncAttributeMaxDynamicSharedMemorySize, SMEM_BYTES);
    cudaGetSymbolAddress(&scratch, g_scratch);
    int dev = 0;
    cudaGetDevice(&dev);
    cudaDeviceGetAttribute(&grid, cudaDevAttrMultiProcessorCount, dev);
    if (grid > 1024) grid = 1024;
  }
  Split split = {};
  {
    const uint32_t g = grid, n = kNumWin / g;
    if (g > kWinPerCol && g <= 2 * kWinPerCol && kWinPerCol - n <= n) {
      const uint32_t below = (kWinPerCol - n) * kWinPerCol;
      split.top = kWinPerCol;
      split.rows = (below > (n + 1) * (g - kWinPerCol) && n + 1 < kWinPerCol) ? n + 1 : n;
      split.alone = kWinPerCol - split.rows;
    }
    const uint32_t others = g - split.top, rest = kNumWin - split.top * split.rows - others * split.alone;
    split.share = rest / others;
    split.pool = rest % others;
    split.magic[0] = split.rows ? ((1u << 20) + split.rows - 1) / split.rows : 0;
    split.magic[1] = ((1u << 20) + kWinPerCol - split.rows - 1) / (kWinPerCol - split.rows);
  }
  auto image_map = [&](void* base, cuuint32_t c, cuuint32_t w, cuuint32_t h, CUtensorMapSwizzle swizzle) {
    CUtensorMap tm;
    const cuuint64_t dims[3] = {(cuuint64_t)kCh, (cuuint64_t)kImg, (cuuint64_t)kImg};
    const cuuint64_t strides[2] = {(cuuint64_t)kCh * 2, (cuuint64_t)kCh * 2 * kImg};
    const cuuint32_t box[3] = {c, w, h};
    const cuuint32_t estr[3] = {1, 1, 1};
    encode(&tm, CU_TENSOR_MAP_DATA_TYPE_BFLOAT16, 3, base, dims, strides, box, estr, CU_TENSOR_MAP_INTERLEAVE_NONE, swizzle,
           CU_TENSOR_MAP_L2_PROMOTION_L2_128B, CU_TENSOR_MAP_FLOAT_OOB_FILL_NONE);
    return tm;
  };
  auto weight_map = [&](void* base, cuuint64_t cols, cuuint32_t rows) {
    CUtensorMap tm;
    const cuuint64_t dims[2] = {cols, (cuuint64_t)kCh};
    const cuuint64_t strides[1] = {cols * 2};
    const cuuint32_t box[2] = {32, rows};
    const cuuint32_t estr[2] = {1, 1};
    encode(&tm, CU_TENSOR_MAP_DATA_TYPE_BFLOAT16, 2, base, dims, strides, box, estr, CU_TENSOR_MAP_INTERLEAVE_NONE,
           CU_TENSOR_MAP_SWIZZLE_64B, CU_TENSOR_MAP_L2_PROMOTION_L2_128B, CU_TENSOR_MAP_FLOAT_OOB_FILL_NONE);
    return tm;
  };
  davit_window_attn_kernel<<<grid, 512, SMEM_BYTES, cudaStreamPerThread>>>(
      image_map(d_in[0], 64, 9, 1, CU_TENSOR_MAP_SWIZZLE_NONE), image_map(d_in[0], 64, 9, 7, CU_TENSOR_MAP_SWIZZLE_NONE),
      image_map(d_in[0], 192, 9, 7, CU_TENSOR_MAP_SWIZZLE_NONE), image_map(d_out, 32, 7, 7, CU_TENSOR_MAP_SWIZZLE_64B),
      weight_map(d_in[2], 576, 192), weight_map(d_in[3], 192, 32),
      (const __nv_bfloat16*)d_in[1], (const __nv_bfloat16*)d_in[0], (const __nv_bfloat16*)d_in[2], (const __nv_bfloat16*)d_in[3],
      (__nv_bfloat16*)d_out, (Scratch*)scratch, split);
}
```

```cpp
#include <cuda.h>
#include <cuda_bf16.h>
#include <cuda_runtime.h>
#include <stdint.h>

namespace {

constexpr int kImg = 511;
constexpr int kCh = 192;
constexpr int kWinPerCol = 73;
constexpr int kNumWin = 73 * 73;

constexpr uint32_t W_PART = 36864;
constexpr uint32_t W_STEP = 3072;
constexpr uint32_t WO_STEP = 6144;
constexpr uint32_t W_BYTES = 8 * W_PART;

struct Scratch {
  uint8_t weights[W_BYTES];
  uint32_t ready;
  uint32_t passed;
  uint32_t claims;
  uint8_t redo[2 * kNumWin];
};
__device__ __align__(128) Scratch g_scratch;

constexpr uint32_t OFF_RING = 0;
constexpr uint32_t OFF_X0 = 3 * W_PART;
constexpr uint32_t kRows = 19;
constexpr uint32_t X0_ROW = 7 * 128;
constexpr uint32_t X0_CHUNK = kRows * X0_ROW;
constexpr uint32_t OFF_HALO = OFF_X0 + 3 * X0_CHUNK;
constexpr uint32_t HALO_ROW = 9 * 128;
constexpr uint32_t OFF_KV = OFF_HALO + 9 * HALO_ROW;
constexpr uint32_t K_CHUNK = 784;
constexpr uint32_t V_GROUP = 768;
constexpr uint32_t A_K0 = 0;
constexpr uint32_t A_V0 = 6 * K_CHUNK;
constexpr uint32_t A_ONES = A_V0 + 6 * V_GROUP;
constexpr uint32_t A_V1 = A_ONES + V_GROUP;
constexpr uint32_t A_K1 = A_V1 + 6 * V_GROUP;
constexpr uint32_t A_LAST = A_K1 + 6 * K_CHUNK;
constexpr uint32_t KV_SIZE = 19840;
constexpr uint32_t OUT_GROUP = 3328;
static_assert(A_LAST + 256 <= KV_SIZE && 5 * OUT_GROUP + 3136 <= KV_SIZE && KV_SIZE % 128 == 0 && 42 * HALO_ROW <= 3 * KV_SIZE &&
              21 * HALO_ROW >= KV_SIZE, "consumer area");
constexpr uint32_t OFF_TAIL = OFF_KV + 3 * KV_SIZE;
constexpr uint32_t SMEM_BYTES = OFF_TAIL + 360;
static_assert(SMEM_BYTES <= 232448, "shared memory");

constexpr uint32_t T_FULL = 0;
constexpr uint32_t T_EMPTY = 24;
constexpr uint32_t T_X0FULL = 48;
constexpr uint32_t T_X0FREE = 72;
constexpr uint32_t T_HALO = 88;
constexpr uint32_t T_WG = 160;
constexpr uint32_t B_KVRDY = 0;
constexpr uint32_t B_KVFREE = 8;
constexpr uint32_t B_OUTRDY = 16;
constexpr uint32_t B_OUTFREE = 24;
constexpr uint32_t T_RAW = 256;
constexpr uint32_t T_CLAIM = 264;
constexpr uint32_t T_ZERO = 272;
constexpr uint32_t T_SCALE = 288;
constexpr uint32_t T_ALL = 292;
constexpr uint32_t T_ANY = 296;
constexpr uint32_t T_DUMP = 300;
constexpr uint32_t T_EXTRA = 352;
constexpr uint32_t T_ROW = 304;

__device__ __forceinline__ void hmma_n96_first(uint32_t (&d)[24], uint32_t a0, uint32_t a1, uint32_t a2, uint32_t a3, uint64_t desc) {
  asm volatile("wgmma.mma_async.sync.aligned.m64n96k16.f16.f16.f16 "
               "{%0, %1, %2, %3, %4, %5, %6, %7, %8, %9, %10, %11, %12, %13, %14, %15, "
               "%16, %17, %18, %19, %20, %21, %22, %23}, "
               "{%24, %25, %26, %27}, %28, 0, 1, 1, 0;\n"
               : "=r"(d[0]), "=r"(d[1]), "=r"(d[2]), "=r"(d[3]), "=r"(d[4]), "=r"(d[5]), "=r"(d[6]), "=r"(d[7]),
                 "=r"(d[8]), "=r"(d[9]), "=r"(d[10]), "=r"(d[11]), "=r"(d[12]), "=r"(d[13]), "=r"(d[14]), "=r"(d[15]),
                 "=r"(d[16]), "=r"(d[17]), "=r"(d[18]), "=r"(d[19]), "=r"(d[20]), "=r"(d[21]), "=r"(d[22]), "=r"(d[23])
               : "r"(a0), "r"(a1), "r"(a2), "r"(a3), "l"(desc));
}
__device__ __forceinline__ void hmma_n96(uint32_t (&d)[24], uint32_t a0, uint32_t a1, uint32_t a2, uint32_t a3, uint64_t desc) {
  asm volatile("wgmma.mma_async.sync.aligned.m64n96k16.f16.f16.f16 "
               "{%0, %1, %2, %3, %4, %5, %6, %7, %8, %9, %10, %11, %12, %13, %14, %15, "
               "%16, %17, %18, %19, %20, %21, %22, %23}, "
               "{%24, %25, %26, %27}, %28, 1, 1, 1, 0;\n"
               : "+r"(d[0]), "+r"(d[1]), "+r"(d[2]), "+r"(d[3]), "+r"(d[4]), "+r"(d[5]), "+r"(d[6]), "+r"(d[7]),
                 "+r"(d[8]), "+r"(d[9]), "+r"(d[10]), "+r"(d[11]), "+r"(d[12]), "+r"(d[13]), "+r"(d[14]), "+r"(d[15]),
                 "+r"(d[16]), "+r"(d[17]), "+r"(d[18]), "+r"(d[19]), "+r"(d[20]), "+r"(d[21]), "+r"(d[22]), "+r"(d[23])
               : "r"(a0), "r"(a1), "r"(a2), "r"(a3), "l"(desc));
}
__device__ __forceinline__ void hmma_n96_over(uint32_t (&d)[24], uint32_t a0, uint32_t a1, uint32_t a2, uint32_t a3, uint64_t desc) {
  asm volatile("wgmma.mma_async.sync.aligned.m64n96k16.f16.f16.f16 "
               "{%0, %1, %2, %3, %4, %5, %6, %7, %8, %9, %10, %11, %12, %13, %14, %15, "
               "%16, %17, %18, %19, %20, %21, %22, %23}, "
               "{%24, %25, %26, %27}, %28, 0, 1, 1, 0;\n"
               : "+r"(d[0]), "+r"(d[1]), "+r"(d[2]), "+r"(d[3]), "+r"(d[4]), "+r"(d[5]), "+r"(d[6]), "+r"(d[7]),
                 "+r"(d[8]), "+r"(d[9]), "+r"(d[10]), "+r"(d[11]), "+r"(d[12]), "+r"(d[13]), "+r"(d[14]), "+r"(d[15]),
                 "+r"(d[16]), "+r"(d[17]), "+r"(d[18]), "+r"(d[19]), "+r"(d[20]), "+r"(d[21]), "+r"(d[22]), "+r"(d[23])
               : "r"(a0), "r"(a1), "r"(a2), "r"(a3), "l"(desc));
}
__device__ __forceinline__ void hmma_n56_first(uint32_t (&d)[14], uint32_t a0, uint32_t a1, uint32_t a2, uint32_t a3, uint64_t desc) {
  asm volatile("wgmma.mma_async.sync.aligned.m64n56k16.f16.f16.f16 "
               "{%0, %1, %2, %3, %4, %5, %6, %7, %8, %9, %10, %11, %12, %13}, "
               "{%14, %15, %16, %17}, %18, 0, 1, 1, 0;\n"
               : "=r"(d[0]), "=r"(d[1]), "=r"(d[2]), "=r"(d[3]), "=r"(d[4]), "=r"(d[5]), "=r"(d[6]), "=r"(d[7]),
                 "=r"(d[8]), "=r"(d[9]), "=r"(d[10]), "=r"(d[11]), "=r"(d[12]), "=r"(d[13])
               : "r"(a0), "r"(a1), "r"(a2), "r"(a3), "l"(desc));
}
__device__ __forceinline__ void hmma_n56(uint32_t (&d)[14], uint32_t a0, uint32_t a1, uint32_t a2, uint32_t a3, uint64_t desc) {
  asm volatile("wgmma.mma_async.sync.aligned.m64n56k16.f16.f16.f16 "
               "{%0, %1, %2, %3, %4, %5, %6, %7, %8, %9, %10, %11, %12, %13}, "
               "{%14, %15, %16, %17}, %18, 1, 1, 1, 0;\n"
               : "+r"(d[0]), "+r"(d[1]), "+r"(d[2]), "+r"(d[3]), "+r"(d[4]), "+r"(d[5]), "+r"(d[6]), "+r"(d[7]),
                 "+r"(d[8]), "+r"(d[9]), "+r"(d[10]), "+r"(d[11]), "+r"(d[12]), "+r"(d[13])
               : "r"(a0), "r"(a1), "r"(a2), "r"(a3), "l"(desc));
}
__device__ __forceinline__ void hmma_n192(uint32_t (&d)[48], uint32_t a0, uint32_t a1, uint32_t a2, uint32_t a3, uint64_t desc) {
  asm volatile("wgmma.mma_async.sync.aligned.m64n192k16.f16.f16.f16 "
               "{%0, %1, %2, %3, %4, %5, %6, %7, %8, %9, %10, %11, %12, %13, %14, %15, "
               "%16, %17, %18, %19, %20, %21, %22, %23, %24, %25, %26, %27, %28, %29, %30, %31, "
               "%32, %33, %34, %35, %36, %37, %38, %39, %40, %41, %42, %43, %44, %45, %46, %47}, "
               "{%48, %49, %50, %51}, %52, 1, 1, 1, 0;\n"
               : "+r"(d[0]), "+r"(d[1]), "+r"(d[2]), "+r"(d[3]), "+r"(d[4]), "+r"(d[5]), "+r"(d[6]), "+r"(d[7]),
                 "+r"(d[8]), "+r"(d[9]), "+r"(d[10]), "+r"(d[11]), "+r"(d[12]), "+r"(d[13]), "+r"(d[14]), "+r"(d[15]),
                 "+r"(d[16]), "+r"(d[17]), "+r"(d[18]), "+r"(d[19]), "+r"(d[20]), "+r"(d[21]), "+r"(d[22]), "+r"(d[23]),
                 "+r"(d[24]), "+r"(d[25]), "+r"(d[26]), "+r"(d[27]), "+r"(d[28]), "+r"(d[29]), "+r"(d[30]), "+r"(d[31]),
                 "+r"(d[32]), "+r"(d[33]), "+r"(d[34]), "+r"(d[35]), "+r"(d[36]), "+r"(d[37]), "+r"(d[38]), "+r"(d[39]),
                 "+r"(d[40]), "+r"(d[41]), "+r"(d[42]), "+r"(d[43]), "+r"(d[44]), "+r"(d[45]), "+r"(d[46]), "+r"(d[47])
               : "r"(a0), "r"(a1), "r"(a2), "r"(a3), "l"(desc));
}

__device__ __forceinline__ void wg_fence() { asm volatile("wgmma.fence.sync.aligned;\n" ::: "memory"); }
__device__ __forceinline__ void wg_commit() { asm volatile("wgmma.commit_group.sync.aligned;\n" ::: "memory"); }
template <int N> __device__ __forceinline__ void wg_wait() { asm volatile("wgmma.wait_group.sync.aligned %0;\n" ::"n"(N) : "memory"); }
__device__ __forceinline__ uint64_t make_desc(uint32_t addr, uint32_t lbo, uint32_t sbo) {
  return (uint64_t)((addr & 0x3FFFF) >> 4) | ((uint64_t)(lbo >> 4) << 16) | ((uint64_t)(sbo >> 4) << 32);
}
__device__ __forceinline__ uint64_t desc_add(uint64_t d, uint32_t bytes) { return d + (bytes >> 4); }
__device__ __forceinline__ uint64_t desc_at(uint64_t d, uint32_t bytes) {
  uint64_t r;
  asm volatile("mov.b64 %0, %1;" : "=l"(r) : "l"(d));
  return desc_add(r, bytes);
}

__device__ __forceinline__ void mbar_init(uint32_t bar, uint32_t count) {
  asm volatile("mbarrier.init.shared::cta.b64 [%0], %1;" ::"r"(bar), "r"(count) : "memory");
}
__device__ __forceinline__ void mbar_expect_tx(uint32_t bar, uint32_t bytes) {
  asm volatile("mbarrier.arrive.expect_tx.shared::cta.b64 _, [%0], %1;" ::"r"(bar), "r"(bytes) : "memory");
}
__device__ __forceinline__ void mbar_wait(uint32_t bar, uint32_t parity) {
  asm volatile("{\n.reg .pred p;\n.reg .u32 c;\n"
               "mbarrier.try_wait.parity.shared::cta.b64 p, [%0], %1;\n"
               "@p bra DONE;\n"
               "mov.u32 c, 0;\n"
               "SPIN:\n"
               "mbarrier.try_wait.parity.shared::cta.b64 p, [%0], %1, 4000;\n"
               "@p bra DONE;\n"
               "add.u32 c, c, 1;\n"
               "setp.lt.u32 p, c, 1048576;\n"
               "@!p trap;\n"
               "bra SPIN;\n"
               "DONE:\n}" ::"r"(bar), "r"(parity) : "memory");
}
__device__ __forceinline__ void bar_sync(uint32_t id) { asm volatile("bar.sync %0, 128;" ::"r"(id) : "memory"); }
__device__ __forceinline__ void mbar_arrive(uint32_t bar) { asm volatile("mbarrier.arrive.shared::cta.b64 _, [%0];" ::"r"(bar) : "memory"); }
__device__ __forceinline__ void warp_arrive(uint32_t bar, bool first) {
  __syncwarp();
  if (first) mbar_arrive(bar);
}
__device__ __forceinline__ void arrive_elected(uint32_t bar) {
  asm volatile("{\n.reg .pred p;\nelect.sync _|p, 0xffffffff;\n@p mbarrier.arrive.shared::cta.b64 _, [%0];\n}" ::"r"(bar) : "memory");
}
__device__ __forceinline__ void fence_async() { asm volatile("fence.proxy.async.shared::cta;" ::: "memory"); }
__device__ __forceinline__ uint32_t lds32(uint32_t a) {
  uint32_t v;
  asm volatile("ld.shared.b32 %0, [%1];" : "=r"(v) : "r"(a) : "memory");
  return v;
}
__device__ __forceinline__ void lds64(uint32_t a, uint32_t& v0, uint32_t& v1) {
  asm volatile("ld.shared.v2.b32 {%0, %1}, [%2];" : "=r"(v0), "=r"(v1) : "r"(a) : "memory");
}
__device__ __forceinline__ void sts32(uint32_t a, uint32_t v) { asm volatile("st.shared.b32 [%0], %1;" ::"r"(a), "r"(v) : "memory"); }
__device__ __forceinline__ void sts64(uint32_t a, uint32_t v0, uint32_t v1) {
  asm volatile("st.shared.v2.b32 [%0], {%1, %2};" ::"r"(a), "r"(v0), "r"(v1) : "memory");
}
__device__ __forceinline__ void sts32_if(bool on, uint32_t a, uint32_t v) {
  asm volatile("{\n.reg .pred p;\nsetp.ne.u32 p, %2, 0;\n@p st.shared.b32 [%0], %1;\n}" ::"r"(a), "r"(v), "r"((uint32_t)on) : "memory");
}
__device__ __forceinline__ void ldsm4(uint32_t a, uint32_t& r0, uint32_t& r1, uint32_t& r2, uint32_t& r3) {
  asm volatile("ldmatrix.sync.aligned.m8n8.x4.shared.b16 {%0, %1, %2, %3}, [%4];" : "=r"(r0), "=r"(r1), "=r"(r2), "=r"(r3) : "r"(a) : "memory");
}
__device__ __forceinline__ void stsm4(uint32_t a, uint32_t r0, uint32_t r1, uint32_t r2, uint32_t r3) {
  asm volatile("stmatrix.sync.aligned.m8n8.x4.shared.b16 [%0], {%1, %2, %3, %4};" ::"r"(a), "r"(r0), "r"(r1), "r"(r2), "r"(r3) : "memory");
}
__device__ __forceinline__ void stsm4_t(uint32_t a, uint32_t r0, uint32_t r1, uint32_t r2, uint32_t r3) {
  asm volatile("stmatrix.sync.aligned.m8n8.x4.trans.shared.b16 [%0], {%1, %2, %3, %4};" ::"r"(a), "r"(r0), "r"(r1), "r"(r2), "r"(r3) : "memory");
}
__device__ __forceinline__ uint32_t pack_bf16(float lo, float hi) {
  uint32_t r;
  asm("cvt.rn.bf16x2.f32 %0, %1, %2;" : "=r"(r) : "f"(hi), "f"(lo));
  return r;
}
__device__ __forceinline__ uint32_t pack_f16(float lo, float hi) {
  uint32_t r;
  asm("cvt.rn.f16x2.f32 %0, %1, %2;" : "=r"(r) : "f"(hi), "f"(lo));
  return r;
}
__device__ __forceinline__ float bf_lo(uint32_t v) { return __uint_as_float(v << 16); }
__device__ __forceinline__ float bf_hi(uint32_t v) { return __uint_as_float(v & 0xffff0000u); }
__device__ __forceinline__ float h_lo(uint32_t v) {
  float r;
  asm("{\n.reg .b16 l, h;\nmov.b32 {l, h}, %1;\ncvt.f32.f16 %0, l;\n}" : "=f"(r) : "r"(v));
  return r;
}
__device__ __forceinline__ float h_hi(uint32_t v) {
  float r;
  asm("{\n.reg .b16 l, h;\nmov.b32 {l, h}, %1;\ncvt.f32.f16 %0, h;\n}" : "=f"(r) : "r"(v));
  return r;
}
__device__ __forceinline__ uint32_t bf16x2_to_f16x2(uint32_t v) { return pack_f16(bf_lo(v), bf_hi(v)); }
__device__ __forceinline__ uint32_t f16x2_to_bf16x2(uint32_t v) { return pack_bf16(h_lo(v), h_hi(v)); }
__device__ __forceinline__ uint32_t bmul2(uint32_t a, uint32_t b) {
  uint32_t r;
  asm("mul.rn.bf16x2 %0, %1, %2;" : "=r"(r) : "r"(a), "r"(b));
  return r;
}
__device__ __forceinline__ uint32_t badd2(uint32_t a, uint32_t b) {
  uint32_t r;
  asm("add.rn.bf16x2 %0, %1, %2;" : "=r"(r) : "r"(a), "r"(b));
  return r;
}
__device__ __forceinline__ uint32_t bfma2(uint32_t a, uint32_t b, uint32_t c) {
  uint32_t r;
  asm("fma.rn.bf16x2 %0, %1, %2, %3;" : "=r"(r) : "r"(a), "r"(b), "r"(c));
  return r;
}
__device__ __forceinline__ uint32_t hadd2(uint32_t a, uint32_t b) {
  uint32_t d;
  asm("add.rn.f16x2 %0, %1, %2;" : "=r"(d) : "r"(a), "r"(b));
  return d;
}
__device__ __forceinline__ uint32_t hmax2(uint32_t a, uint32_t b) {
  uint32_t d;
  asm("max.f16x2 %0, %1, %2;" : "=r"(d) : "r"(a), "r"(b));
  return d;
}
__device__ __forceinline__ uint32_t hmul2(uint32_t a, uint32_t b) {
  uint32_t d;
  asm("mul.rn.f16x2 %0, %1, %2;" : "=r"(d) : "r"(a), "r"(b));
  return d;
}
__device__ __forceinline__ uint32_t hmul2_lo(uint32_t a, uint32_t r) {
  uint32_t d;
  asm("{\n.reg .b16 l, h;\n.reg .b32 t;\nmov.b32 {l, h}, %2;\nmov.b32 t, {l, l};\nmul.rn.f16x2 %0, %1, t;\n}" : "=r"(d) : "r"(a), "r"(r));
  return d;
}
__device__ __forceinline__ uint32_t hmul2_hi(uint32_t a, uint32_t r) {
  uint32_t d;
  asm("{\n.reg .b16 l, h;\n.reg .b32 t;\nmov.b32 {l, h}, %2;\nmov.b32 t, {h, h};\nmul.rn.f16x2 %0, %1, t;\n}" : "=r"(d) : "r"(a), "r"(r));
  return d;
}
__device__ __forceinline__ float rcp(float x) {
  float r;
  asm("rcp.approx.ftz.f32 %0, %1;" : "=f"(r) : "f"(x));
  return r;
}
__device__ __forceinline__ float rsqrt_fast(float x) {
  float r;
  asm("rsqrt.approx.ftz.f32 %0, %1;" : "=f"(r) : "f"(x));
  return r;
}
template <int N> __device__ __forceinline__ void fence_regs(uint32_t (&d)[N]) {
#pragma unroll
  for (int i = 0; i < N; i++) asm volatile("" : "+r"(d[i])::"memory");
}

__device__ __forceinline__ void row_stats(const uint32_t (&x)[48], bool odd, float& sum, float& squares) {
  float s0 = 0.f, q0 = 0.f, s1 = 0.f, q1 = 0.f;
#pragma unroll
  for (int i = 0; i < 48; i++) {
    const float lo = h_lo(x[i]), hi = h_hi(x[i]);
    if (i & 1) {
      s1 += lo; q1 = fmaf(lo, lo, q1);
      s1 += hi; q1 = fmaf(hi, hi, q1);
    } else {
      s0 += lo; q0 = fmaf(lo, lo, q0);
      s0 += hi; q0 = fmaf(hi, hi, q0);
    }
  }
  sum = (odd ? s1 : s0) + __shfl_xor_sync(0xffffffffu, odd ? s0 : s1, 1);
  squares = (odd ? q1 : q0) + __shfl_xor_sync(0xffffffffu, odd ? q0 : q1, 1);
  sum += __shfl_xor_sync(0xffffffffu, sum, 2);
  squares += __shfl_xor_sync(0xffffffffu, squares, 2);
}
__device__ __forceinline__ void lane_stats_packed(const uint32_t (&x)[48], uint32_t (&t)[2]) {
  uint32_t s[4] = {x[0], x[1], x[2], x[3]}, q[4];
#pragma unroll
  for (int r = 0; r < 4; r++) q[r] = hmul2(x[r], x[r]);
#pragma unroll
  for (int i = 4; i < 48; i++) {
    asm("add.rn.f16x2 %0, %0, %1;" : "+r"(s[i & 3]) : "r"(x[i]));
    asm("fma.rn.f16x2 %0, %1, %1, %0;" : "+r"(q[i & 3]) : "r"(x[i]));
  }
#pragma unroll
  for (int r = 0; r < 2; r++) {
    const uint32_t a = hadd2(s[r], s[r + 2]), b = hadd2(q[r], q[r + 2]);
    t[r] = hadd2(__byte_perm(a, b, 0x5410), __byte_perm(a, b, 0x7632));
  }
}
__device__ __forceinline__ uint32_t quad_stats_packed(const uint32_t (&t)[2], bool odd) {
  const uint32_t u = hadd2(__shfl_xor_sync(0xffffffffu, odd ? t[0] : t[1], 1), odd ? t[1] : t[0]);
  return hadd2(u, __shfl_xor_sync(0xffffffffu, u, 2));
}

__device__ __forceinline__ void store_k(const uint32_t (&k)[24], uint32_t k_st, bool full, bool first_row, uint32_t r) {
  if (full) {
#pragma unroll
    for (int j = 0; j < 12; j += 2)
      stsm4(k_st + (j / 6) * A_K1 + (j % 6) * K_CHUNK, hmul2_lo(k[2 * j], r), hmul2_hi(k[2 * j + 1], r), hmul2_lo(k[2 * j + 2], r),
            hmul2_hi(k[2 * j + 3], r));
  } else {
#pragma unroll
    for (int j = 0; j < 12; j++) sts32_if(first_row, k_st + (j / 6) * A_K1 + (j % 6) * K_CHUNK, hmul2_lo(k[2 * j], r));
    __syncwarp();
  }
}
template <int HALF> __device__ __forceinline__ uint32_t both(uint32_t v) {
  uint32_t d;
  if (HALF == 0) asm("{\n.reg .b16 l, h;\nmov.b32 {l, h}, %1;\nmov.b32 %0, {l, l};\n}" : "=r"(d) : "r"(v));
  else asm("{\n.reg .b16 l, h;\nmov.b32 {l, h}, %1;\nmov.b32 %0, {h, h};\n}" : "=r"(d) : "r"(v));
  return d;
}
__device__ __forceinline__ uint32_t exp2_scaled(uint32_t s, uint32_t c, uint32_t off) {
  uint32_t d;
  asm("{\n.reg .b32 t;\nfma.rn.f16x2 t, %1, %2, %3;\nex2.approx.f16x2 %0, t;\n}" : "=r"(d) : "r"(s), "r"(c), "r"(off));
  return d;
}
__device__ __forceinline__ uint32_t softmax_top(const uint32_t (&s)[14], uint32_t lane, uint32_t c, uint32_t& last) {
  last = __shfl_sync(0xffffffffu, __byte_perm(s[12], s[13], 0x5410), lane & 28);
  const uint32_t a = hmax2(hmax2(hmax2(s[0], s[2]), s[4]), hmax2(hmax2(s[6], s[8]), s[10]));
  const uint32_t b = hmax2(hmax2(hmax2(s[1], s[3]), s[5]), hmax2(hmax2(s[7], s[9]), s[11]));
  uint32_t m = hmax2(__byte_perm(a, b, 0x5410), __byte_perm(a, b, 0x7632));
  m = hmax2(m, __shfl_xor_sync(0xffffffffu, m, 1));
  m = hmax2(hmax2(m, last), __shfl_xor_sync(0xffffffffu, m, 2));
  return hmul2(m, c);
}
__device__ __forceinline__ void lds128(uint32_t a, uint32_t* v) {
  asm volatile("ld.shared.v4.b32 {%0, %1, %2, %3}, [%4];" : "=r"(v[0]), "=r"(v[1]), "=r"(v[2]), "=r"(v[3]) : "r"(a) : "memory");
}
template <int SUM, int VAL>
__device__ __forceinline__ void softmax_rows(const uint32_t (&s)[14], uint32_t top, uint32_t last, uint32_t c, uint32_t pad,
                                             uint32_t v_last, uint32_t (&pa)[12], uint32_t (&ov)[14]) {
  uint32_t off, v[6];
  lds128(v_last, v);
  lds64(v_last + 16, v[4], v[5]);
  asm("sub.rn.f16x2 %0, %1, %2;" : "=r"(off) : "r"(pad), "r"(top));
#pragma unroll
  for (int j = 0; j < 6; j++) {
    pa[2 * j] = exp2_scaled(s[2 * j], both<0>(c), both<0>(off));
    pa[2 * j + 1] = exp2_scaled(s[2 * j + 1], both<1>(c), both<1>(off));
  }
  const uint32_t p = exp2_scaled(last, c, off);
#pragma unroll
  for (int j = 0; j < 6; j++) {
    ov[VAL + 2 * j] = hmul2_lo(v[j], p);
    ov[VAL + 2 * j + 1] = hmul2_hi(v[j], p);
  }
  ov[SUM] = __byte_perm(p, p, 0x1010);
  ov[SUM + 1] = __byte_perm(p, p, 0x3232);
}
__device__ __forceinline__ void issue_pv(uint32_t (&ov)[14], const uint32_t (&pa)[12], uint64_t v_desc) {
#pragma unroll
  for (int k = 0; k < 3; k++) hmma_n56(ov, pa[4 * k], pa[4 * k + 1], pa[4 * k + 2], pa[4 * k + 3], desc_add(v_desc, k * 256));
}
__device__ __forceinline__ void sts128_if(bool on, uint32_t a, uint32_t v0, uint32_t v1, uint32_t v2, uint32_t v3) {
  asm volatile("{\n.reg .pred p;\nsetp.ne.u32 p, %5, 0;\n@p st.shared.v4.b32 [%0], {%1, %2, %3, %4};\n}"
               ::"r"(a), "r"(v0), "r"(v1), "r"(v2), "r"(v3), "r"((uint32_t)on) : "memory");
}
__device__ __forceinline__ void store_v(const uint32_t (&v)[24], uint32_t v_st, uint32_t v_last, bool full, bool first_row, uint32_t r) {
  if (full) {
#pragma unroll
    for (int j = 0; j < 12; j += 2)
      stsm4_t(v_st + (j / 6) * (A_V1 - A_V0) + (j % 6) * V_GROUP, hmul2_lo(v[2 * j], r), hmul2_hi(v[2 * j + 1], r), hmul2_lo(v[2 * j + 2], r),
              hmul2_hi(v[2 * j + 3], r));
  } else {
#pragma unroll
    for (int h = 0; h < 2; h++) {
      sts128_if(first_row, v_last + h * 128, hmul2_lo(v[12 * h], r), hmul2_lo(v[12 * h + 2], r), hmul2_lo(v[12 * h + 4], r),
                hmul2_lo(v[12 * h + 6], r));
      sts128_if(first_row, v_last + h * 128 + 16, hmul2_lo(v[12 * h + 8], r), hmul2_lo(v[12 * h + 10], r), 0u, 0u);
    }
    __syncwarp();
  }
}
__device__ __forceinline__ void issue_s(uint32_t (&s)[14], const uint32_t* qa, uint64_t k_desc) {
  hmma_n56_first(s, qa[0], qa[1], qa[2], qa[3], k_desc);
#pragma unroll
  for (int k = 1; k < 3; k++) hmma_n56(s, qa[4 * k], qa[4 * k + 1], qa[4 * k + 2], qa[4 * k + 3], desc_add(k_desc, k * 2 * K_CHUNK));
}
template <int SUM, int VAL>
__device__ __forceinline__ void pack_o(const uint32_t (&ov)[14], uint32_t* o) {
  const uint32_t p = pack_f16(rcp(fmaxf(h_lo(ov[SUM]), 0.5f)), rcp(fmaxf(h_lo(ov[SUM + 1]), 0.5f)));
#pragma unroll
  for (int j = 0; j < 6; j++) {
    o[2 * j] = hmul2_lo(ov[VAL + 2 * j], p);
    o[2 * j + 1] = hmul2_hi(ov[VAL + 2 * j + 1], p);
  }
}
template <int FIRST>
__device__ __forceinline__ void issue_half(uint32_t (&d)[24], const uint32_t (&x)[48], uint64_t desc) {
  if (FIRST == 2) hmma_n96_over(d, x[0], x[1], x[2], x[3], desc);
  if (FIRST == 1) hmma_n96_first(d, x[0], x[1], x[2], x[3], desc);
#pragma unroll
  for (int s = FIRST ? 1 : 6; s < (FIRST ? 6 : 12); s++) hmma_n96(d, x[4 * s], x[4 * s + 1], x[4 * s + 2], x[4 * s + 3], desc_add(desc, s * W_STEP));
}
template <int N>
__device__ __forceinline__ void issue_out(uint32_t (&d)[48], const uint32_t* o, uint64_t desc) {
#pragma unroll
  for (int s = 0; s < N; s++) hmma_n192(d, o[4 * s], o[4 * s + 1], o[4 * s + 2], o[4 * s + 3], desc_add(desc, s * WO_STEP));
}

__device__ __forceinline__ void mma_bf16(float (&c)[4], uint32_t a0, uint32_t a1, uint32_t a2, uint32_t a3, uint32_t b0, uint32_t b1) {
  asm("mma.sync.aligned.m16n8k16.row.col.f32.bf16.bf16.f32 {%0, %1, %2, %3}, {%4, %5, %6, %7}, {%8, %9}, {%0, %1, %2, %3};"
      : "+f"(c[0]), "+f"(c[1]), "+f"(c[2]), "+f"(c[3]) : "r"(a0), "r"(a1), "r"(a2), "r"(a3), "r"(b0), "r"(b1));
}
__device__ __forceinline__ void mma_bf16_k8(float (&d)[4], uint32_t a0, uint32_t a1, uint32_t b, const float (&c)[4]) {
  asm("mma.sync.aligned.m16n8k8.row.col.f32.bf16.bf16.f32 {%0, %1, %2, %3}, {%4, %5}, {%6}, {%7, %8, %9, %10};"
      : "=f"(d[0]), "=f"(d[1]), "=f"(d[2]), "=f"(d[3]) : "r"(a0), "r"(a1), "r"(b), "f"(c[0]), "f"(c[1]), "f"(c[2]), "f"(c[3]));
}
__device__ __forceinline__ bool on_diagonal(uint32_t lane) { return (lane & 3) == (lane >> 3); }
__device__ __forceinline__ float column_stats(const uint32_t (&v)[24], uint32_t lane, uint32_t& hi, uint32_t& lo) {
  float sum[2][4] = {}, sq[2][4] = {}, sr[2][4] = {};
#pragma unroll
  for (int c = 0; c < 24; c += 4) mma_bf16(sum[(c >> 2) & 1], v[c], v[c + 1], v[c + 2], v[c + 3], 0x3F803F80u, 0x3F803F80u);
#pragma unroll
  for (int c = 0; c < 24; c += 2) {
    mma_bf16_k8(sq[(c >> 1) & 1], v[c], v[c + 1], v[c], sq[(c >> 1) & 1]);
    mma_bf16_k8(sr[(c >> 1) & 1], v[c], v[c + 1], v[c + 1], sr[(c >> 1) & 1]);
  }
  const float total = (sum[0][0] + sum[0][2]) + (sum[1][0] + sum[1][2]), mean = total * (1.f / 192.f);
  const bool diag = on_diagonal(lane);
  const float n2 = (lane & 4) ? (sq[0][1] + sq[1][1]) + (sr[0][3] + sr[1][3]) : (sq[0][0] + sq[1][0]) + (sr[0][2] + sr[1][2]);
  hi = diag ? __float_as_uint(n2) : 0u;
  lo = __float_as_uint((diag && n2 > 0.f) ? fmaxf(fmaf(-total, mean, n2), 0.f) : INFINITY);
  return mean;
}
__device__ __forceinline__ uint32_t warp_max_abs(const uint32_t (&v)[8]) {
  uint32_t m = v[0];
#pragma unroll
  for (int c = 1; c < 8; c++) asm("max.NaN.xorsign.abs.bf16x2 %0, %0, %1;" : "+r"(m) : "r"(v[c]));
  return __reduce_max_sync(0xffffffffu, max(m & 0x7fffu, (m >> 16) & 0x7fffu));
}
__device__ __forceinline__ bool norms_in_range(uint32_t hi, uint32_t lo) {
  return hi - 0x08800000u <= 0x7B000000u - 0x08800000u && lo >= hi - (12u << 23);
}
__device__ __forceinline__ int norm_exponent(uint32_t n2) { return (int)(0x453B8000u - n2) >> 24; }
__device__ __forceinline__ void scale_to_f16(uint32_t (&v)[8], uint32_t lane, int e, float mean) {
  const uint32_t ident = on_diagonal(lane) ? (uint32_t)(e + 127) << ((lane & 4) ? 23 : 7) : 0u;
  const float c0 = -mean * __uint_as_float((uint32_t)(e + 127) << 23), c[4] = {c0, c0, c0, c0};
#pragma unroll
  for (int i = 0; i < 8; i += 2) {
    float d[4];
    mma_bf16_k8(d, v[i], v[i + 1], ident, c);
    v[i] = pack_f16(d[0], d[1]);
    v[i + 1] = pack_f16(d[2], d[3]);
  }
}
__device__ __forceinline__ float pow2(int e) { return __uint_as_float((uint32_t)(min(max(e, -126), 127) + 127) << 23); }

constexpr uint32_t kUnits = 24;
constexpr uint32_t RAW_O = W_PART, RAW_RED = RAW_O + 32 * 384;
__device__ __forceinline__ void bulk_load(uint32_t dst, const void* src, uint32_t bytes, uint32_t bar) {
  asm volatile("cp.async.bulk.shared::cluster.global.mbarrier::complete_tx::bytes [%0], [%1], %2, [%3];"
               ::"r"(dst), "l"(src), "r"(bytes), "r"(bar) : "memory");
}
__device__ __forceinline__ void tile_load(uint32_t dst, const CUtensorMap* tm, uint32_t c0, uint32_t c1, uint32_t bar) {
  asm volatile("cp.async.bulk.tensor.2d.shared::cluster.global.tile.mbarrier::complete_tx::bytes [%0], [%1, {%2, %3}], [%4];"
               ::"r"(dst), "l"(tm), "r"(c0), "r"(c1), "r"(bar) : "memory");
}
__device__ __forceinline__ void request_unit(uint32_t u, uint32_t raw, uint32_t bar, const CUtensorMap* tmw, const CUtensorMap* tmwo) {
  const bool is_o = (u & 7) >= 6;
  const uint32_t pair = is_o ? u & 1 : (u & 7) / 3, part = is_o ? 1 : (u & 7) % 3;
  mbar_expect_tx(bar, is_o ? W_PART + 32 * 384 : W_PART);
#pragma unroll
  for (uint32_t i = 0; i < 3; i++) tile_load(raw + i * (192 * 64), tmw, ((part + 1) % 3) * 192 + pair * 96 + 32 * i, 0, bar);
  if (is_o) {
#pragma unroll
    for (uint32_t i = 0; i < 6; i++) tile_load(raw + RAW_O + i * (32 * 64), tmwo, 32 * i, pair * 96 + (u >> 3) * 32, bar);
  }
}
__device__ __forceinline__ void ldsm4_t(uint32_t a, uint32_t* v) {
  asm volatile("ldmatrix.sync.aligned.m8n8.x4.trans.shared.b16 {%0, %1, %2, %3}, [%4];" : "=r"(v[0]), "=r"(v[1]), "=r"(v[2]), "=r"(v[3]) : "r"(a) : "memory");
}
__device__ __forceinline__ void prepare_unit(uint32_t u, uint32_t wid, uint32_t lane, uint32_t raw, Scratch* scr) {
  const bool is_o = (u & 7) >= 6;
  const uint32_t third = u >> 3;
  uint32_t v[24], w[8];
  const uint32_t src = raw + (wid >> 2) * (192 * 64) + lane * 64 + (((wid ^ (lane >> 1)) & 3) << 4);
#pragma unroll
  for (int m = 0; m < 6; m++) ldsm4_t(src + m * (32 * 64), &v[4 * m]);
  uint32_t hi, lo, top = 0;
  const float mean = column_stats(v, lane, hi, lo);
  if (is_o) {
#pragma unroll
    for (int m = 0; m < 2; m++)
      ldsm4_t(raw + RAW_O + (wid >> 1) * (32 * 64) + lane * 64 + ((((2 * wid + m) ^ (lane >> 1)) & 3) << 4), &w[4 * m]);
    top = warp_max_abs(w);
  } else {
#pragma unroll
    for (int m = 0; m < 2; m++) ldsm4_t(src + (2 * third + m) * (32 * 64), &w[4 * m]);
  }
  hi = __reduce_max_sync(0xffffffffu, hi);
  lo = __reduce_min_sync(0xffffffffu, lo);
  if (lane == 0) {
    sts64(raw + RAW_RED + wid * 16, hi, lo);
    sts32(raw + RAW_RED + wid * 16 + 8, top);
  }
  asm volatile("bar.sync 4, 384;" ::: "memory");
  lds64(raw + RAW_RED + (lane % 12) * 16, hi, lo);
  top = lds32(raw + RAW_RED + (lane % 12) * 16 + 8);
  hi = __reduce_max_sync(0xffffffffu, hi);
  lo = __reduce_min_sync(0xffffffffu, lo);
  top = __reduce_max_sync(0xffffffffu, top);
  const int e = norm_exponent(hi);
  scale_to_f16(w, lane, is_o ? -e : e - 4, is_o ? 0.f : mean);
  const uint32_t mat = lane >> 3, at = (mat & 1) * 128 + (lane & 7) * 16;
#pragma unroll
  for (int m = 0; m < 2; m++)
    stsm4(raw + at + (is_o ? (mat >> 1) * WO_STEP + (2 * wid + m) * 256 : (2 * m + (mat >> 1)) * W_STEP + wid * 256), w[4 * m], w[4 * m + 1],
          w[4 * m + 2], w[4 * m + 3]);
  fence_async();
  asm volatile("bar.sync 4, 384;" ::: "memory");
  if (wid == 0 && lane == 0) {
    asm volatile("cp.async.bulk.global.shared::cta.bulk_group [%0], [%1], %2;\ncp.async.bulk.commit_group;"
                 ::"l"(scr->weights + (u & 7) * W_PART + third * (W_PART / 3)), "r"(raw), "n"(W_PART / 3) : "memory");
    const bool bad = is_o ? !(__uint_as_float(top << 16) * pow2(-e) <= 0.25f) : !norms_in_range(hi, lo);
    const uint32_t exponent = (!is_o && third == 0 && u % 3 != 1) ? (uint32_t)(e + 64) << (u < 3 ? 10 : 19) : 0u;
    asm volatile("cp.async.bulk.wait_group 0;" ::: "memory");
    asm volatile("red.relaxed.gpu.global.add.u32 [%0], %1;" ::"l"(&scr->ready), "r"(bad ? 33u : 1u + exponent) : "memory");
  }
  __syncwarp();
}

constexpr uint32_t REDO_BYTES = 75776;
static_assert(3 * REDO_BYTES <= OFF_TAIL && (3 * 49 * 192 + 49 * 144) * 2 <= REDO_BYTES, "redo scratch");
__device__ __forceinline__ float round_bf16(float x) { return __bfloat162float(__float2bfloat16(x)); }
__device__ __forceinline__ void redo_window(int c0, int y0, int t, uint32_t bar, uint8_t* scratch, const __nv_bfloat16* x,
                                            const __nv_bfloat16* dw, const __nv_bfloat16* wqkv, const __nv_bfloat16* wo,
                                            __nv_bfloat16* out) {
  __nv_bfloat16* x0 = reinterpret_cast<__nv_bfloat16*>(scratch);
  __nv_bfloat16* h = x0 + 49 * 192;
  __nv_bfloat16* o = h + 49 * 192;
  __nv_bfloat16* qkv = o + 49 * 192;
  bar_sync(bar);
#pragma unroll 1
  for (int i = t; i < 49 * 192; i += 128) {
    const int tok = i / 192, c = i % 192, y = y0 + tok / 7, xx = c0 + tok % 7;
    float pe = 0.f;
#pragma unroll 1
    for (int k = 0; k < 9; k++) {
      const int yy = y + k / 3 - 1, xj = xx + k % 3 - 1;
      const bool in = (uint32_t)yy < kImg && (uint32_t)xj < kImg;
      const float v = in ? __bfloat162float(x[((size_t)yy * kImg + xj) * kCh + c]) : 0.f;
      pe = round_bf16(pe + round_bf16(v * __bfloat162float(dw[k * kCh + c])));
    }
    x0[i] = __float2bfloat16(__bfloat162float(x[((size_t)y * kImg + xx) * kCh + c]) + pe);
  }
  bar_sync(bar);
  if (t < 49) {
    float s = 0.f, v = 0.f;
#pragma unroll 1
    for (int c = 0; c < 192; c++) s += __bfloat162float(x0[t * 192 + c]);
    const float mean = s * (1.f / 192.f);
#pragma unroll 1
    for (int c = 0; c < 192; c++) {
      const float d = __bfloat162float(x0[t * 192 + c]) - mean;
      v = fmaf(d, d, v);
    }
    const float m = round_bf16(mean), sd = round_bf16(sqrtf(round_bf16(round_bf16(v * (1.f / 192.f)) + 1e-5f)));
#pragma unroll 1
    for (int c = 0; c < 192; c++) h[t * 192 + c] = __float2bfloat16(round_bf16(__bfloat162float(x0[t * 192 + c]) - m) / sd);
  }
#pragma unroll 1
  for (int head = 0; head < 4; head++) {
    bar_sync(bar);
#pragma unroll 1
    for (int i = t; i < 49 * 144; i += 128) {
      const int tok = i / 144, n = i % 144, col = (n / 48) * 192 + head * 48 + n % 48;
      float a = 0.f;
#pragma unroll 4
      for (int c = 0; c < 192; c++) a = fmaf(__bfloat162float(h[tok * 192 + c]), __bfloat162float(wqkv[c * 576 + col]), a);
      qkv[i] = __float2bfloat16(a);
    }
    bar_sync(bar);
    if (t < 49) {
      float p[49], m = -INFINITY, s = 0.f;
#pragma unroll
      for (int b = 0; b < 49; b++) {
        float a = 0.f;
#pragma unroll 4
        for (int d = 0; d < 48; d++) a = fmaf(__bfloat162float(qkv[t * 144 + d]), __bfloat162float(qkv[b * 144 + 48 + d]), a);
        p[b] = round_bf16(round_bf16(a) * 0.14433757f);
        m = fmaxf(m, p[b]);
      }
#pragma unroll
      for (int b = 0; b < 49; b++) {
        p[b] = expf(p[b] - m);
        s += p[b];
      }
#pragma unroll
      for (int b = 0; b < 49; b++) p[b] = round_bf16(p[b] / s);
#pragma unroll 1
      for (int d = 0; d < 48; d++) {
        float a = 0.f;
#pragma unroll
        for (int b = 0; b < 49; b++) a = fmaf(p[b], __bfloat162float(qkv[b * 144 + 96 + d]), a);
        o[t * 192 + head * 48 + d] = __float2bfloat16(a);
      }
    }
  }
  bar_sync(bar);
#pragma unroll 1
  for (int i = t; i < 49 * 192; i += 128) {
    const int tok = i / 192, n = i % 192;
    float a = 0.f;
#pragma unroll 4
    for (int c = 0; c < 192; c++) a = fmaf(__bfloat162float(o[tok * 192 + c]), __bfloat162float(wo[c * kCh + n]), a);
    out[((size_t)(y0 + tok / 7) * kImg + c0 + tok % 7) * kCh + n] = __float2bfloat16(__bfloat162float(x0[tok * 192 + n]) + round_bf16(a));
  }
}

__device__ __forceinline__ uint32_t fresh_tid() {
  uint32_t t;
  asm volatile("mov.u32 %0, %%tid.x;" : "=r"(t));
  return t;
}
struct Split {
  uint32_t top, rows, alone, share, pool;
  uint32_t magic[2];
};
struct Windows {
  uint32_t first, count, alone, jump, height, row0, magic;
  __device__ __forceinline__ explicit Windows(const Split& s) {
    uint32_t b;
    asm volatile("mov.u32 %0, %%ctaid.x;" : "=r"(b));
    const bool upper = b < s.top;
    const uint32_t i = upper ? 0 : b - s.top;
    height = upper ? s.rows : kWinPerCol - s.rows;
    row0 = upper ? 0 : s.rows;
    magic = upper ? s.magic[0] : s.magic[1];
    alone = upper ? s.rows : s.alone;
    first = upper ? b * s.rows : i * s.alone;
    count = upper ? s.rows : s.alone + s.share;
    jump = (gridDim.x - s.top - 1 - i) * s.alone + i * s.share;
  }
  __device__ __forceinline__ bool at(uint32_t j, uint32_t& col, uint32_t& row) const {
    const uint32_t v = first + j + (j >= alone ? jump : 0);
    col = (v * magic) >> 20;
    row = v - col * height + row0;
    return row == row0 || j == alone;
  }
  __device__ __forceinline__ void at(uint32_t j, uint32_t& col, uint32_t& row, uint32_t extra) const {
    at(j, col, row);
    if (j == count) {
      col = extra & 255;
      row = extra >> 8;
    }
  }
};
template <uint32_t BYTES>
__device__ __forceinline__ void load_rows(uint32_t dst, const CUtensorMap* tm, uint32_t ch, int x, int y, uint32_t bar) {
  asm volatile("{\n.reg .pred p;\nelect.sync _|p, 0xffffffff;\n"
               "@p mbarrier.arrive.expect_tx.shared::cta.b64 _, [%5], %6;\n"
               "@p cp.async.bulk.tensor.3d.shared::cluster.global.tile.mbarrier::complete_tx::bytes [%0], [%1, {%2, %3, %4}], [%5];\n}"
               ::"r"(dst), "l"(tm), "r"(ch), "r"(x), "r"(y), "r"(bar), "n"(BYTES) : "memory");
}
__device__ __forceinline__ void prefetch_box(const CUtensorMap* tm, int x, int y) {
  asm volatile("cp.async.bulk.prefetch.tensor.3d.L2.global.tile [%0, {%1, %2, %3}];" ::"l"(tm), "r"(0), "r"(x), "r"(y) : "memory");
}
__device__ __forceinline__ void prefetch_rows(const CUtensorMap* tm, int x, int y) {
  asm volatile("{\n.reg .pred p;\nelect.sync _|p, 0xffffffff;\n"
               "@p cp.async.bulk.prefetch.tensor.3d.L2.global.tile [%0, {%1, %2, %3}];\n}" ::"l"(tm), "r"(0), "r"(x), "r"(y) : "memory");
}
__device__ __forceinline__ void store_group(const CUtensorMap* tm, uint32_t src, uint32_t ch, uint32_t x, uint32_t y) {
  asm volatile("cp.async.bulk.tensor.3d.global.shared::cta.tile.bulk_group [%0, {%2, %3, %4}], [%1];"
               ::"l"(tm), "r"(src), "r"(ch), "r"(x), "r"(y) : "memory");
}

template <int N> struct Int { static constexpr int value = N; };
struct Conv {
  uint32_t wt[9], prev[9], acc[7];
  __device__ __forceinline__ void begin(const uint32_t (&cur)[9]) {
#pragma unroll
    for (int x = 0; x < 7; x++) {
      uint32_t a = bmul2(prev[x], wt[0]);
      a = bfma2(prev[x + 1], wt[1], a);
      a = bfma2(prev[x + 2], wt[2], a);
#pragma unroll
      for (int t = 0; t < 3; t++) a = bfma2(cur[x + t], wt[3 + t], a);
      acc[x] = a;
    }
#pragma unroll
    for (int x = 0; x < 9; x++) prev[x] = cur[x];
  }
  __device__ __forceinline__ void start_column(uint32_t slot0, uint32_t bar0, uint32_t parity0, uint32_t slot1, uint32_t bar1,
                                               uint32_t parity1, uint32_t lane, uint32_t dump, bool request, const CUtensorMap* tm,
                                               uint32_t ch, int x, int y) {
    uint32_t cur[9];
    mbar_wait(bar0, parity0);
#pragma unroll
    for (int i = 0; i < 9; i++) prev[i] = lds32(slot0 + lane * 4 + i * 128);
    sts32(dump, prev[0] ^ prev[1] ^ prev[2] ^ prev[3] ^ prev[4] ^ prev[5] ^ prev[6] ^ prev[7] ^ prev[8]);
    if (request) load_rows<HALO_ROW>(slot0, tm, ch, x, y, bar0);
    mbar_wait(bar1, parity1);
#pragma unroll
    for (int i = 0; i < 9; i++) cur[i] = lds32(slot1 + lane * 4 + i * 128);
    begin(cur);
    sts32(dump, acc[0] ^ acc[3] ^ acc[6]);
    if (request) load_rows<HALO_ROW>(slot1, tm, ch, x, y + 1, bar1);
  }
  __device__ __forceinline__ void row_at(uint32_t src, uint32_t dst, uint32_t t) {
    uint32_t cur[9];
#pragma unroll
    for (int x = 0; x < 9; x++) cur[x] = lds32(src + x * 128);
#pragma unroll
    for (int x = 0; x < 7; x++) {
      uint32_t a = acc[x];
#pragma unroll
      for (int i = 0; i < 3; i++) a = bfma2(cur[x + i], wt[6 + i], a);
      sts32((dst ^ (((t + x) & 7) << 4)) + x * 128, bf16x2_to_f16x2(badd2(prev[x + 1], a)));
    }
    begin(cur);
  }
  template <int R>
  __device__ __forceinline__ void row(uint32_t src, uint32_t dst, uint32_t at) {
    uint32_t cur[9];
#pragma unroll
    for (int x = 0; x < 9; x++) cur[x] = lds32(src + x * 128);
#pragma unroll
    for (int x = 0; x < 7; x++) {
      uint32_t a = acc[x];
#pragma unroll
      for (int t = 0; t < 3; t++) a = bfma2(cur[x + t], wt[6 + t], a);
      sts32((dst ^ (((R * 7 + x) & 7) << 4)) + at + x * 128, bf16x2_to_f16x2(badd2(prev[x + 1], a)));
    }
    begin(cur);
  }
};

__global__ void __launch_bounds__(512, 1)
davit_window_attn_kernel(const __grid_constant__ CUtensorMap tm1, const __grid_constant__ CUtensorMap tm7c,
                         const __grid_constant__ CUtensorMap tm7, const __grid_constant__ CUtensorMap tmo,
                         const __grid_constant__ CUtensorMap tmw, const __grid_constant__ CUtensorMap tmwo,
                         const __nv_bfloat16* __restrict__ dw, const __nv_bfloat16* __restrict__ x_raw,
                         const __nv_bfloat16* __restrict__ wqkv_raw, const __nv_bfloat16* __restrict__ wo_raw,
                         __nv_bfloat16* __restrict__ out, Scratch* __restrict__ scr, const Split split) {
  extern __shared__ __align__(1024) uint8_t smem_raw[];
  const uint32_t sb = (uint32_t)__cvta_generic_to_shared(smem_raw);
  const uint32_t tail = sb + OFF_TAIL;
  uint32_t wt[9];
  {
    const uint32_t tid = threadIdx.x;
    const uint32_t wid = __shfl_sync(0xffffffffu, tid >> 5, 0), lane = tid & 31;
    if (wid > 12) {
      const uint32_t chunk = wid - 13, hbar = tail + T_HALO + 24 * chunk, rbar = tail + T_ROW + 16 * chunk;
      if (lane == 0) {
        mbar_init(hbar, 1);
        mbar_init(hbar + 8, 1);
        mbar_init(hbar + 16, 1);
        mbar_init(rbar, 1);
        mbar_init(rbar + 8, 1);
        if (wid == 13) mbar_init(tail + T_RAW, 1);
        if (wid == 14) mbar_init(tail + T_CLAIM, 1);
        fence_async();
      }
      __syncwarp();
      if (blockIdx.x < kUnits) {
        if (wid == 13 && lane == 0) request_unit(blockIdx.x, sb + OFF_RING, tail + T_RAW, &tmw, &tmwo);
        asm volatile("bar.sync 5, 96;" ::: "memory");
      }
      uint32_t col, row;
      Windows(split).at(0, col, row);
      const int x = (int)col * 7 - 1, y = (int)row * 7;
      const uint32_t halo = sb + OFF_HALO + chunk * 3 * HALO_ROW;
      load_rows<HALO_ROW>(halo, &tm1, chunk * 64, x, y - 1, hbar);
      load_rows<HALO_ROW>(halo + HALO_ROW, &tm1, chunk * 64, x, y, hbar + 8);
      load_rows<7 * HALO_ROW>(sb + OFF_KV + chunk * 7 * HALO_ROW, &tm7c, chunk * 64, x, y + 1, rbar);
#pragma unroll
      for (int i = 0; i < 9; i++) wt[i] = __ldg(reinterpret_cast<const uint32_t*>(dw) + i * (kCh / 2) + chunk * 32 + lane);
    } else {
      if (lane == 0) {
        if (wid < 12) {
          const uint32_t i = 2 * wid, counts = (uint32_t)((wid < 8 ? 0x4144444333CCC111ull >> (8 * wid) : 0x11444144u >> (8 * wid - 64)));
          mbar_init(tail + 8 * (i < 11 ? i : i + 9), counts & 15);
          if (wid < 11)
          mbar_init(tail + 8 * (i < 10 ? i + 1 : i + 10), (counts >> 4) & 15);
          fence_async();
        }
      }
      if (wid == 12) {
        for (uint32_t line = blockIdx.x + gridDim.x * lane; line < 2304; line += gridDim.x * 32) {
          const uint8_t* p = (line < 1728) ? reinterpret_cast<const uint8_t*>(wqkv_raw) + line * 128
                                           : reinterpret_cast<const uint8_t*>(wo_raw) + (line - 1728) * 128;
          asm volatile("prefetch.global.L2 [%0];" ::"l"(p));
        }
        if (lane < 7) sts32(tail + T_ZERO + 4 * lane, 0u);
      }
    }
    __syncthreads();
    if (wid < 12) {
#pragma unroll 1
      for (uint32_t u = blockIdx.x, i = 0; u < kUnits; u += gridDim.x, i++) {
        if (i) {
          asm volatile("bar.sync 4, 384;" ::: "memory");
          if (tid == 0) request_unit(u, sb + OFF_RING, tail + T_RAW, &tmw, &tmwo);
        }
        mbar_wait(tail + T_RAW, i & 1);
        prepare_unit(u, wid, lane, sb + OFF_RING, scr);
      }
    }
  }

  if (threadIdx.x >= 384) {
    asm volatile("setmaxnreg.dec.sync.aligned.u32 %0;" ::"n"(56));
    const uint32_t tid = fresh_tid();
    const uint32_t warp = __shfl_sync(0xffffffffu, (tid >> 5) & 3, 0), lane = tid & 31;
    if (warp == 0) {
      if (lane == 0) {
        const Windows win(split);
        uint32_t spins = 0, seen;
        while (true) {
          asm volatile("ld.acquire.gpu.global.u32 %0, [%1];" : "=r"(seen) : "l"(&scr->ready) : "memory");
          if ((seen & 31) == kUnits) break;
          if (++spins > (1u << 22)) __trap();
        }
        asm volatile("fence.proxy.async.global;" ::: "memory");
        const uint8_t* w = scr->weights;
        {
          const int e0 = (int)((seen >> 10) & 511) - 128, e1 = (int)(seen >> 19) - 128;
          sts32(tail + T_SCALE, pack_f16(fmaxf(0.20823509f * pow2(9 - e0), 0x1p-24f), fmaxf(0.20823509f * pow2(9 - e1), 0x1p-24f)));
          if ((seen & 0x3E0u) || e0 < 1 || e1 < 1) sts32(tail + T_ALL, 1u);
        }
#pragma unroll
        for (uint32_t s = 0; s < 3; s++) {
          mbar_expect_tx(tail + T_FULL + 8 * s, W_PART);
          bulk_load(sb + OFF_RING + s * W_PART, w + s * W_PART, W_PART, tail + T_FULL + 8 * s);
        }
#pragma unroll 1
        for (uint32_t j = 2; j < 4 && j < win.count; j++) {
          uint32_t col, row;
          const bool fresh = win.at(j, col, row);
          if (j == 3 || fresh) prefetch_box(&tm7, 7 * col - 1, 7 * row + 1);
          if (fresh) prefetch_box(&tm7, 7 * col - 1, 7 * row - 1);
        }
        if (atomicInc(&scr->passed, gridDim.x - 1) == gridDim.x - 1) scr->ready = 0;
        const uint32_t uses = 8 * (win.count / 3 + 1);
        uint32_t s = 0, parity = 0;
#pragma unroll 1
        for (uint32_t u = 3; u < uses; u++) {
          mbar_wait(tail + T_EMPTY + 8 * s, parity);
          mbar_expect_tx(tail + T_FULL + 8 * s, W_PART);
          bulk_load(sb + OFF_RING + s * W_PART, w + (u & 7) * W_PART, W_PART, tail + T_FULL + 8 * s);
          s = (s == 2) ? 0 : s + 1;
          parity ^= (s == 0);
        }
      }
    } else {
      Conv cv;
#pragma unroll
      for (int i = 0; i < 9; i++) cv.wt[i] = wt[i];
      {
        const uint32_t chunk = warp - 1, halo = sb + OFF_HALO + chunk * 3 * HALO_ROW, hbar = tail + T_HALO + 24 * chunk;
        const Windows win(split);
        uint32_t col, row, cn, rn;
        const uint32_t staged = (win.count > 1 && !win.at(1, col, row)) ? 2 : 1;
        const bool fresh = win.at(staged, cn, rn);
        const int xn = 7 * cn - 1, yn = fresh ? 7 * rn - 1 : 7 * rn + 1;
        if (staged < win.count) load_rows<HALO_ROW>(halo + 2 * HALO_ROW, &tm1, chunk * 64, xn, yn, hbar + 16);
        cv.start_column(halo, hbar, 0, halo + HALO_ROW, hbar + 8, 0, lane, tail + T_DUMP, staged < win.count, &tm1, chunk * 64, xn, yn + 1);
        if (staged == 2)
          load_rows<7 * HALO_ROW>(sb + OFF_KV + (3 + chunk) * 7 * HALO_ROW, &tm7c, chunk * 64, 7 * col - 1, 7 * row + 1,
                                  tail + T_ROW + 16 * chunk + 8);
#pragma unroll 1
        for (uint32_t i = 0; i < staged; i++) {
          mbar_wait(tail + T_ROW + 16 * chunk + 8 * i, 0);
#pragma unroll 1
          for (uint32_t r = 0; r < 7; r++)
            cv.row_at(sb + OFF_KV + ((3 * i + chunk) * 7 + r) * HALO_ROW + lane * 4,
                      sb + OFF_X0 + chunk * X0_CHUNK + lane * 4 + (7 * i + r) * X0_ROW, 7 * r);
          __syncwarp();
          arrive_elected(tail + T_X0FULL + 8 * i);
          if (i == 0 && chunk == 0 && staged < win.count) prefetch_rows(&tm7, xn, yn + 3);
        }
      }
      const uint32_t chunk = __shfl_sync(0xffffffffu, (fresh_tid() >> 5) & 3, 0) - 1, ch = chunk * 64;
      const uint32_t halo = sb + OFF_HALO + chunk * 3 * HALO_ROW, hbar = tail + T_HALO + 24 * chunk;
      const uint32_t src = halo + lane * 4, dst = sb + OFF_X0 + chunk * X0_CHUNK + lane * 4;
      const Windows win(split);
      uint32_t count = win.count;
      uint32_t col, row;
      const uint32_t staged = (count > 1 && !win.at(1, col, row)) ? 2 : 1;
      bool fresh = win.at(staged, col, row);
      uint32_t s0 = 2, p0 = 0;
#pragma unroll 1
      for (uint32_t j = staged; j < count; j++) {
        int x = (int)col * 7 - 1, y = (int)row * 7;
        uint32_t at = 7 * j % kRows * X0_ROW;
        if (fresh) {
          const uint32_t s1 = (s0 == 2) ? 0 : s0 + 1;
          cv.start_column(halo + s0 * HALO_ROW, hbar + 8 * s0, p0, halo + s1 * HALO_ROW, hbar + 8 * s1, p0 ^ (s0 == 2), lane, tail + T_DUMP, true,
                          &tm1, ch, x, y + 2);
          p0 ^= (s0 != 0);
          s0 = (s0 == 0) ? 2 : s0 - 1;
        }
        const uint32_t slot[3] = {s0, (s0 == 2) ? 0 : s0 + 1, (s0 == 0) ? 2 : s0 - 1}, parity[3] = {p0, p0 ^ (s0 == 2), p0 ^ (s0 != 0)};
        if (chunk == 0 && j + 1 == win.count) {
          if (lane == 0) {
            const uint32_t i = atomicInc(&scr->claims, gridDim.x - 1);
            uint32_t extra = ~0u;
            if (i < split.pool) {
              const uint32_t v = kWinPerCol * (kWinPerCol - split.rows) - split.pool + i, c = (v * split.magic[1]) >> 20;
              extra = c + 256 * (v - c * (kWinPerCol - split.rows) + split.rows);
              prefetch_box(&tm7, 7 * c - 1, 7 * (extra >> 8) - 1);
              prefetch_box(&tm7, 7 * c - 1, 7 * (extra >> 8) + 1);
            }
            sts32(tail + T_EXTRA, extra);
            mbar_arrive(tail + T_CLAIM);
          }
          __syncwarp();
        }
        if (chunk == 0 && j + 2 < win.count) {
          if (win.at(j + 2, col, row)) prefetch_rows(&tm7, 7 * col - 1, 7 * row - 1);
          prefetch_rows(&tm7, 7 * col - 1, 7 * row + 1);
        }
        fresh = win.at(j + 1, col, row);
        auto step = [&](auto r) {
          constexpr int R = decltype(r)::value;
          if (R == kRows - 14) {
            mbar_wait(tail + T_X0FREE + 8 * (j & 1), ((j >> 1) & 1) ^ 1);
          }
          if (R == 4) {
            if (j + 1 == win.count) {
              mbar_wait(tail + T_CLAIM, 0);
              const uint32_t extra = __shfl_sync(0xffffffffu, lds32(tail + T_EXTRA), 0);
              count += (extra != ~0u);
              col = extra & 255;
              row = extra >> 8;
              fresh = true;
            }
            x = (int)col * 7 - 1;
            y = (int)row * 7 - (fresh ? 9 : 7);
          }
          mbar_wait(hbar + 8 * slot[R % 3], parity[R % 3] ^ ((R / 3) & 1));
          cv.template row<R>(src + slot[R % 3] * HALO_ROW, dst, at);
          if (R < 4 || j + 1 < count) load_rows<HALO_ROW>(halo + slot[R % 3] * HALO_ROW, &tm1, ch, x, y + R + 4, hbar + 8 * slot[R % 3]);
          at = (at == (kRows - 1) * X0_ROW) ? 0 : at + X0_ROW;
        };
        step(Int<0>()); step(Int<1>()); step(Int<2>()); step(Int<3>()); step(Int<4>()); step(Int<5>()); step(Int<6>());
        __syncwarp();
        arrive_elected(tail + T_X0FULL + 8 * (j % 3));
        s0 = slot[1];
        p0 = parity[1];
      }
    }
    __syncwarp();
    asm volatile("bar.sync 0, 512;" ::: "memory");
  } else {
    asm volatile("setmaxnreg.inc.sync.aligned.u32 %0;" ::"n"(152));
    const uint32_t wid = __shfl_sync(0xffffffffu, fresh_tid() >> 5, 0);
    const uint32_t wg = wid >> 2, warp = wid & 3;
    uint32_t lane;
    asm volatile("mov.u32 %0, %%laneid;" : "=r"(lane));
    const uint32_t count = Windows(split).count;
    const uint32_t q = lane & 3, mat = lane >> 3, row = lane & 7;
    const uint32_t area = sb + OFF_KV + wg * KV_SIZE;
    const uint32_t bars = tail + T_WG + 32 * wg;
    const bool full = warp < 3;
    const bool valid = full || lane < 4;
    const bool lead = lane == 0;
    uint32_t k_st, v_st, x_ld, x_mask, x_row, o_st;
    {
      const uint32_t rowg = full ? 2 * warp + (mat & 1) : 6, colg = full ? (mat >> 1) : (mat & 1);
      k_st = full ? area + A_K0 + colg * K_CHUNK + rowg * 128 + row * 16 : area + A_K0 + 768 + q * 4;
      v_st = full ? area + A_V0 + colg * V_GROUP + rowg * 128 + row * 16 : area + A_ONES + lane * 16;
      const uint32_t t = 16 * warp + row + 8 * (mat & 1);
      x_ld = (t < 49) ? sb + OFF_X0 + t * 128 + (((mat >> 1) ^ row) << 4) : tail + T_ZERO;
      x_mask = (t < 49) ? ~0u : 0u;
      x_row = t / 7;
      const uint32_t a = area + (full ? t : 48) * 64;
      o_st = a + (((full ? (mat >> 1) : 0) ^ ((a >> 7) & 3)) << 4) + (full ? 0 : 4 * q);
    }
    const uint32_t v_last = area + A_LAST + q * 32;
    const uint32_t pad = (valid ? 0u : 0xFC00u) | (full ? 0u : 0xFC000000u);
    const uint64_t k_desc = make_desc(area + A_K0, K_CHUNK, 128);
    const uint64_t v_desc = make_desc(area + A_V0, 128, V_GROUP);
    const uint64_t w_desc = make_desc(sb + OFF_RING, 128, 256);
    if (wg == 2) asm volatile("bar.arrive 8, 256;" ::: "memory");
    auto send_output = [&](uint32_t j, uint32_t parity, bool last) {
      uint32_t col, row;
      if (last) Windows(split).at(j, col, row, lds32(tail + T_EXTRA));
      else Windows(split).at(j, col, row);
      mbar_wait(bars + B_OUTRDY, parity);
#pragma unroll
      for (int i = 0; i < 6; i++) store_group(&tmo, area + i * OUT_GROUP, 32 * i, 7 * col, 7 * row);
      asm volatile("cp.async.bulk.commit_group;" ::: "memory");
    };
    uint32_t round = 0;
#pragma unroll 1
    for (; 3 * round + wg <= count; round++) {
      const uint32_t r = __shfl_sync(0xffffffffu, round, 0), j = 3 * r + wg, ph = r & 1;
      if (j == count) {
        mbar_wait(tail + T_CLAIM, 0);
        if (__shfl_sync(0xffffffffu, lds32(tail + T_EXTRA), 0) == ~0u) break;
      }
      const uint32_t m = 8 * r / 3, rot = 8 * r - 3 * m;
      const uint32_t ra = 8 * rot, rb = (rot == 2) ? 0 : ra + 8, rc = (rot == 0) ? 16 : ra - 8;
      const uint32_t pa = m & 1, pb = pa ^ (rot == 2), pc = pa ^ (rot != 0);
      uint32_t x[48], ka[24], va[24], oa[24], ob[24], rr, scales;
      uint32_t (&qa)[24] = ka;
      uint32_t sc0[14], sc1[14], pa0[12], pa1[12], ov0[14], ov1[14];
      mbar_wait(tail + T_X0FULL + 8 * wg, ph);
      asm volatile("" : "+r"(x_mask));
      const uint32_t x_at = 7 * j % kRows;
      const uint32_t x_a = x_ld + ((x_at * X0_ROW - (x_row >= kRows - x_at ? X0_CHUNK : 0)) & x_mask);
      auto load_x = [&](auto s0, auto s1) {
#pragma unroll
        for (int s = decltype(s0)::value; s < decltype(s1)::value; s++)
          ldsm4((x_a ^ (((s & 3) << 5) & x_mask)) + ((s >> 2) * X0_CHUNK & x_mask), x[4 * s], x[4 * s + 1], x[4 * s + 2], x[4 * s + 3]);
      };
      load_x(Int<0>(), Int<6>());
#pragma unroll
      for (int p = 0; p < 2; p++) {
        asm volatile("bar.sync %0, 256;" ::"r"(8 + wg) : "memory");
        mbar_wait(tail + T_FULL + ra, pa ^ p);
        if (p == 0) {
          load_x(Int<6>(), Int<12>());
          warp_arrive(tail + T_X0FREE + 8 * (j & 1), lead);
        }
        wg_fence();
        {
          const uint64_t d = desc_at(w_desc, ra * (W_PART / 8));
          issue_half<1>(ka, x, d);
          if (p == 0) wg_fence();
          issue_half<0>(ka, x, d);
        }
        wg_commit();
        if (p == 0) {
          if (!full && lead && r > 0) send_output(j - 3, ph ^ 1, false);
          __syncwarp();
        }
        if (p == 1) {
          wg_wait<1>();
          fence_regs(ov1);
          if (lead) mbar_arrive(bars + B_KVFREE);
          pack_o<0, 2>(ov1, &oa[12]);
        }
        mbar_wait(tail + T_FULL + rb, pb ^ p);
        wg_fence();
        {
          const uint64_t d = desc_at(w_desc, rb * (W_PART / 8));
          issue_half<1>(va, x, d);
          wg_commit();
          wg_wait<1>();
          if (lead) mbar_arrive(tail + T_EMPTY + ra);
          __syncwarp();
          issue_half<0>(va, x, d);
          wg_commit();
        }
        asm volatile("bar.arrive %0, 256;" ::"r"(wg == 2 ? 8 : 9 + wg) : "memory");
        if (p == 0) {
          scales = __shfl_sync(0xffffffffu, lds32(tail + T_SCALE), 0);
          const bool odd = q & 1;
          uint32_t lane_sums[2];
          lane_stats_packed(x, lane_sums);
          const uint32_t packed = quad_stats_packed(lane_sums, odd);
          float sum = h_lo(packed), squares = h_hi(packed);
          const bool fine = (squares >= 0.1875f || (pad & (odd ? 0xFC000000u : 0xFC00u))) & (squares <= 65504.f) & (sum * sum <= 96.f * squares);
          const bool exact = !__all_sync(0xffffffffu, fine);
          if (exact) {
            wg_wait<0>();
            row_stats(x, odd, sum, squares);
          }
          const float mean = sum * (1.f / 192.f);
          const float rs = 16.f * rsqrt_fast(fmaxf(fmaf(squares, 1.f / 192.f, -mean * mean), 0.f) + 1e-5f);
          if (exact) {
            const uint32_t range = __reduce_max_sync(0xffffffffu, __float_as_uint(squares * fmaxf(rs * rs, 1.f)));
            if ((range > 0x4D400000u || (range != 0u && range < 0x4585A800u)) && lead) {
              scr->redo[blockIdx.x + gridDim.x * j] = 1;
              sts32(tail + T_ANY, 1u);
            }
          }
          const float o = __shfl_xor_sync(0xffffffffu, rs, 1);
          rr = pack_f16(odd ? o : rs, odd ? rs : o);
          if (!full && lead) {
            asm volatile("cp.async.bulk.wait_group.read 0;" ::: "memory");
            mbar_arrive(bars + B_OUTFREE);
          }
          __syncwarp();
          mbar_wait(bars + B_OUTFREE, ph);
        } else {
          mbar_wait(bars + B_KVFREE, 0);
        }
        fence_regs(ka);
        store_k(ka, k_st, full, lane < 4, rr);
        mbar_wait(tail + T_FULL + rc, pc ^ p);
        wg_fence();
        {
          const uint64_t d = desc_at(w_desc, rc * (W_PART / 8));
          issue_half<2>(qa, x, d);
          wg_commit();
          wg_wait<1>();
          if (lead) mbar_arrive(tail + T_EMPTY + rb);
          __syncwarp();
          issue_half<0>(qa, x, d);
          wg_commit();
        }
        fence_regs(va);
        if (p == 0 && !full) {
          sts128_if(true, v_st, 0x3C003C00u, 0x3C003C00u, 0x3C003C00u, 0x3C003C00u);
          sts128_if(lane < 16, v_st + 512, 0x3C003C00u, 0x3C003C00u, 0x3C003C00u, 0x3C003C00u);
        }
        store_v(va, v_st, v_last, full, lane < 4, rr);
        fence_async();
        warp_arrive(bars + B_KVRDY, lead);
        wg_wait<0>();
        fence_regs(qa);
        if (lead) mbar_arrive(tail + T_EMPTY + rc);
        {
          const uint32_t rq = hmul2(rr, 0x18001800u);
#pragma unroll
          for (int i = 0; i < 24; i += 2) {
            qa[i] = hmul2_lo(qa[i], rq);
            qa[i + 1] = hmul2_hi(qa[i + 1], rq);
          }
        }
        const uint32_t cr = (p == 0) ? both<0>(scales) : both<1>(scales);
        mbar_wait(bars + B_KVRDY, p);

        wg_fence();
        issue_s(sc0, &qa[0], desc_at(k_desc, 0));
        wg_commit();
        uint32_t top0, top1, last0, last1;
        if (p == 0) {
          issue_s(sc1, &qa[12], desc_at(k_desc, A_K1));
          wg_commit();
          wg_wait<1>();
          fence_regs(sc0);
          top0 = softmax_top(sc0, lane, cr, last0);
          softmax_rows<12, 0>(sc0, top0, last0, cr, pad, v_last, pa0, ov0);
          wg_fence();
          issue_pv(ov0, pa0, desc_at(v_desc, 0));
          wg_commit();
          wg_wait<1>();
          fence_regs(sc1);
          top1 = softmax_top(sc1, lane, cr, last1);
          softmax_rows<0, 2>(sc1, top1, last1, cr, pad, v_last + 128, pa1, ov1);
        } else {
          wg_wait<0>();
          fence_regs(sc0);
          wg_fence();
          issue_s(sc1, &qa[12], desc_at(k_desc, A_K1));
          wg_commit();
          top0 = softmax_top(sc0, lane, cr, last0);
          wg_wait<0>();
          fence_regs(sc1);
          softmax_rows<12, 0>(sc0, top0, last0, cr, pad, v_last, pa0, ov0);
          mbar_wait(tail + T_FULL + ra, pa);
          wg_fence();
          issue_pv(ov0, pa0, desc_at(v_desc, 0));
          wg_commit();
          issue_out<6>(x, oa, desc_at(w_desc, ra * (W_PART / 8)));
          wg_commit();
          top1 = softmax_top(sc1, lane, cr, last1);
          wg_wait<1>();
          fence_regs(ov0);
          softmax_rows<0, 2>(sc1, top1, last1, cr, pad, v_last + 128, pa1, ov1);
        }
        wg_fence();
        issue_pv(ov1, pa1, desc_at(v_desc, A_ONES - A_V0));
        wg_commit();
        wg_wait<1>();
        if (p == 0) fence_regs(ov0);
        else if (lead) mbar_arrive(tail + T_EMPTY + ra);
        {
          uint32_t big;
          asm("{\n.reg .pred p, q;\n.reg .b32 t;\nmax.xorsign.abs.f16x2 t, %1, %2;\nabs.f16x2 t, t;\nsetp.gt.f16x2 p|q, t, %3;\n"
              "or.pred p, p, q;\nselp.u32 %0, 1, 0, p;\n}" : "=r"(big) : "r"(top0), "r"(top1), "r"(0x60006000u));
          if (__any_sync(0xffffffffu, big) && lead) {
            scr->redo[blockIdx.x + gridDim.x * j] = 1;
            sts32(tail + T_ANY, 1u);
          }
          __syncwarp();
        }
        uint32_t (&o)[24] = (p == 0) ? oa : ob;
        pack_o<12, 0>(ov0, &o[0]);
        if (p == 1) {
          mbar_wait(tail + T_FULL + rb, pb);
          wg_fence();
          issue_out<3>(x, &ob[0], desc_at(w_desc, rb * (W_PART / 8)));
          wg_commit();
          wg_wait<1>();
          fence_regs(ov1);
          if (lead) mbar_arrive(bars + B_KVFREE);
          pack_o<0, 2>(ov1, &o[12]);
        }
      }
      wg_fence();
      issue_out<3>(x, &ob[12], desc_at(w_desc, rb * (W_PART / 8) + 3 * WO_STEP));
      wg_commit();
      mbar_wait(bars + B_KVFREE, 1);
      wg_wait<0>();
      fence_regs(x);
      if (lead) mbar_arrive(tail + T_EMPTY + rb);
      asm volatile("" : "+r"(o_st));
      if (full) {
#pragma unroll
        for (int s = 0; s < 12; s++)
          stsm4((o_st ^ (((s ^ (s >> 1)) & 1) << 5)) + (s >> 1) * OUT_GROUP, f16x2_to_bf16x2(x[4 * s]), f16x2_to_bf16x2(x[4 * s + 1]),
                f16x2_to_bf16x2(x[4 * s + 2]), f16x2_to_bf16x2(x[4 * s + 3]));
        fence_async();
        warp_arrive(bars + B_OUTRDY, lead);
      } else {
#pragma unroll
        for (int i = 0; i < 24; i++)
          sts32_if(lane < 4, (o_st ^ (((i ^ ((i >> 1) & 2)) & 3) << 4)) + (i >> 2) * OUT_GROUP, f16x2_to_bf16x2(x[2 * i]));
        fence_async();
        warp_arrive(bars + B_OUTRDY, lead);
      }
    }
    if (!full && lead && round > 0) send_output(3 * round + wg - 3, (round & 1) ^ 1, true);
    __syncwarp();
    if (3 * round <= count) {
#pragma unroll 1
      for (uint32_t i = 0; i < 5; i++) {
        if (i % 3 == 0) {
          asm volatile("bar.sync %0, 256;" ::"r"(8 + wg) : "memory");
          asm volatile("bar.arrive %0, 256;" ::"r"(wg == 2 ? 8 : 9 + wg) : "memory");
        }
        const uint32_t u = 8 * round + i;
        mbar_wait(tail + T_FULL + 8 * (u % 3), (u / 3) & 1);
        if (lead) mbar_arrive(tail + T_EMPTY + 8 * (u % 3));
        __syncwarp();
      }
    }
    if (!full && lead) asm volatile("cp.async.bulk.wait_group.read 0;" ::: "memory");
    __syncwarp();
    asm volatile("bar.sync 0, 512;" ::: "memory");
    const uint32_t redo_all = lds32(tail + T_ALL);
    if (redo_all | lds32(tail + T_ANY)) {
      const uint32_t t = fresh_tid(), c = t >> 7;
      if ((t & 127) == 96) asm volatile("cp.async.bulk.wait_group 0;\nfence.proxy.async.global;" ::: "memory");
      __syncwarp();
      const Windows win(split);
      const uint32_t extra = lds32(tail + T_EXTRA);
      for (uint32_t j = c; j < win.count + (extra != ~0u); j += 3) {
        uint8_t* flag = &scr->redo[blockIdx.x + gridDim.x * j];
        if (!redo_all && !*reinterpret_cast<volatile uint8_t*>(flag)) continue;
        uint32_t col, row;
        win.at(j, col, row, extra);
        redo_window(7 * col, 7 * row, t & 127, 1 + c, smem_raw + c * REDO_BYTES, x_raw, dw, wqkv_raw, wo_raw, out);
        if ((t & 127) == 0) *flag = 0;
      }
    }
  }
}

typedef CUresult (*EncodeTiledFn)(CUtensorMap*, CUtensorMapDataType, cuuint32_t, void*, const cuuint64_t*, const cuuint64_t*,
                                  const cuuint32_t*, const cuuint32_t*, CUtensorMapInterleave, CUtensorMapSwizzle,
                                  CUtensorMapL2promotion, CUtensorMapFloatOOBfill);

}

extern "C" void kernel_launch(void* const* d_in, const int* in_sizes, int n_in, void* d_out, int out_size) {
  (void)in_sizes; (void)n_in; (void)out_size;
  static EncodeTiledFn encode = nullptr;
  static int grid = 0;
  static void* scratch = nullptr;
  if (!encode) {
    void* fn = nullptr;
    cudaDriverEntryPointQueryResult st;
    cudaGetDriverEntryPoint("cuTensorMapEncodeTiled", &fn, cudaEnableDefault, &st);
    encode = (EncodeTiledFn)fn;
    cudaFuncSetAttribute(davit_window_attn_kernel, cudaFuncAttributeMaxDynamicSharedMemorySize, SMEM_BYTES);
    cudaGetSymbolAddress(&scratch, g_scratch);
    int dev = 0;
    cudaGetDevice(&dev);
    cudaDeviceGetAttribute(&grid, cudaDevAttrMultiProcessorCount, dev);
    if (grid > 1024) grid = 1024;
  }
  Split split = {};
  {
    const uint32_t g = grid, n = kNumWin / g;
    if (g > kWinPerCol && g <= 2 * kWinPerCol && kWinPerCol - n <= n) {
      const uint32_t below = (kWinPerCol - n) * kWinPerCol;
      split.top = kWinPerCol;
      split.rows = (below > (n + 1) * (g - kWinPerCol) && n + 1 < kWinPerCol) ? n + 1 : n;
      split.alone = kWinPerCol - split.rows;
    }
    const uint32_t others = g - split.top, rest = kNumWin - split.top * split.rows - others * split.alone;
    split.share = rest / others;
    split.pool = rest % others;
    split.magic[0] = split.rows ? ((1u << 20) + split.rows - 1) / split.rows : 0;
    split.magic[1] = ((1u << 20) + kWinPerCol - split.rows - 1) / (kWinPerCol - split.rows);
  }
  auto image_map = [&](void* base, cuuint32_t c, cuuint32_t w, cuuint32_t h, CUtensorMapSwizzle swizzle) {
    CUtensorMap tm;
    const cuuint64_t dims[3] = {(cuuint64_t)kCh, (cuuint64_t)kImg, (cuuint64_t)kImg};
    const cuuint64_t strides[2] = {(cuuint64_t)kCh * 2, (cuuint64_t)kCh * 2 * kImg};
    const cuuint32_t box[3] = {c, w, h};
    const cuuint32_t estr[3] = {1, 1, 1};
    encode(&tm, CU_TENSOR_MAP_DATA_TYPE_BFLOAT16, 3, base, dims, strides, box, estr, CU_TENSOR_MAP_INTERLEAVE_NONE, swizzle,
           CU_TENSOR_MAP_L2_PROMOTION_L2_128B, CU_TENSOR_MAP_FLOAT_OOB_FILL_NONE);
    return tm;
  };
  auto weight_map = [&](void* base, cuuint64_t cols, cuuint32_t rows) {
    CUtensorMap tm;
    const cuuint64_t dims[2] = {cols, (cuuint64_t)kCh};
    const cuuint64_t strides[1] = {cols * 2};
    const cuuint32_t box[2] = {32, rows};
    const cuuint32_t estr[2] = {1, 1};
    encode(&tm, CU_TENSOR_MAP_DATA_TYPE_BFLOAT16, 2, base, dims, strides, box, estr, CU_TENSOR_MAP_INTERLEAVE_NONE,
           CU_TENSOR_MAP_SWIZZLE_64B, CU_TENSOR_MAP_L2_PROMOTION_L2_128B, CU_TENSOR_MAP_FLOAT_OOB_FILL_NONE);
    return tm;
  };
  davit_window_attn_kernel<<<grid, 512, SMEM_BYTES, cudaStreamPerThread>>>(
      image_map(d_in[0], 64, 9, 1, CU_TENSOR_MAP_SWIZZLE_NONE), image_map(d_in[0], 64, 9, 7, CU_TENSOR_MAP_SWIZZLE_NONE),
      image_map(d_in[0], 192, 9, 7, CU_TENSOR_MAP_SWIZZLE_NONE), image_map(d_out, 32, 7, 7, CU_TENSOR_MAP_SWIZZLE_64B),
      weight_map(d_in[2], 576, 192), weight_map(d_in[3], 192, 32),
      (const __nv_bfloat16*)d_in[1], (const __nv_bfloat16*)d_in[0], (const __nv_bfloat16*)d_in[2], (const __nv_bfloat16*)d_in[3],
      (__nv_bfloat16*)d_out, (Scratch*)scratch, split);
}
```

```cpp
#include <cuda.h>
#include <cuda_bf16.h>
#include <cuda_runtime.h>
#include <stdint.h>

namespace {

constexpr int kImg = 511;
constexpr int kCh = 192;
constexpr int kWinPerCol = 73;
constexpr int kNumWin = 73 * 73;

constexpr uint32_t W_PART = 36864;
constexpr uint32_t W_STEP = 3072;
constexpr uint32_t WO_STEP = 6144;
constexpr uint32_t W_BYTES = 8 * W_PART;

struct Scratch {
  uint8_t weights[W_BYTES];
  uint32_t ready;
  uint32_t passed;
  uint32_t claims;
  uint8_t redo[2 * kNumWin];
};
__device__ __align__(128) Scratch g_scratch;

constexpr uint32_t OFF_RING = 0;
constexpr uint32_t OFF_X0 = 3 * W_PART;
constexpr uint32_t kRows = 19;
constexpr uint32_t X0_ROW = 7 * 128;
constexpr uint32_t X0_CHUNK = kRows * X0_ROW;
constexpr uint32_t OFF_HALO = OFF_X0 + 3 * X0_CHUNK;
constexpr uint32_t HALO_ROW = 9 * 128;
constexpr uint32_t OFF_KV = OFF_HALO + 9 * HALO_ROW;
constexpr uint32_t K_CHUNK = 784;
constexpr uint32_t V_GROUP = 768;
constexpr uint32_t A_K0 = 0;
constexpr uint32_t A_V0 = 6 * K_CHUNK;
constexpr uint32_t A_ONES = A_V0 + 6 * V_GROUP;
constexpr uint32_t A_V1 = A_ONES + V_GROUP;
constexpr uint32_t A_K1 = A_V1 + 6 * V_GROUP;
constexpr uint32_t A_LAST = A_K1 + 6 * K_CHUNK;
constexpr uint32_t KV_SIZE = 19840;
constexpr uint32_t OUT_GROUP = 3328;
static_assert(A_LAST + 256 <= KV_SIZE && 5 * OUT_GROUP + 3136 <= KV_SIZE && KV_SIZE % 128 == 0 && 42 * HALO_ROW <= 3 * KV_SIZE &&
              21 * HALO_ROW >= KV_SIZE, "consumer area");
constexpr uint32_t OFF_TAIL = OFF_KV + 3 * KV_SIZE;
constexpr uint32_t SMEM_BYTES = OFF_TAIL + 360;
static_assert(SMEM_BYTES <= 232448, "shared memory");

constexpr uint32_t T_FULL = 0;
constexpr uint32_t T_EMPTY = 24;
constexpr uint32_t T_X0FULL = 48;
constexpr uint32_t T_X0FREE = 72;
constexpr uint32_t T_HALO = 88;
constexpr uint32_t T_WG = 160;
constexpr uint32_t B_KVRDY = 0;
constexpr uint32_t B_KVFREE = 8;
constexpr uint32_t B_OUTRDY = 16;
constexpr uint32_t B_OUTFREE = 24;
constexpr uint32_t T_RAW = 256;
constexpr uint32_t T_CLAIM = 264;
constexpr uint32_t T_ZERO = 272;
constexpr uint32_t T_SCALE = 288;
constexpr uint32_t T_ALL = 292;
constexpr uint32_t T_ANY = 296;
constexpr uint32_t T_DUMP = 300;
constexpr uint32_t T_ROW = 304;
constexpr uint32_t T_EXTRA = 352;

__device__ __forceinline__ void hmma_n96_first(uint32_t (&d)[24], uint32_t a0, uint32_t a1, uint32_t a2, uint32_t a3, uint64_t desc) {
  asm volatile("wgmma.mma_async.sync.aligned.m64n96k16.f16.f16.f16 "
               "{%0, %1, %2, %3, %4, %5, %6, %7, %8, %9, %10, %11, %12, %13, %14, %15, "
               "%16, %17, %18, %19, %20, %21, %22, %23}, "
               "{%24, %25, %26, %27}, %28, 0, 1, 1, 0;\n"
               : "=r"(d[0]), "=r"(d[1]), "=r"(d[2]), "=r"(d[3]), "=r"(d[4]), "=r"(d[5]), "=r"(d[6]), "=r"(d[7]),
                 "=r"(d[8]), "=r"(d[9]), "=r"(d[10]), "=r"(d[11]), "=r"(d[12]), "=r"(d[13]), "=r"(d[14]), "=r"(d[15]),
                 "=r"(d[16]), "=r"(d[17]), "=r"(d[18]), "=r"(d[19]), "=r"(d[20]), "=r"(d[21]), "=r"(d[22]), "=r"(d[23])
               : "r"(a0), "r"(a1), "r"(a2), "r"(a3), "l"(desc));
}
__device__ __forceinline__ void hmma_n96(uint32_t (&d)[24], uint32_t a0, uint32_t a1, uint32_t a2, uint32_t a3, uint64_t desc) {
  asm volatile("wgmma.mma_async.sync.aligned.m64n96k16.f16.f16.f16 "
               "{%0, %1, %2, %3, %4, %5, %6, %7, %8, %9, %10, %11, %12, %13, %14, %15, "
               "%16, %17, %18, %19, %20, %21, %22, %23}, "
               "{%24, %25, %26, %27}, %28, 1, 1, 1, 0;\n"
               : "+r"(d[0]), "+r"(d[1]), "+r"(d[2]), "+r"(d[3]), "+r"(d[4]), "+r"(d[5]), "+r"(d[6]), "+r"(d[7]),
                 "+r"(d[8]), "+r"(d[9]), "+r"(d[10]), "+r"(d[11]), "+r"(d[12]), "+r"(d[13]), "+r"(d[14]), "+r"(d[15]),
                 "+r"(d[16]), "+r"(d[17]), "+r"(d[18]), "+r"(d[19]), "+r"(d[20]), "+r"(d[21]), "+r"(d[22]), "+r"(d[23])
               : "r"(a0), "r"(a1), "r"(a2), "r"(a3), "l"(desc));
}
__device__ __forceinline__ void hmma_n96_over(uint32_t (&d)[24], uint32_t a0, uint32_t a1, uint32_t a2, uint32_t a3, uint64_t desc) {
  asm volatile("wgmma.mma_async.sync.aligned.m64n96k16.f16.f16.f16 "
               "{%0, %1, %2, %3, %4, %5, %6, %7, %8, %9, %10, %11, %12, %13, %14, %15, "
               "%16, %17, %18, %19, %20, %21, %22, %23}, "
               "{%24, %25, %26, %27}, %28, 0, 1, 1, 0;\n"
               : "+r"(d[0]), "+r"(d[1]), "+r"(d[2]), "+r"(d[3]), "+r"(d[4]), "+r"(d[5]), "+r"(d[6]), "+r"(d[7]),
                 "+r"(d[8]), "+r"(d[9]), "+r"(d[10]), "+r"(d[11]), "+r"(d[12]), "+r"(d[13]), "+r"(d[14]), "+r"(d[15]),
                 "+r"(d[16]), "+r"(d[17]), "+r"(d[18]), "+r"(d[19]), "+r"(d[20]), "+r"(d[21]), "+r"(d[22]), "+r"(d[23])
               : "r"(a0), "r"(a1), "r"(a2), "r"(a3), "l"(desc));
}
__device__ __forceinline__ void hmma_n56_first(uint32_t (&d)[14], uint32_t a0, uint32_t a1, uint32_t a2, uint32_t a3, uint64_t desc) {
  asm volatile("wgmma.mma_async.sync.aligned.m64n56k16.f16.f16.f16 "
               "{%0, %1, %2, %3, %4, %5, %6, %7, %8, %9, %10, %11, %12, %13}, "
               "{%14, %15, %16, %17}, %18, 0, 1, 1, 0;\n"
               : "=r"(d[0]), "=r"(d[1]), "=r"(d[2]), "=r"(d[3]), "=r"(d[4]), "=r"(d[5]), "=r"(d[6]), "=r"(d[7]),
                 "=r"(d[8]), "=r"(d[9]), "=r"(d[10]), "=r"(d[11]), "=r"(d[12]), "=r"(d[13])
               : "r"(a0), "r"(a1), "r"(a2), "r"(a3), "l"(desc));
}
__device__ __forceinline__ void hmma_n56(uint32_t (&d)[14], uint32_t a0, uint32_t a1, uint32_t a2, uint32_t a3, uint64_t desc) {
  asm volatile("wgmma.mma_async.sync.aligned.m64n56k16.f16.f16.f16 "
               "{%0, %1, %2, %3, %4, %5, %6, %7, %8, %9, %10, %11, %12, %13}, "
               "{%14, %15, %16, %17}, %18, 1, 1, 1, 0;\n"
               : "+r"(d[0]), "+r"(d[1]), "+r"(d[2]), "+r"(d[3]), "+r"(d[4]), "+r"(d[5]), "+r"(d[6]), "+r"(d[7]),
                 "+r"(d[8]), "+r"(d[9]), "+r"(d[10]), "+r"(d[11]), "+r"(d[12]), "+r"(d[13])
               : "r"(a0), "r"(a1), "r"(a2), "r"(a3), "l"(desc));
}
__device__ __forceinline__ void hmma_n192(uint32_t (&d)[48], uint32_t a0, uint32_t a1, uint32_t a2, uint32_t a3, uint64_t desc) {
  asm volatile("wgmma.mma_async.sync.aligned.m64n192k16.f16.f16.f16 "
               "{%0, %1, %2, %3, %4, %5, %6, %7, %8, %9, %10, %11, %12, %13, %14, %15, "
               "%16, %17, %18, %19, %20, %21, %22, %23, %24, %25, %26, %27, %28, %29, %30, %31, "
               "%32, %33, %34, %35, %36, %37, %38, %39, %40, %41, %42, %43, %44, %45, %46, %47}, "
               "{%48, %49, %50, %51}, %52, 1, 1, 1, 0;\n"
               : "+r"(d[0]), "+r"(d[1]), "+r"(d[2]), "+r"(d[3]), "+r"(d[4]), "+r"(d[5]), "+r"(d[6]), "+r"(d[7]),
                 "+r"(d[8]), "+r"(d[9]), "+r"(d[10]), "+r"(d[11]), "+r"(d[12]), "+r"(d[13]), "+r"(d[14]), "+r"(d[15]),
                 "+r"(d[16]), "+r"(d[17]), "+r"(d[18]), "+r"(d[19]), "+r"(d[20]), "+r"(d[21]), "+r"(d[22]), "+r"(d[23]),
                 "+r"(d[24]), "+r"(d[25]), "+r"(d[26]), "+r"(d[27]), "+r"(d[28]), "+r"(d[29]), "+r"(d[30]), "+r"(d[31]),
                 "+r"(d[32]), "+r"(d[33]), "+r"(d[34]), "+r"(d[35]), "+r"(d[36]), "+r"(d[37]), "+r"(d[38]), "+r"(d[39]),
                 "+r"(d[40]), "+r"(d[41]), "+r"(d[42]), "+r"(d[43]), "+r"(d[44]), "+r"(d[45]), "+r"(d[46]), "+r"(d[47])
               : "r"(a0), "r"(a1), "r"(a2), "r"(a3), "l"(desc));
}

__device__ __forceinline__ void wg_fence() { asm volatile("wgmma.fence.sync.aligned;\n" ::: "memory"); }
__device__ __forceinline__ void wg_commit() { asm volatile("wgmma.commit_group.sync.aligned;\n" ::: "memory"); }
template <int N> __device__ __forceinline__ void wg_wait() { asm volatile("wgmma.wait_group.sync.aligned %0;\n" ::"n"(N) : "memory"); }
__device__ __forceinline__ uint64_t make_desc(uint32_t addr, uint32_t lbo, uint32_t sbo) {
  return (uint64_t)((addr & 0x3FFFF) >> 4) | ((uint64_t)(lbo >> 4) << 16) | ((uint64_t)(sbo >> 4) << 32);
}
__device__ __forceinline__ uint64_t desc_add(uint64_t d, uint32_t bytes) { return d + (bytes >> 4); }
__device__ __forceinline__ uint64_t desc_at(uint64_t d, uint32_t bytes) {
  uint64_t r;
  asm volatile("mov.b64 %0, %1;" : "=l"(r) : "l"(d));
  return desc_add(r, bytes);
}

__device__ __forceinline__ void mbar_init(uint32_t bar, uint32_t count) {
  asm volatile("mbarrier.init.shared::cta.b64 [%0], %1;" ::"r"(bar), "r"(count) : "memory");
}
__device__ __forceinline__ void mbar_expect_tx(uint32_t bar, uint32_t bytes) {
  asm volatile("mbarrier.arrive.expect_tx.shared::cta.b64 _, [%0], %1;" ::"r"(bar), "r"(bytes) : "memory");
}
__device__ __forceinline__ void mbar_wait(uint32_t bar, uint32_t parity) {
  asm volatile("{\n.reg .pred p;\n.reg .u32 c;\n"
               "mbarrier.try_wait.parity.shared::cta.b64 p, [%0], %1;\n"
               "@p bra DONE;\n"
               "mov.u32 c, 0;\n"
               "SPIN:\n"
               "mbarrier.try_wait.parity.shared::cta.b64 p, [%0], %1, 4000;\n"
               "@p bra DONE;\n"
               "add.u32 c, c, 1;\n"
               "setp.lt.u32 p, c, 1048576;\n"
               "@!p trap;\n"
               "bra SPIN;\n"
               "DONE:\n}" ::"r"(bar), "r"(parity) : "memory");
}
__device__ __forceinline__ void bar_sync(uint32_t id) { asm volatile("bar.sync %0, 128;" ::"r"(id) : "memory"); }
__device__ __forceinline__ void mbar_arrive(uint32_t bar) { asm volatile("mbarrier.arrive.shared::cta.b64 _, [%0];" ::"r"(bar) : "memory"); }
__device__ __forceinline__ void warp_arrive(uint32_t bar, bool first) {
  __syncwarp();
  if (first) mbar_arrive(bar);
}
__device__ __forceinline__ void arrive_elected(uint32_t bar) {
  asm volatile("{\n.reg .pred p;\nelect.sync _|p, 0xffffffff;\n@p mbarrier.arrive.shared::cta.b64 _, [%0];\n}" ::"r"(bar) : "memory");
}
__device__ __forceinline__ void fence_async() { asm volatile("fence.proxy.async.shared::cta;" ::: "memory"); }
__device__ __forceinline__ uint32_t lds32(uint32_t a) {
  uint32_t v;
  asm volatile("ld.shared.b32 %0, [%1];" : "=r"(v) : "r"(a) : "memory");
  return v;
}
__device__ __forceinline__ void lds64(uint32_t a, uint32_t& v0, uint32_t& v1) {
  asm volatile("ld.shared.v2.b32 {%0, %1}, [%2];" : "=r"(v0), "=r"(v1) : "r"(a) : "memory");
}
__device__ __forceinline__ void sts32(uint32_t a, uint32_t v) { asm volatile("st.shared.b32 [%0], %1;" ::"r"(a), "r"(v) : "memory"); }
__device__ __forceinline__ void sts64(uint32_t a, uint32_t v0, uint32_t v1) {
  asm volatile("st.shared.v2.b32 [%0], {%1, %2};" ::"r"(a), "r"(v0), "r"(v1) : "memory");
}
__device__ __forceinline__ void sts32_if(bool on, uint32_t a, uint32_t v) {
  asm volatile("{\n.reg .pred p;\nsetp.ne.u32 p, %2, 0;\n@p st.shared.b32 [%0], %1;\n}" ::"r"(a), "r"(v), "r"((uint32_t)on) : "memory");
}
__device__ __forceinline__ void ldsm4(uint32_t a, uint32_t& r0, uint32_t& r1, uint32_t& r2, uint32_t& r3) {
  asm volatile("ldmatrix.sync.aligned.m8n8.x4.shared.b16 {%0, %1, %2, %3}, [%4];" : "=r"(r0), "=r"(r1), "=r"(r2), "=r"(r3) : "r"(a) : "memory");
}
__device__ __forceinline__ void stsm4(uint32_t a, uint32_t r0, uint32_t r1, uint32_t r2, uint32_t r3) {
  asm volatile("stmatrix.sync.aligned.m8n8.x4.shared.b16 [%0], {%1, %2, %3, %4};" ::"r"(a), "r"(r0), "r"(r1), "r"(r2), "r"(r3) : "memory");
}
__device__ __forceinline__ void stsm4_t(uint32_t a, uint32_t r0, uint32_t r1, uint32_t r2, uint32_t r3) {
  asm volatile("stmatrix.sync.aligned.m8n8.x4.trans.shared.b16 [%0], {%1, %2, %3, %4};" ::"r"(a), "r"(r0), "r"(r1), "r"(r2), "r"(r3) : "memory");
}
__device__ __forceinline__ uint32_t pack_bf16(float lo, float hi) {
  uint32_t r;
  asm("cvt.rn.bf16x2.f32 %0, %1, %2;" : "=r"(r) : "f"(hi), "f"(lo));
  return r;
}
__device__ __forceinline__ uint32_t pack_f16(float lo, float hi) {
  uint32_t r;
  asm("cvt.rn.f16x2.f32 %0, %1, %2;" : "=r"(r) : "f"(hi), "f"(lo));
  return r;
}
__device__ __forceinline__ float bf_lo(uint32_t v) { return __uint_as_float(v << 16); }
__device__ __forceinline__ float bf_hi(uint32_t v) { return __uint_as_float(v & 0xffff0000u); }
__device__ __forceinline__ float h_lo(uint32_t v) {
  float r;
  asm("{\n.reg .b16 l, h;\nmov.b32 {l, h}, %1;\ncvt.f32.f16 %0, l;\n}" : "=f"(r) : "r"(v));
  return r;
}
__device__ __forceinline__ float h_hi(uint32_t v) {
  float r;
  asm("{\n.reg .b16 l, h;\nmov.b32 {l, h}, %1;\ncvt.f32.f16 %0, h;\n}" : "=f"(r) : "r"(v));
  return r;
}
__device__ __forceinline__ uint32_t bf16x2_to_f16x2(uint32_t v) { return pack_f16(bf_lo(v), bf_hi(v)); }
__device__ __forceinline__ uint32_t f16x2_to_bf16x2(uint32_t v) { return pack_bf16(h_lo(v), h_hi(v)); }
__device__ __forceinline__ uint32_t bmul2(uint32_t a, uint32_t b) {
  uint32_t r;
  asm("mul.rn.bf16x2 %0, %1, %2;" : "=r"(r) : "r"(a), "r"(b));
  return r;
}
__device__ __forceinline__ uint32_t badd2(uint32_t a, uint32_t b) {
  uint32_t r;
  asm("add.rn.bf16x2 %0, %1, %2;" : "=r"(r) : "r"(a), "r"(b));
  return r;
}
__device__ __forceinline__ uint32_t bfma2(uint32_t a, uint32_t b, uint32_t c) {
  uint32_t r;
  asm("fma.rn.bf16x2 %0, %1, %2, %3;" : "=r"(r) : "r"(a), "r"(b), "r"(c));
  return r;
}
__device__ __forceinline__ uint32_t hadd2(uint32_t a, uint32_t b) {
  uint32_t d;
  asm("add.rn.f16x2 %0, %1, %2;" : "=r"(d) : "r"(a), "r"(b));
  return d;
}
__device__ __forceinline__ uint32_t hmax2(uint32_t a, uint32_t b) {
  uint32_t d;
  asm("max.f16x2 %0, %1, %2;" : "=r"(d) : "r"(a), "r"(b));
  return d;
}
__device__ __forceinline__ uint32_t hmul2(uint32_t a, uint32_t b) {
  uint32_t d;
  asm("mul.rn.f16x2 %0, %1, %2;" : "=r"(d) : "r"(a), "r"(b));
  return d;
}
__device__ __forceinline__ uint32_t hmul2_lo(uint32_t a, uint32_t r) {
  uint32_t d;
  asm("{\n.reg .b16 l, h;\n.reg .b32 t;\nmov.b32 {l, h}, %2;\nmov.b32 t, {l, l};\nmul.rn.f16x2 %0, %1, t;\n}" : "=r"(d) : "r"(a), "r"(r));
  return d;
}
__device__ __forceinline__ uint32_t hmul2_hi(uint32_t a, uint32_t r) {
  uint32_t d;
  asm("{\n.reg .b16 l, h;\n.reg .b32 t;\nmov.b32 {l, h}, %2;\nmov.b32 t, {h, h};\nmul.rn.f16x2 %0, %1, t;\n}" : "=r"(d) : "r"(a), "r"(r));
  return d;
}
__device__ __forceinline__ float rcp(float x) {
  float r;
  asm("rcp.approx.ftz.f32 %0, %1;" : "=f"(r) : "f"(x));
  return r;
}
__device__ __forceinline__ float rsqrt_fast(float x) {
  float r;
  asm("rsqrt.approx.ftz.f32 %0, %1;" : "=f"(r) : "f"(x));
  return r;
}
template <int N> __device__ __forceinline__ void fence_regs(uint32_t (&d)[N]) {
#pragma unroll
  for (int i = 0; i < N; i++) asm volatile("" : "+r"(d[i])::"memory");
}

__device__ __forceinline__ void row_stats(const uint32_t (&x)[48], bool odd, float& sum, float& squares) {
  float s0 = 0.f, q0 = 0.f, s1 = 0.f, q1 = 0.f;
#pragma unroll
  for (int i = 0; i < 48; i++) {
    const float lo = h_lo(x[i]), hi = h_hi(x[i]);
    if (i & 1) {
      s1 += lo; q1 = fmaf(lo, lo, q1);
      s1 += hi; q1 = fmaf(hi, hi, q1);
    } else {
      s0 += lo; q0 = fmaf(lo, lo, q0);
      s0 += hi; q0 = fmaf(hi, hi, q0);
    }
  }
  sum = (odd ? s1 : s0) + __shfl_xor_sync(0xffffffffu, odd ? s0 : s1, 1);
  squares = (odd ? q1 : q0) + __shfl_xor_sync(0xffffffffu, odd ? q0 : q1, 1);
  sum += __shfl_xor_sync(0xffffffffu, sum, 2);
  squares += __shfl_xor_sync(0xffffffffu, squares, 2);
}
__device__ __forceinline__ void lane_stats_packed(const uint32_t (&x)[48], uint32_t (&t)[2]) {
  uint32_t s[4] = {x[0], x[1], x[2], x[3]}, q[4];
#pragma unroll
  for (int r = 0; r < 4; r++) q[r] = hmul2(x[r], x[r]);
#pragma unroll
  for (int i = 4; i < 48; i++) {
    asm("add.rn.f16x2 %0, %0, %1;" : "+r"(s[i & 3]) : "r"(x[i]));
    asm("fma.rn.f16x2 %0, %1, %1, %0;" : "+r"(q[i & 3]) : "r"(x[i]));
  }
#pragma unroll
  for (int r = 0; r < 2; r++) {
    const uint32_t a = hadd2(s[r], s[r + 2]), b = hadd2(q[r], q[r + 2]);
    t[r] = hadd2(__byte_perm(a, b, 0x5410), __byte_perm(a, b, 0x7632));
  }
}
__device__ __forceinline__ uint32_t quad_stats_packed(const uint32_t (&t)[2], bool odd) {
  const uint32_t u = hadd2(__shfl_xor_sync(0xffffffffu, odd ? t[0] : t[1], 1), odd ? t[1] : t[0]);
  return hadd2(u, __shfl_xor_sync(0xffffffffu, u, 2));
}

__device__ __forceinline__ void store_k(const uint32_t (&k)[24], uint32_t k_st, bool full, bool first_row, uint32_t r) {
  if (full) {
#pragma unroll
    for (int j = 0; j < 12; j += 2)
      stsm4(k_st + (j / 6) * A_K1 + (j % 6) * K_CHUNK, hmul2_lo(k[2 * j], r), hmul2_hi(k[2 * j + 1], r), hmul2_lo(k[2 * j + 2], r),
            hmul2_hi(k[2 * j + 3], r));
  } else {
#pragma unroll
    for (int j = 0; j < 12; j++) sts32_if(first_row, k_st + (j / 6) * A_K1 + (j % 6) * K_CHUNK, hmul2_lo(k[2 * j], r));
    __syncwarp();
  }
}
template <int HALF> __device__ __forceinline__ uint32_t both(uint32_t v) {
  uint32_t d;
  if (HALF == 0) asm("{\n.reg .b16 l, h;\nmov.b32 {l, h}, %1;\nmov.b32 %0, {l, l};\n}" : "=r"(d) : "r"(v));
  else asm("{\n.reg .b16 l, h;\nmov.b32 {l, h}, %1;\nmov.b32 %0, {h, h};\n}" : "=r"(d) : "r"(v));
  return d;
}
__device__ __forceinline__ uint32_t exp2_scaled(uint32_t s, uint32_t c, uint32_t off) {
  uint32_t d;
  asm("{\n.reg .b32 t;\nfma.rn.f16x2 t, %1, %2, %3;\nex2.approx.f16x2 %0, t;\n}" : "=r"(d) : "r"(s), "r"(c), "r"(off));
  return d;
}
__device__ __forceinline__ uint32_t softmax_top(const uint32_t (&s)[14], uint32_t lane, uint32_t c, uint32_t& last) {
  last = __shfl_sync(0xffffffffu, __byte_perm(s[12], s[13], 0x5410), lane & 28);
  const uint32_t a = hmax2(hmax2(hmax2(s[0], s[2]), s[4]), hmax2(hmax2(s[6], s[8]), s[10]));
  const uint32_t b = hmax2(hmax2(hmax2(s[1], s[3]), s[5]), hmax2(hmax2(s[7], s[9]), s[11]));
  uint32_t m = hmax2(__byte_perm(a, b, 0x5410), __byte_perm(a, b, 0x7632));
  m = hmax2(m, __shfl_xor_sync(0xffffffffu, m, 1));
  m = hmax2(hmax2(m, last), __shfl_xor_sync(0xffffffffu, m, 2));
  return hmul2(m, c);
}
__device__ __forceinline__ void lds128(uint32_t a, uint32_t* v) {
  asm volatile("ld.shared.v4.b32 {%0, %1, %2, %3}, [%4];" : "=r"(v[0]), "=r"(v[1]), "=r"(v[2]), "=r"(v[3]) : "r"(a) : "memory");
}
template <int SUM, int VAL>
__device__ __forceinline__ void softmax_rows(const uint32_t (&s)[14], uint32_t top, uint32_t last, uint32_t c, uint32_t pad,
                                             uint32_t v_last, uint32_t (&pa)[12], uint32_t (&ov)[14]) {
  uint32_t off, v[6];
  lds128(v_last, v);
  lds64(v_last + 16, v[4], v[5]);
  asm("sub.rn.f16x2 %0, %1, %2;" : "=r"(off) : "r"(pad), "r"(top));
#pragma unroll
  for (int j = 0; j < 6; j++) {
    pa[2 * j] = exp2_scaled(s[2 * j], both<0>(c), both<0>(off));
    pa[2 * j + 1] = exp2_scaled(s[2 * j + 1], both<1>(c), both<1>(off));
  }
  const uint32_t p = exp2_scaled(last, c, off);
#pragma unroll
  for (int j = 0; j < 6; j++) {
    ov[VAL + 2 * j] = hmul2_lo(v[j], p);
    ov[VAL + 2 * j + 1] = hmul2_hi(v[j], p);
  }
  ov[SUM] = __byte_perm(p, p, 0x1010);
  ov[SUM + 1] = __byte_perm(p, p, 0x3232);
}
__device__ __forceinline__ void issue_pv(uint32_t (&ov)[14], const uint32_t (&pa)[12], uint64_t v_desc) {
#pragma unroll
  for (int k = 0; k < 3; k++) hmma_n56(ov, pa[4 * k], pa[4 * k + 1], pa[4 * k + 2], pa[4 * k + 3], desc_add(v_desc, k * 256));
}
__device__ __forceinline__ void sts128_if(bool on, uint32_t a, uint32_t v0, uint32_t v1, uint32_t v2, uint32_t v3) {
  asm volatile("{\n.reg .pred p;\nsetp.ne.u32 p, %5, 0;\n@p st.shared.v4.b32 [%0], {%1, %2, %3, %4};\n}"
               ::"r"(a), "r"(v0), "r"(v1), "r"(v2), "r"(v3), "r"((uint32_t)on) : "memory");
}
__device__ __forceinline__ void store_v(const uint32_t (&v)[24], uint32_t v_st, uint32_t v_last, bool full, bool first_row, uint32_t r) {
  if (full) {
#pragma unroll
    for (int j = 0; j < 12; j += 2)
      stsm4_t(v_st + (j / 6) * (A_V1 - A_V0) + (j % 6) * V_GROUP, hmul2_lo(v[2 * j], r), hmul2_hi(v[2 * j + 1], r), hmul2_lo(v[2 * j + 2], r),
              hmul2_hi(v[2 * j + 3], r));
  } else {
#pragma unroll
    for (int h = 0; h < 2; h++) {
      sts128_if(first_row, v_last + h * 128, hmul2_lo(v[12 * h], r), hmul2_lo(v[12 * h + 2], r), hmul2_lo(v[12 * h + 4], r),
                hmul2_lo(v[12 * h + 6], r));
      sts128_if(first_row, v_last + h * 128 + 16, hmul2_lo(v[12 * h + 8], r), hmul2_lo(v[12 * h + 10], r), 0u, 0u);
    }
    __syncwarp();
  }
}
__device__ __forceinline__ void issue_s(uint32_t (&s)[14], const uint32_t* qa, uint64_t k_desc) {
  hmma_n56_first(s, qa[0], qa[1], qa[2], qa[3], k_desc);
#pragma unroll
  for (int k = 1; k < 3; k++) hmma_n56(s, qa[4 * k], qa[4 * k + 1], qa[4 * k + 2], qa[4 * k + 3], desc_add(k_desc, k * 2 * K_CHUNK));
}
template <int SUM, int VAL>
__device__ __forceinline__ void pack_o(const uint32_t (&ov)[14], uint32_t* o) {
  const uint32_t p = pack_f16(rcp(fmaxf(h_lo(ov[SUM]), 0.5f)), rcp(fmaxf(h_lo(ov[SUM + 1]), 0.5f)));
#pragma unroll
  for (int j = 0; j < 6; j++) {
    o[2 * j] = hmul2_lo(ov[VAL + 2 * j], p);
    o[2 * j + 1] = hmul2_hi(ov[VAL + 2 * j + 1], p);
  }
}
template <int FIRST>
__device__ __forceinline__ void issue_half(uint32_t (&d)[24], const uint32_t (&x)[48], uint64_t desc) {
  if (FIRST == 2) hmma_n96_over(d, x[0], x[1], x[2], x[3], desc);
  if (FIRST == 1) hmma_n96_first(d, x[0], x[1], x[2], x[3], desc);
#pragma unroll
  for (int s = FIRST ? 1 : 6; s < (FIRST ? 6 : 12); s++) hmma_n96(d, x[4 * s], x[4 * s + 1], x[4 * s + 2], x[4 * s + 3], desc_add(desc, s * W_STEP));
}
template <int N>
__device__ __forceinline__ void issue_out(uint32_t (&d)[48], const uint32_t* o, uint64_t desc) {
#pragma unroll
  for (int s = 0; s < N; s++) hmma_n192(d, o[4 * s], o[4 * s + 1], o[4 * s + 2], o[4 * s + 3], desc_add(desc, s * WO_STEP));
}

__device__ __forceinline__ void mma_bf16(float (&c)[4], uint32_t a0, uint32_t a1, uint32_t a2, uint32_t a3, uint32_t b0, uint32_t b1) {
  asm("mma.sync.aligned.m16n8k16.row.col.f32.bf16.bf16.f32 {%0, %1, %2, %3}, {%4, %5, %6, %7}, {%8, %9}, {%0, %1, %2, %3};"
      : "+f"(c[0]), "+f"(c[1]), "+f"(c[2]), "+f"(c[3]) : "r"(a0), "r"(a1), "r"(a2), "r"(a3), "r"(b0), "r"(b1));
}
__device__ __forceinline__ void mma_bf16_k8(float (&d)[4], uint32_t a0, uint32_t a1, uint32_t b, const float (&c)[4]) {
  asm("mma.sync.aligned.m16n8k8.row.col.f32.bf16.bf16.f32 {%0, %1, %2, %3}, {%4, %5}, {%6}, {%7, %8, %9, %10};"
      : "=f"(d[0]), "=f"(d[1]), "=f"(d[2]), "=f"(d[3]) : "r"(a0), "r"(a1), "r"(b), "f"(c[0]), "f"(c[1]), "f"(c[2]), "f"(c[3]));
}
__device__ __forceinline__ bool on_diagonal(uint32_t lane) { return (lane & 3) == (lane >> 3); }
__device__ __forceinline__ float column_stats(const uint32_t (&v)[24], uint32_t lane, uint32_t& hi, uint32_t& lo) {
  float sum[2][4] = {}, sq[2][4] = {}, sr[2][4] = {};
#pragma unroll
  for (int c = 0; c < 24; c += 4) mma_bf16(sum[(c >> 2) & 1], v[c], v[c + 1], v[c + 2], v[c + 3], 0x3F803F80u, 0x3F803F80u);
#pragma unroll
  for (int c = 0; c < 24; c += 2) {
    mma_bf16_k8(sq[(c >> 1) & 1], v[c], v[c + 1], v[c], sq[(c >> 1) & 1]);
    mma_bf16_k8(sr[(c >> 1) & 1], v[c], v[c + 1], v[c + 1], sr[(c >> 1) & 1]);
  }
  const float total = (sum[0][0] + sum[0][2]) + (sum[1][0] + sum[1][2]), mean = total * (1.f / 192.f);
  const bool diag = on_diagonal(lane);
  const float n2 = (lane & 4) ? (sq[0][1] + sq[1][1]) + (sr[0][3] + sr[1][3]) : (sq[0][0] + sq[1][0]) + (sr[0][2] + sr[1][2]);
  hi = diag ? __float_as_uint(n2) : 0u;
  lo = __float_as_uint((diag && n2 > 0.f) ? fmaxf(fmaf(-total, mean, n2), 0.f) : INFINITY);
  return mean;
}
__device__ __forceinline__ uint32_t warp_max_abs(const uint32_t (&v)[8]) {
  uint32_t m = v[0];
#pragma unroll
  for (int c = 1; c < 8; c++) asm("max.NaN.xorsign.abs.bf16x2 %0, %0, %1;" : "+r"(m) : "r"(v[c]));
  return __reduce_max_sync(0xffffffffu, max(m & 0x7fffu, (m >> 16) & 0x7fffu));
}
__device__ __forceinline__ bool norms_in_range(uint32_t hi, uint32_t lo) {
  return hi - 0x08800000u <= 0x7B000000u - 0x08800000u && lo >= hi - (12u << 23);
}
__device__ __forceinline__ int norm_exponent(uint32_t n2) { return (int)(0x453B8000u - n2) >> 24; }
__device__ __forceinline__ void scale_to_f16(uint32_t (&v)[8], uint32_t lane, int e, float mean) {
  const uint32_t ident = on_diagonal(lane) ? (uint32_t)(e + 127) << ((lane & 4) ? 23 : 7) : 0u;
  const float c0 = -mean * __uint_as_float((uint32_t)(e + 127) << 23), c[4] = {c0, c0, c0, c0};
#pragma unroll
  for (int i = 0; i < 8; i += 2) {
    float d[4];
    mma_bf16_k8(d, v[i], v[i + 1], ident, c);
    v[i] = pack_f16(d[0], d[1]);
    v[i + 1] = pack_f16(d[2], d[3]);
  }
}
__device__ __forceinline__ float pow2(int e) { return __uint_as_float((uint32_t)(min(max(e, -126), 127) + 127) << 23); }

constexpr uint32_t kUnits = 24;
constexpr uint32_t RAW_O = W_PART, RAW_RED = RAW_O + 32 * 384;
__device__ __forceinline__ void bulk_load(uint32_t dst, const void* src, uint32_t bytes, uint32_t bar) {
  asm volatile("cp.async.bulk.shared::cluster.global.mbarrier::complete_tx::bytes [%0], [%1], %2, [%3];"
               ::"r"(dst), "l"(src), "r"(bytes), "r"(bar) : "memory");
}
__device__ __forceinline__ void tile_load(uint32_t dst, const CUtensorMap* tm, uint32_t c0, uint32_t c1, uint32_t bar) {
  asm volatile("cp.async.bulk.tensor.2d.shared::cluster.global.tile.mbarrier::complete_tx::bytes [%0], [%1, {%2, %3}], [%4];"
               ::"r"(dst), "l"(tm), "r"(c0), "r"(c1), "r"(bar) : "memory");
}
__device__ __forceinline__ void request_unit(uint32_t u, uint32_t raw, uint32_t bar, const CUtensorMap* tmw, const CUtensorMap* tmwo) {
  const bool is_o = (u & 7) >= 6;
  const uint32_t pair = is_o ? u & 1 : (u & 7) / 3, part = is_o ? 1 : (u & 7) % 3;
  mbar_expect_tx(bar, is_o ? W_PART + 32 * 384 : W_PART);
#pragma unroll
  for (uint32_t i = 0; i < 3; i++) tile_load(raw + i * (192 * 64), tmw, ((part + 1) % 3) * 192 + pair * 96 + 32 * i, 0, bar);
  if (is_o) {
#pragma unroll
    for (uint32_t i = 0; i < 6; i++) tile_load(raw + RAW_O + i * (32 * 64), tmwo, 32 * i, pair * 96 + (u >> 3) * 32, bar);
  }
}
__device__ __forceinline__ void ldsm4_t(uint32_t a, uint32_t* v) {
  asm volatile("ldmatrix.sync.aligned.m8n8.x4.trans.shared.b16 {%0, %1, %2, %3}, [%4];" : "=r"(v[0]), "=r"(v[1]), "=r"(v[2]), "=r"(v[3]) : "r"(a) : "memory");
}
__device__ __forceinline__ void prepare_unit(uint32_t u, uint32_t wid, uint32_t lane, uint32_t raw, Scratch* scr) {
  const bool is_o = (u & 7) >= 6;
  const uint32_t third = u >> 3;
  uint32_t v[24], w[8];
  const uint32_t src = raw + (wid >> 2) * (192 * 64) + lane * 64 + (((wid ^ (lane >> 1)) & 3) << 4);
#pragma unroll
  for (int m = 0; m < 6; m++) ldsm4_t(src + m * (32 * 64), &v[4 * m]);
  uint32_t hi, lo, top = 0;
  const float mean = column_stats(v, lane, hi, lo);
  if (is_o) {
#pragma unroll
    for (int m = 0; m < 2; m++)
      ldsm4_t(raw + RAW_O + (wid >> 1) * (32 * 64) + lane * 64 + ((((2 * wid + m) ^ (lane >> 1)) & 3) << 4), &w[4 * m]);
    top = warp_max_abs(w);
  } else {
#pragma unroll
    for (int m = 0; m < 2; m++) ldsm4_t(src + (2 * third + m) * (32 * 64), &w[4 * m]);
  }
  hi = __reduce_max_sync(0xffffffffu, hi);
  lo = __reduce_min_sync(0xffffffffu, lo);
  if (lane == 0) {
    sts64(raw + RAW_RED + wid * 16, hi, lo);
    sts32(raw + RAW_RED + wid * 16 + 8, top);
  }
  asm volatile("bar.sync 4, 384;" ::: "memory");
  lds64(raw + RAW_RED + (lane % 12) * 16, hi, lo);
  top = lds32(raw + RAW_RED + (lane % 12) * 16 + 8);
  hi = __reduce_max_sync(0xffffffffu, hi);
  lo = __reduce_min_sync(0xffffffffu, lo);
  top = __reduce_max_sync(0xffffffffu, top);
  const int e = norm_exponent(hi);
  scale_to_f16(w, lane, is_o ? -e : e - 4, is_o ? 0.f : mean);
  const uint32_t mat = lane >> 3, at = (mat & 1) * 128 + (lane & 7) * 16;
#pragma unroll
  for (int m = 0; m < 2; m++)
    stsm4(raw + at + (is_o ? (mat >> 1) * WO_STEP + (2 * wid + m) * 256 : (2 * m + (mat >> 1)) * W_STEP + wid * 256), w[4 * m], w[4 * m + 1],
          w[4 * m + 2], w[4 * m + 3]);
  fence_async();
  asm volatile("bar.sync 4, 384;" ::: "memory");
  if (wid == 0 && lane == 0) {
    asm volatile("cp.async.bulk.global.shared::cta.bulk_group [%0], [%1], %2;\ncp.async.bulk.commit_group;"
                 ::"l"(scr->weights + (u & 7) * W_PART + third * (W_PART / 3)), "r"(raw), "n"(W_PART / 3) : "memory");
    const bool bad = is_o ? !(__uint_as_float(top << 16) * pow2(-e) <= 0.25f) : !norms_in_range(hi, lo);
    const uint32_t exponent = (!is_o && third == 0 && u % 3 != 1) ? (uint32_t)(e + 64) << (u < 3 ? 10 : 19) : 0u;
    asm volatile("cp.async.bulk.wait_group 0;" ::: "memory");
    asm volatile("red.relaxed.gpu.global.add.u32 [%0], %1;" ::"l"(&scr->ready), "r"(bad ? 33u : 1u + exponent) : "memory");
  }
  __syncwarp();
}

constexpr uint32_t REDO_BYTES = 75776;
static_assert(3 * REDO_BYTES <= OFF_TAIL && (3 * 49 * 192 + 49 * 144) * 2 <= REDO_BYTES, "redo scratch");
__device__ __forceinline__ float round_bf16(float x) { return __bfloat162float(__float2bfloat16(x)); }
__device__ __forceinline__ void redo_window(int c0, int y0, int t, uint32_t bar, uint8_t* scratch, const __nv_bfloat16* x,
                                            const __nv_bfloat16* dw, const __nv_bfloat16* wqkv, const __nv_bfloat16* wo,
                                            __nv_bfloat16* out) {
  __nv_bfloat16* x0 = reinterpret_cast<__nv_bfloat16*>(scratch);
  __nv_bfloat16* h = x0 + 49 * 192;
  __nv_bfloat16* o = h + 49 * 192;
  __nv_bfloat16* qkv = o + 49 * 192;
  bar_sync(bar);
#pragma unroll 1
  for (int i = t; i < 49 * 192; i += 128) {
    const int tok = i / 192, c = i % 192, y = y0 + tok / 7, xx = c0 + tok % 7;
    float pe = 0.f;
#pragma unroll 1
    for (int k = 0; k < 9; k++) {
      const int yy = y + k / 3 - 1, xj = xx + k % 3 - 1;
      const bool in = (uint32_t)yy < kImg && (uint32_t)xj < kImg;
      const float v = in ? __bfloat162float(x[((size_t)yy * kImg + xj) * kCh + c]) : 0.f;
      pe = round_bf16(pe + round_bf16(v * __bfloat162float(dw[k * kCh + c])));
    }
    x0[i] = __float2bfloat16(__bfloat162float(x[((size_t)y * kImg + xx) * kCh + c]) + pe);
  }
  bar_sync(bar);
  if (t < 49) {
    float s = 0.f, v = 0.f;
#pragma unroll 1
    for (int c = 0; c < 192; c++) s += __bfloat162float(x0[t * 192 + c]);
    const float mean = s * (1.f / 192.f);
#pragma unroll 1
    for (int c = 0; c < 192; c++) {
      const float d = __bfloat162float(x0[t * 192 + c]) - mean;
      v = fmaf(d, d, v);
    }
    const float m = round_bf16(mean), sd = round_bf16(sqrtf(round_bf16(round_bf16(v * (1.f / 192.f)) + 1e-5f)));
#pragma unroll 1
    for (int c = 0; c < 192; c++) h[t * 192 + c] = __float2bfloat16(round_bf16(__bfloat162float(x0[t * 192 + c]) - m) / sd);
  }
#pragma unroll 1
  for (int head = 0; head < 4; head++) {
    bar_sync(bar);
#pragma unroll 1
    for (int i = t; i < 49 * 144; i += 128) {
      const int tok = i / 144, n = i % 144, col = (n / 48) * 192 + head * 48 + n % 48;
      float a = 0.f;
#pragma unroll 4
      for (int c = 0; c < 192; c++) a = fmaf(__bfloat162float(h[tok * 192 + c]), __bfloat162float(wqkv[c * 576 + col]), a);
      qkv[i] = __float2bfloat16(a);
    }
    bar_sync(bar);
    if (t < 49) {
      float p[49], m = -INFINITY, s = 0.f;
#pragma unroll
      for (int b = 0; b < 49; b++) {
        float a = 0.f;
#pragma unroll 4
        for (int d = 0; d < 48; d++) a = fmaf(__bfloat162float(qkv[t * 144 + d]), __bfloat162float(qkv[b * 144 + 48 + d]), a);
        p[b] = round_bf16(round_bf16(a) * 0.14433757f);
        m = fmaxf(m, p[b]);
      }
#pragma unroll
      for (int b = 0; b < 49; b++) {
        p[b] = expf(p[b] - m);
        s += p[b];
      }
#pragma unroll
      for (int b = 0; b < 49; b++) p[b] = round_bf16(p[b] / s);
#pragma unroll 1
      for (int d = 0; d < 48; d++) {
        float a = 0.f;
#pragma unroll
        for (int b = 0; b < 49; b++) a = fmaf(p[b], __bfloat162float(qkv[b * 144 + 96 + d]), a);
        o[t * 192 + head * 48 + d] = __float2bfloat16(a);
      }
    }
  }
  bar_sync(bar);
#pragma unroll 1
  for (int i = t; i < 49 * 192; i += 128) {
    const int tok = i / 192, n = i % 192;
    float a = 0.f;
#pragma unroll 4
    for (int c = 0; c < 192; c++) a = fmaf(__bfloat162float(o[tok * 192 + c]), __bfloat162float(wo[c * kCh + n]), a);
    out[((size_t)(y0 + tok / 7) * kImg + c0 + tok % 7) * kCh + n] = __float2bfloat16(__bfloat162float(x0[tok * 192 + n]) + round_bf16(a));
  }
}

__device__ __forceinline__ uint32_t fresh_tid() {
  uint32_t t;
  asm volatile("mov.u32 %0, %%tid.x;" : "=r"(t));
  return t;
}
struct Split {
  uint32_t top, rows, alone, share, pool;
  uint32_t magic[2];
};
struct Windows {
  uint32_t first, count, alone, jump, height, row0, magic;
  __device__ __forceinline__ explicit Windows(const Split& s) {
    uint32_t b;
    asm volatile("mov.u32 %0, %%ctaid.x;" : "=r"(b));
    const bool upper = b < s.top;
    const uint32_t i = upper ? 0 : b - s.top;
    height = upper ? s.rows : kWinPerCol - s.rows;
    row0 = upper ? 0 : s.rows;
    magic = upper ? s.magic[0] : s.magic[1];
    alone = upper ? s.rows : s.alone;
    first = upper ? b * s.rows : i * s.alone;
    count = upper ? s.rows : s.alone + s.share;
    jump = (gridDim.x - s.top - 1 - i) * s.alone + i * s.share;
  }
  __device__ __forceinline__ bool at(uint32_t j, uint32_t& col, uint32_t& row) const {
    const uint32_t v = first + j + (j >= alone ? jump : 0);
    col = (v * magic) >> 20;
    row = v - col * height + row0;
    return row == row0 || j == alone;
  }
  __device__ __forceinline__ void at(uint32_t j, uint32_t& col, uint32_t& row, uint32_t extra) const {
    at(j, col, row);
    if (j == count) {
      col = extra & 255;
      row = extra >> 8;
    }
  }
};
template <uint32_t BYTES>
__device__ __forceinline__ void load_rows(uint32_t dst, const CUtensorMap* tm, uint32_t ch, int x, int y, uint32_t bar) {
  asm volatile("{\n.reg .pred p;\nelect.sync _|p, 0xffffffff;\n"
               "@p mbarrier.arrive.expect_tx.shared::cta.b64 _, [%5], %6;\n"
               "@p cp.async.bulk.tensor.3d.shared::cluster.global.tile.mbarrier::complete_tx::bytes [%0], [%1, {%2, %3, %4}], [%5];\n}"
               ::"r"(dst), "l"(tm), "r"(ch), "r"(x), "r"(y), "r"(bar), "n"(BYTES) : "memory");
}
__device__ __forceinline__ void prefetch_box(const CUtensorMap* tm, int x, int y) {
  asm volatile("cp.async.bulk.prefetch.tensor.3d.L2.global.tile [%0, {%1, %2, %3}];" ::"l"(tm), "r"(0), "r"(x), "r"(y) : "memory");
}
__device__ __forceinline__ void prefetch_rows(const CUtensorMap* tm, int x, int y) {
  asm volatile("{\n.reg .pred p;\nelect.sync _|p, 0xffffffff;\n"
               "@p cp.async.bulk.prefetch.tensor.3d.L2.global.tile [%0, {%1, %2, %3}];\n}" ::"l"(tm), "r"(0), "r"(x), "r"(y) : "memory");
}
__device__ __forceinline__ void store_group(const CUtensorMap* tm, uint32_t src, uint32_t ch, uint32_t x, uint32_t y) {
  asm volatile("cp.async.bulk.tensor.3d.global.shared::cta.tile.bulk_group [%0, {%2, %3, %4}], [%1];"
               ::"l"(tm), "r"(src), "r"(ch), "r"(x), "r"(y) : "memory");
}

template <int N> struct Int { static constexpr int value = N; };
struct Conv {
  uint32_t wt[9], prev[9], acc[7];
  __device__ __forceinline__ void begin(const uint32_t (&cur)[9]) {
#pragma unroll
    for (int x = 0; x < 7; x++) {
      uint32_t a = bmul2(prev[x], wt[0]);
      a = bfma2(prev[x + 1], wt[1], a);
      a = bfma2(prev[x + 2], wt[2], a);
#pragma unroll
      for (int t = 0; t < 3; t++) a = bfma2(cur[x + t], wt[3 + t], a);
      acc[x] = a;
    }
#pragma unroll
    for (int x = 0; x < 9; x++) prev[x] = cur[x];
  }
  __device__ __forceinline__ void start_column(uint32_t slot0, uint32_t bar0, uint32_t parity0, uint32_t slot1, uint32_t bar1,
                                               uint32_t parity1, uint32_t lane, uint32_t dump, bool request, const CUtensorMap* tm,
                                               uint32_t ch, int x, int y) {
    uint32_t cur[9];
    mbar_wait(bar0, parity0);
#pragma unroll
    for (int i = 0; i < 9; i++) prev[i] = lds32(slot0 + lane * 4 + i * 128);
    sts32(dump, prev[0] ^ prev[1] ^ prev[2] ^ prev[3] ^ prev[4] ^ prev[5] ^ prev[6] ^ prev[7] ^ prev[8]);
    if (request) load_rows<HALO_ROW>(slot0, tm, ch, x, y, bar0);
    mbar_wait(bar1, parity1);
#pragma unroll
    for (int i = 0; i < 9; i++) cur[i] = lds32(slot1 + lane * 4 + i * 128);
    begin(cur);
    sts32(dump, acc[0] ^ acc[3] ^ acc[6]);
    if (request) load_rows<HALO_ROW>(slot1, tm, ch, x, y + 1, bar1);
  }
  __device__ __forceinline__ void row_at(uint32_t src, uint32_t dst, uint32_t t) {
    uint32_t cur[9];
#pragma unroll
    for (int x = 0; x < 9; x++) cur[x] = lds32(src + x * 128);
#pragma unroll
    for (int x = 0; x < 7; x++) {
      uint32_t a = acc[x];
#pragma unroll
      for (int i = 0; i < 3; i++) a = bfma2(cur[x + i], wt[6 + i], a);
      sts32((dst ^ (((t + x) & 7) << 4)) + x * 128, bf16x2_to_f16x2(badd2(prev[x + 1], a)));
    }
    begin(cur);
  }
  template <int R>
  __device__ __forceinline__ void row(uint32_t src, uint32_t dst, uint32_t at) {
    uint32_t cur[9];
#pragma unroll
    for (int x = 0; x < 9; x++) cur[x] = lds32(src + x * 128);
#pragma unroll
    for (int x = 0; x < 7; x++) {
      uint32_t a = acc[x];
#pragma unroll
      for (int t = 0; t < 3; t++) a = bfma2(cur[x + t], wt[6 + t], a);
      sts32((dst ^ (((R * 7 + x) & 7) << 4)) + at + x * 128, bf16x2_to_f16x2(badd2(prev[x + 1], a)));
    }
    begin(cur);
  }
};

__global__ void __launch_bounds__(512, 1)
davit_window_attn_kernel(const __grid_constant__ CUtensorMap tm1, const __grid_constant__ CUtensorMap tm7c,
                         const __grid_constant__ CUtensorMap tm7, const __grid_constant__ CUtensorMap tmo,
                         const __grid_constant__ CUtensorMap tmw, const __grid_constant__ CUtensorMap tmwo,
                         const __nv_bfloat16* __restrict__ dw, const __nv_bfloat16* __restrict__ x_raw,
                         const __nv_bfloat16* __restrict__ wqkv_raw, const __nv_bfloat16* __restrict__ wo_raw,
                         __nv_bfloat16* __restrict__ out, Scratch* __restrict__ scr, const Split split) {
  extern __shared__ __align__(1024) uint8_t smem_raw[];
  const uint32_t sb = (uint32_t)__cvta_generic_to_shared(smem_raw);
  const uint32_t tail = sb + OFF_TAIL;
  uint32_t wt[9];
  {
    const uint32_t tid = threadIdx.x;
    const uint32_t wid = __shfl_sync(0xffffffffu, tid >> 5, 0), lane = tid & 31;
    if (wid > 12) {
      const uint32_t chunk = wid - 13, hbar = tail + T_HALO + 24 * chunk, rbar = tail + T_ROW + 16 * chunk;
      if (lane == 0) {
        mbar_init(hbar, 1);
        mbar_init(hbar + 8, 1);
        mbar_init(hbar + 16, 1);
        mbar_init(rbar, 1);
        mbar_init(rbar + 8, 1);
        if (wid == 13) mbar_init(tail + T_RAW, 1);
        if (wid == 14) mbar_init(tail + T_CLAIM, 1);
        fence_async();
      }
      __syncwarp();
      if (blockIdx.x < kUnits) {
        if (wid == 13 && lane == 0) request_unit(blockIdx.x, sb + OFF_RING, tail + T_RAW, &tmw, &tmwo);
        asm volatile("bar.sync 5, 96;" ::: "memory");
      }
      uint32_t col, row;
      Windows(split).at(0, col, row);
      const int x = (int)col * 7 - 1, y = (int)row * 7;
      const uint32_t halo = sb + OFF_HALO + chunk * 3 * HALO_ROW;
      load_rows<HALO_ROW>(halo, &tm1, chunk * 64, x, y - 1, hbar);
      load_rows<HALO_ROW>(halo + HALO_ROW, &tm1, chunk * 64, x, y, hbar + 8);
      load_rows<7 * HALO_ROW>(sb + OFF_KV + chunk * 7 * HALO_ROW, &tm7c, chunk * 64, x, y + 1, rbar);
#pragma unroll
      for (int i = 0; i < 9; i++) wt[i] = __ldg(reinterpret_cast<const uint32_t*>(dw) + i * (kCh / 2) + chunk * 32 + lane);
    } else {
      if (lane == 0 && wid < 12) {
        const uint32_t i = 2 * wid, counts = (uint32_t)((wid < 8 ? 0x4144444333CCC111ull >> (8 * wid) : 0x01444144u >> (8 * wid - 64)));
        mbar_init(tail + 8 * (i < 11 ? i : i + 9), counts & 15);
        if (wid < 11) mbar_init(tail + 8 * (i < 10 ? i + 1 : i + 10), (counts >> 4) & 15);
        fence_async();
      }
      if (wid == 12) {
        for (uint32_t line = blockIdx.x + gridDim.x * lane; line < 2304; line += gridDim.x * 32) {
          const uint8_t* p = (line < 1728) ? reinterpret_cast<const uint8_t*>(wqkv_raw) + line * 128
                                           : reinterpret_cast<const uint8_t*>(wo_raw) + (line - 1728) * 128;
          asm volatile("prefetch.global.L2 [%0];" ::"l"(p));
        }
        if (lane < 7) sts32(tail + T_ZERO + 4 * lane, 0u);
      }
    }
    __syncthreads();
    if (wid < 12) {
#pragma unroll 1
      for (uint32_t u = blockIdx.x, i = 0; u < kUnits; u += gridDim.x, i++) {
        if (i) {
          asm volatile("bar.sync 4, 384;" ::: "memory");
          if (tid == 0) request_unit(u, sb + OFF_RING, tail + T_RAW, &tmw, &tmwo);
        }
        mbar_wait(tail + T_RAW, i & 1);
        prepare_unit(u, wid, lane, sb + OFF_RING, scr);
      }
    }
  }

  if (threadIdx.x >= 384) {
    asm volatile("setmaxnreg.dec.sync.aligned.u32 %0;" ::"n"(56));
    const uint32_t tid = fresh_tid();
    const uint32_t warp = __shfl_sync(0xffffffffu, (tid >> 5) & 3, 0), lane = tid & 31;
    if (warp == 0) {
      if (lane == 0) {
        const Windows win(split);
        uint32_t spins = 0, seen;
        while (true) {
          asm volatile("ld.acquire.gpu.global.u32 %0, [%1];" : "=r"(seen) : "l"(&scr->ready) : "memory");
          if ((seen & 31) == kUnits) break;
          if (++spins > (1u << 22)) __trap();
        }
        asm volatile("fence.proxy.async.global;" ::: "memory");
        const uint8_t* w = scr->weights;
        {
          const int e0 = (int)((seen >> 10) & 511) - 128, e1 = (int)(seen >> 19) - 128;
          sts32(tail + T_SCALE, pack_f16(fmaxf(0.20823509f * pow2(9 - e0), 0x1p-24f), fmaxf(0.20823509f * pow2(9 - e1), 0x1p-24f)));
          if ((seen & 0x3E0u) || e0 < 1 || e1 < 1) sts32(tail + T_ALL, 1u);
        }
#pragma unroll
        for (uint32_t s = 0; s < 3; s++) {
          mbar_expect_tx(tail + T_FULL + 8 * s, W_PART);
          bulk_load(sb + OFF_RING + s * W_PART, w + s * W_PART, W_PART, tail + T_FULL + 8 * s);
        }
#pragma unroll 1
        for (uint32_t j = 2; j < 4 && j < win.count; j++) {
          uint32_t col, row;
          const bool fresh = win.at(j, col, row);
          if (j == 3 || fresh) prefetch_box(&tm7, 7 * col - 1, 7 * row + 1);
          if (fresh) prefetch_box(&tm7, 7 * col - 1, 7 * row - 1);
        }
        if (atomicInc(&scr->passed, gridDim.x - 1) == gridDim.x - 1) scr->ready = 0;
        const uint32_t uses = 8 * (win.count / 3 + 1);
        uint32_t s = 0, parity = 0;
#pragma unroll 1
        for (uint32_t u = 3; u < uses; u++) {
          mbar_wait(tail + T_EMPTY + 8 * s, parity);
          mbar_expect_tx(tail + T_FULL + 8 * s, W_PART);
          bulk_load(sb + OFF_RING + s * W_PART, w + (u & 7) * W_PART, W_PART, tail + T_FULL + 8 * s);
          s = (s == 2) ? 0 : s + 1;
          parity ^= (s == 0);
        }
      }
    } else {
      Conv cv;
#pragma unroll
      for (int i = 0; i < 9; i++) cv.wt[i] = wt[i];
      {
        const uint32_t chunk = warp - 1, halo = sb + OFF_HALO + chunk * 3 * HALO_ROW, hbar = tail + T_HALO + 24 * chunk;
        const Windows win(split);
        uint32_t col, row, cn, rn;
        const uint32_t staged = (win.count > 1 && !win.at(1, col, row)) ? 2 : 1;
        const bool fresh = win.at(staged, cn, rn);
        const int xn = 7 * cn - 1, yn = fresh ? 7 * rn - 1 : 7 * rn + 1;
        if (staged < win.count) load_rows<HALO_ROW>(halo + 2 * HALO_ROW, &tm1, chunk * 64, xn, yn, hbar + 16);
        cv.start_column(halo, hbar, 0, halo + HALO_ROW, hbar + 8, 0, lane, tail + T_DUMP, staged < win.count, &tm1, chunk * 64, xn, yn + 1);
        if (staged == 2)
          load_rows<7 * HALO_ROW>(sb + OFF_KV + (3 + chunk) * 7 * HALO_ROW, &tm7c, chunk * 64, 7 * col - 1, 7 * row + 1,
                                  tail + T_ROW + 16 * chunk + 8);
#pragma unroll 1
        for (uint32_t i = 0; i < staged; i++) {
          mbar_wait(tail + T_ROW + 16 * chunk + 8 * i, 0);
#pragma unroll 1
          for (uint32_t r = 0; r < 7; r++)
            cv.row_at(sb + OFF_KV + ((3 * i + chunk) * 7 + r) * HALO_ROW + lane * 4,
                      sb + OFF_X0 + chunk * X0_CHUNK + lane * 4 + (7 * i + r) * X0_ROW, 7 * r);
          __syncwarp();
          arrive_elected(tail + T_X0FULL + 8 * i);
          if (i == 0 && chunk == 0 && staged < win.count) prefetch_rows(&tm7, xn, yn + 3);
        }
      }
      const uint32_t chunk = __shfl_sync(0xffffffffu, (fresh_tid() >> 5) & 3, 0) - 1, ch = chunk * 64;
      const uint32_t halo = sb + OFF_HALO + chunk * 3 * HALO_ROW, hbar = tail + T_HALO + 24 * chunk;
      const uint32_t src = halo + lane * 4, dst = sb + OFF_X0 + chunk * X0_CHUNK + lane * 4;
      const Windows win(split);
      uint32_t count = win.count;
      uint32_t col, row;
      const uint32_t staged = (count > 1 && !win.at(1, col, row)) ? 2 : 1;
      bool fresh = win.at(staged, col, row);
      uint32_t s0 = 2, p0 = 0;
#pragma unroll 1
      for (uint32_t j = staged; j < count; j++) {
        int x = (int)col * 7 - 1, y = (int)row * 7;
        uint32_t at = 7 * j % kRows * X0_ROW;
        if (fresh) {
          const uint32_t s1 = (s0 == 2) ? 0 : s0 + 1;
          cv.start_column(halo + s0 * HALO_ROW, hbar + 8 * s0, p0, halo + s1 * HALO_ROW, hbar + 8 * s1, p0 ^ (s0 == 2), lane, tail + T_DUMP, true,
                          &tm1, ch, x, y + 2);
          p0 ^= (s0 != 0);
          s0 = (s0 == 0) ? 2 : s0 - 1;
        }
        const uint32_t slot[3] = {s0, (s0 == 2) ? 0 : s0 + 1, (s0 == 0) ? 2 : s0 - 1}, parity[3] = {p0, p0 ^ (s0 == 2), p0 ^ (s0 != 0)};
        if (chunk == 0 && j + 1 == win.count) {
          if (lane == 0) {
            const uint32_t i = atomicInc(&scr->claims, gridDim.x - 1);
            uint32_t extra = ~0u;
            if (i < split.pool) {
              const uint32_t v = kWinPerCol * (kWinPerCol - split.rows) - split.pool + i, c = (v * split.magic[1]) >> 20;
              extra = c + 256 * (v - c * (kWinPerCol - split.rows) + split.rows);
              prefetch_box(&tm7, 7 * c - 1, 7 * (extra >> 8) - 1);
              prefetch_box(&tm7, 7 * c - 1, 7 * (extra >> 8) + 1);
            }
            sts32(tail + T_EXTRA, extra);
            mbar_arrive(tail + T_CLAIM);
          }
          __syncwarp();
        }
        if (chunk == 0 && j + 2 < win.count) {
          if (win.at(j + 2, col, row)) prefetch_rows(&tm7, 7 * col - 1, 7 * row - 1);
          prefetch_rows(&tm7, 7 * col - 1, 7 * row + 1);
        }
        fresh = win.at(j + 1, col, row);
        auto step = [&](auto r) {
          constexpr int R = decltype(r)::value;
          if (R == kRows - 14) {
            mbar_wait(tail + T_X0FREE + 8 * (j & 1), ((j >> 1) & 1) ^ 1);
          }
          if (R == 4) {
            if (j + 1 == win.count) {
              mbar_wait(tail + T_CLAIM, 0);
              const uint32_t extra = __shfl_sync(0xffffffffu, lds32(tail + T_EXTRA), 0);
              count += (extra != ~0u);
              col = extra & 255;
              row = extra >> 8;
              fresh = true;
            }
            x = (int)col * 7 - 1;
            y = (int)row * 7 - (fresh ? 9 : 7);
          }
          mbar_wait(hbar + 8 * slot[R % 3], parity[R % 3] ^ ((R / 3) & 1));
          cv.template row<R>(src + slot[R % 3] * HALO_ROW, dst, at);
          if (R < 4 || j + 1 < count) load_rows<HALO_ROW>(halo + slot[R % 3] * HALO_ROW, &tm1, ch, x, y + R + 4, hbar + 8 * slot[R % 3]);
          at = (at == (kRows - 1) * X0_ROW) ? 0 : at + X0_ROW;
        };
        step(Int<0>()); step(Int<1>()); step(Int<2>()); step(Int<3>()); step(Int<4>()); step(Int<5>()); step(Int<6>());
        __syncwarp();
        arrive_elected(tail + T_X0FULL + 8 * (j % 3));
        s0 = slot[1];
        p0 = parity[1];
      }
    }
    __syncwarp();
    asm volatile("bar.sync 0, 512;" ::: "memory");
  } else {
    asm volatile("setmaxnreg.inc.sync.aligned.u32 %0;" ::"n"(152));
    const uint32_t wid = __shfl_sync(0xffffffffu, fresh_tid() >> 5, 0);
    const uint32_t wg = wid >> 2, warp = wid & 3;
    uint32_t lane;
    asm volatile("mov.u32 %0, %%laneid;" : "=r"(lane));
    const uint32_t count = Windows(split).count;
    const uint32_t q = lane & 3, mat = lane >> 3, row = lane & 7;
    const uint32_t area = sb + OFF_KV + wg * KV_SIZE;
    const uint32_t bars = tail + T_WG + 32 * wg;
    const bool full = warp < 3;
    const bool valid = full || lane < 4;
    const bool lead = lane == 0;
    uint32_t k_st, v_st, x_ld, x_mask, x_row, o_st;
    {
      const uint32_t rowg = full ? 2 * warp + (mat & 1) : 6, colg = full ? (mat >> 1) : (mat & 1);
      k_st = full ? area + A_K0 + colg * K_CHUNK + rowg * 128 + row * 16 : area + A_K0 + 768 + q * 4;
      v_st = full ? area + A_V0 + colg * V_GROUP + rowg * 128 + row * 16 : area + A_ONES + lane * 16;
      const uint32_t t = 16 * warp + row + 8 * (mat & 1);
      x_ld = (t < 49) ? sb + OFF_X0 + t * 128 + (((mat >> 1) ^ row) << 4) : tail + T_ZERO;
      x_mask = (t < 49) ? ~0u : 0u;
      x_row = t / 7;
      const uint32_t a = area + (full ? t : 48) * 64;
      o_st = a + (((full ? (mat >> 1) : 0) ^ ((a >> 7) & 3)) << 4) + (full ? 0 : 4 * q);
    }
    const uint32_t v_last = area + A_LAST + q * 32;
    const uint32_t pad = (valid ? 0u : 0xFC00u) | (full ? 0u : 0xFC000000u);
    const uint64_t k_desc = make_desc(area + A_K0, K_CHUNK, 128);
    const uint64_t v_desc = make_desc(area + A_V0, 128, V_GROUP);
    const uint64_t w_desc = make_desc(sb + OFF_RING, 128, 256);
    if (wg == 2) asm volatile("bar.arrive 8, 256;" ::: "memory");
    auto send_output = [&](uint32_t j, uint32_t parity, bool last) {
      uint32_t col, row;
      if (last) Windows(split).at(j, col, row, lds32(tail + T_EXTRA));
      else Windows(split).at(j, col, row);
      mbar_wait(bars + B_OUTRDY, parity);
#pragma unroll
      for (int i = 0; i < 6; i++) store_group(&tmo, area + i * OUT_GROUP, 32 * i, 7 * col, 7 * row);
      asm volatile("cp.async.bulk.commit_group;" ::: "memory");
    };
    uint32_t round = 0;
#pragma unroll 1
    for (; 3 * round + wg <= count; round++) {
      const uint32_t r = __shfl_sync(0xffffffffu, round, 0), j = 3 * r + wg, ph = r & 1;
      if (j == count) {
        mbar_wait(tail + T_CLAIM, 0);
        if (__shfl_sync(0xffffffffu, lds32(tail + T_EXTRA), 0) == ~0u) break;
      }
      const uint32_t m = 8 * r / 3, rot = 8 * r - 3 * m;
      const uint32_t ra = 8 * rot, rb = (rot == 2) ? 0 : ra + 8, rc = (rot == 0) ? 16 : ra - 8;
      const uint32_t pa = m & 1, pb = pa ^ (rot == 2), pc = pa ^ (rot != 0);
      uint32_t x[48], ka[24], va[24], oa[24], ob[24], rr, scales;
      uint32_t (&qa)[24] = ka;
      uint32_t sc0[14], sc1[14], pa0[12], pa1[12], ov0[14], ov1[14];
      mbar_wait(tail + T_X0FULL + 8 * wg, ph);
      asm volatile("" : "+r"(x_mask));
      const uint32_t x_at = 7 * j % kRows;
      const uint32_t x_a = x_ld + ((x_at * X0_ROW - (x_row >= kRows - x_at ? X0_CHUNK : 0)) & x_mask);
      auto load_x = [&](auto s0, auto s1) {
#pragma unroll
        for (int s = decltype(s0)::value; s < decltype(s1)::value; s++)
          ldsm4((x_a ^ (((s & 3) << 5) & x_mask)) + ((s >> 2) * X0_CHUNK & x_mask), x[4 * s], x[4 * s + 1], x[4 * s + 2], x[4 * s + 3]);
      };
      load_x(Int<0>(), Int<6>());
#pragma unroll
      for (int p = 0; p < 2; p++) {
        asm volatile("bar.sync %0, 256;" ::"r"(8 + wg) : "memory");
        mbar_wait(tail + T_FULL + ra, pa ^ p);
        if (p == 0) {
          load_x(Int<6>(), Int<12>());
          warp_arrive(tail + T_X0FREE + 8 * (j & 1), lead);
        }
        wg_fence();
        {
          const uint64_t d = desc_at(w_desc, ra * (W_PART / 8));
          issue_half<1>(ka, x, d);
          if (p == 0) wg_fence();
          issue_half<0>(ka, x, d);
        }
        wg_commit();
        if (p == 0) {
          if (!full && lead && r > 0) send_output(j - 3, ph ^ 1, false);
          __syncwarp();
        }
        if (p == 1) {
          wg_wait<1>();
          fence_regs(ov1);
          if (lead) mbar_arrive(bars + B_KVFREE);
          pack_o<0, 2>(ov1, &oa[12]);
        }
        mbar_wait(tail + T_FULL + rb, pb ^ p);
        wg_fence();
        {
          const uint64_t d = desc_at(w_desc, rb * (W_PART / 8));
          issue_half<1>(va, x, d);
          wg_commit();
          wg_wait<1>();
          if (lead) mbar_arrive(tail + T_EMPTY + ra);
          __syncwarp();
          issue_half<0>(va, x, d);
          wg_commit();
        }
        asm volatile("bar.arrive %0, 256;" ::"r"(wg == 2 ? 8 : 9 + wg) : "memory");
        if (p == 0) {
          scales = __shfl_sync(0xffffffffu, lds32(tail + T_SCALE), 0);
          const bool odd = q & 1;
          uint32_t lane_sums[2];
          lane_stats_packed(x, lane_sums);
          const uint32_t packed = quad_stats_packed(lane_sums, odd);
          float sum = h_lo(packed), squares = h_hi(packed);
          const bool fine = (squares >= 0.1875f || (pad & (odd ? 0xFC000000u : 0xFC00u))) & (squares <= 65504.f) & (sum * sum <= 96.f * squares);
          const bool exact = !__all_sync(0xffffffffu, fine);
          if (exact) {
            wg_wait<0>();
            row_stats(x, odd, sum, squares);
          }
          const float mean = sum * (1.f / 192.f);
          const float rs = 16.f * rsqrt_fast(fmaxf(fmaf(squares, 1.f / 192.f, -mean * mean), 0.f) + 1e-5f);
          if (exact) {
            const uint32_t range = __reduce_max_sync(0xffffffffu, __float_as_uint(squares * fmaxf(rs * rs, 1.f)));
            if ((range > 0x4D400000u || (range != 0u && range < 0x4585A800u)) && lead) {
              scr->redo[blockIdx.x + gridDim.x * j] = 1;
              sts32(tail + T_ANY, 1u);
            }
          }
          const float o = __shfl_xor_sync(0xffffffffu, rs, 1);
          rr = pack_f16(odd ? o : rs, odd ? rs : o);
          if (!full && lead) {
            asm volatile("cp.async.bulk.wait_group.read 0;" ::: "memory");
            mbar_arrive(bars + B_OUTFREE);
          }
          __syncwarp();
          mbar_wait(bars + B_OUTFREE, ph);
        } else {
          mbar_wait(bars + B_KVFREE, 0);
        }
        fence_regs(ka);
        store_k(ka, k_st, full, lane < 4, rr);
        mbar_wait(tail + T_FULL + rc, pc ^ p);
        wg_fence();
        {
          const uint64_t d = desc_at(w_desc, rc * (W_PART / 8));
          issue_half<2>(qa, x, d);
          wg_commit();
          wg_wait<1>();
          if (lead) mbar_arrive(tail + T_EMPTY + rb);
          __syncwarp();
          issue_half<0>(qa, x, d);
          wg_commit();
        }
        fence_regs(va);
        if (p == 0 && !full) {
          sts128_if(true, v_st, 0x3C003C00u, 0x3C003C00u, 0x3C003C00u, 0x3C003C00u);
          sts128_if(lane < 16, v_st + 512, 0x3C003C00u, 0x3C003C00u, 0x3C003C00u, 0x3C003C00u);
        }
        store_v(va, v_st, v_last, full, lane < 4, rr);
        fence_async();
        warp_arrive(bars + B_KVRDY, lead);
        wg_wait<0>();
        fence_regs(qa);
        if (lead) mbar_arrive(tail + T_EMPTY + rc);
        {
          const uint32_t rq = hmul2(rr, 0x18001800u);
#pragma unroll
          for (int i = 0; i < 24; i += 2) {
            qa[i] = hmul2_lo(qa[i], rq);
            qa[i + 1] = hmul2_hi(qa[i + 1], rq);
          }
        }
        const uint32_t cr = (p == 0) ? both<0>(scales) : both<1>(scales);
        mbar_wait(bars + B_KVRDY, p);

        wg_fence();
        issue_s(sc0, &qa[0], desc_at(k_desc, 0));
        wg_commit();
        uint32_t top0, top1, last0, last1;
        if (p == 0) {
          issue_s(sc1, &qa[12], desc_at(k_desc, A_K1));
          wg_commit();
          wg_wait<1>();
          fence_regs(sc0);
          top0 = softmax_top(sc0, lane, cr, last0);
          softmax_rows<12, 0>(sc0, top0, last0, cr, pad, v_last, pa0, ov0);
          wg_fence();
          issue_pv(ov0, pa0, desc_at(v_desc, 0));
          wg_commit();
          wg_wait<1>();
          fence_regs(sc1);
          top1 = softmax_top(sc1, lane, cr, last1);
          softmax_rows<0, 2>(sc1, top1, last1, cr, pad, v_last + 128, pa1, ov1);
        } else {
          wg_wait<0>();
          fence_regs(sc0);
          wg_fence();
          issue_s(sc1, &qa[12], desc_at(k_desc, A_K1));
          wg_commit();
          top0 = softmax_top(sc0, lane, cr, last0);
          wg_wait<0>();
          fence_regs(sc1);
          softmax_rows<12, 0>(sc0, top0, last0, cr, pad, v_last, pa0, ov0);
          mbar_wait(tail + T_FULL + ra, pa);
          wg_fence();
          issue_pv(ov0, pa0, desc_at(v_desc, 0));
          wg_commit();
          issue_out<6>(x, oa, desc_at(w_desc, ra * (W_PART / 8)));
          wg_commit();
          top1 = softmax_top(sc1, lane, cr, last1);
          wg_wait<1>();
          fence_regs(ov0);
          softmax_rows<0, 2>(sc1, top1, last1, cr, pad, v_last + 128, pa1, ov1);
        }
        wg_fence();
        issue_pv(ov1, pa1, desc_at(v_desc, A_ONES - A_V0));
        wg_commit();
        wg_wait<1>();
        if (p == 0) fence_regs(ov0);
        else if (lead) mbar_arrive(tail + T_EMPTY + ra);
        {
          uint32_t big;
          asm("{\n.reg .pred p, q;\n.reg .b32 t;\nmax.xorsign.abs.f16x2 t, %1, %2;\nabs.f16x2 t, t;\nsetp.gt.f16x2 p|q, t, %3;\n"
              "or.pred p, p, q;\nselp.u32 %0, 1, 0, p;\n}" : "=r"(big) : "r"(top0), "r"(top1), "r"(0x60006000u));
          if (__any_sync(0xffffffffu, big) && lead) {
            scr->redo[blockIdx.x + gridDim.x * j] = 1;
            sts32(tail + T_ANY, 1u);
          }
          __syncwarp();
        }
        uint32_t (&o)[24] = (p == 0) ? oa : ob;
        pack_o<12, 0>(ov0, &o[0]);
        if (p == 1) {
          mbar_wait(tail + T_FULL + rb, pb);
          wg_fence();
          issue_out<3>(x, &ob[0], desc_at(w_desc, rb * (W_PART / 8)));
          wg_commit();
          wg_wait<1>();
          fence_regs(ov1);
          if (lead) mbar_arrive(bars + B_KVFREE);
          pack_o<0, 2>(ov1, &o[12]);
        }
      }
      wg_fence();
      issue_out<3>(x, &ob[12], desc_at(w_desc, rb * (W_PART / 8) + 3 * WO_STEP));
      wg_commit();
      mbar_wait(bars + B_KVFREE, 1);
      wg_wait<0>();
      fence_regs(x);
      if (lead) mbar_arrive(tail + T_EMPTY + rb);
      asm volatile("" : "+r"(o_st));
      if (full) {
#pragma unroll
        for (int s = 0; s < 12; s++)
          stsm4((o_st ^ (((s ^ (s >> 1)) & 1) << 5)) + (s >> 1) * OUT_GROUP, f16x2_to_bf16x2(x[4 * s]), f16x2_to_bf16x2(x[4 * s + 1]),
                f16x2_to_bf16x2(x[4 * s + 2]), f16x2_to_bf16x2(x[4 * s + 3]));
        fence_async();
        warp_arrive(bars + B_OUTRDY, lead);
      } else {
#pragma unroll
        for (int i = 0; i < 24; i++)
          sts32_if(lane < 4, (o_st ^ (((i ^ ((i >> 1) & 2)) & 3) << 4)) + (i >> 2) * OUT_GROUP, f16x2_to_bf16x2(x[2 * i]));
        fence_async();
        warp_arrive(bars + B_OUTRDY, lead);
      }
    }
    if (!full && lead && round > 0) send_output(3 * round + wg - 3, (round & 1) ^ 1, true);
    __syncwarp();
    if (3 * round <= count) {
#pragma unroll 1
      for (uint32_t i = 0; i < 5; i++) {
        if (i % 3 == 0) {
          asm volatile("bar.sync %0, 256;" ::"r"(8 + wg) : "memory");
          asm volatile("bar.arrive %0, 256;" ::"r"(wg == 2 ? 8 : 9 + wg) : "memory");
        }
        const uint32_t u = 8 * round + i;
        mbar_wait(tail + T_FULL + 8 * (u % 3), (u / 3) & 1);
        if (lead) mbar_arrive(tail + T_EMPTY + 8 * (u % 3));
        __syncwarp();
      }
    }
    if (!full && lead) asm volatile("cp.async.bulk.wait_group.read 0;" ::: "memory");
    __syncwarp();
    asm volatile("bar.sync 0, 512;" ::: "memory");
    const uint32_t redo_all = lds32(tail + T_ALL);
    if (redo_all | lds32(tail + T_ANY)) {
      const uint32_t t = fresh_tid(), c = t >> 7;
      if ((t & 127) == 96) asm volatile("cp.async.bulk.wait_group 0;\nfence.proxy.async.global;" ::: "memory");
      __syncwarp();
      const Windows win(split);
      const uint32_t extra = lds32(tail + T_EXTRA);
      for (uint32_t j = c; j < win.count + (extra != ~0u); j += 3) {
        uint8_t* flag = &scr->redo[blockIdx.x + gridDim.x * j];
        if (!redo_all && !*reinterpret_cast<volatile uint8_t*>(flag)) continue;
        uint32_t col, row;
        win.at(j, col, row, extra);
        redo_window(7 * col, 7 * row, t & 127, 1 + c, smem_raw + c * REDO_BYTES, x_raw, dw, wqkv_raw, wo_raw, out);
        if ((t & 127) == 0) *flag = 0;
      }
    }
  }
}

typedef CUresult (*EncodeTiledFn)(CUtensorMap*, CUtensorMapDataType, cuuint32_t, void*, const cuuint64_t*, const cuuint64_t*,
                                  const cuuint32_t*, const cuuint32_t*, CUtensorMapInterleave, CUtensorMapSwizzle,
                                  CUtensorMapL2promotion, CUtensorMapFloatOOBfill);

}

extern "C" void kernel_launch(void* const* d_in, const int* in_sizes, int n_in, void* d_out, int out_size) {
  (void)in_sizes; (void)n_in; (void)out_size;
  static EncodeTiledFn encode = nullptr;
  static int grid = 0;
  static void* scratch = nullptr;
  if (!encode) {
    void* fn = nullptr;
    cudaDriverEntryPointQueryResult st;
    cudaGetDriverEntryPoint("cuTensorMapEncodeTiled", &fn, cudaEnableDefault, &st);
    encode = (EncodeTiledFn)fn;
    cudaFuncSetAttribute(davit_window_attn_kernel, cudaFuncAttributeMaxDynamicSharedMemorySize, SMEM_BYTES);
    cudaGetSymbolAddress(&scratch, g_scratch);
    int dev = 0;
    cudaGetDevice(&dev);
    cudaDeviceGetAttribute(&grid, cudaDevAttrMultiProcessorCount, dev);
    if (grid > 1024) grid = 1024;
  }
  Split split = {};
  {
    const uint32_t g = grid, n = kNumWin / g;
    if (g > kWinPerCol && g <= 2 * kWinPerCol && kWinPerCol - n <= n) {
      const uint32_t below = (kWinPerCol - n) * kWinPerCol;
      split.top = kWinPerCol;
      split.rows = (below > (n + 1) * (g - kWinPerCol) && n + 1 < kWinPerCol) ? n + 1 : n;
      split.alone = kWinPerCol - split.rows;
    }
    const uint32_t others = g - split.top, rest = kNumWin - split.top * split.rows - others * split.alone;
    split.share = rest / others;
    split.pool = rest % others;
    split.magic[0] = split.rows ? ((1u << 20) + split.rows - 1) / split.rows : 0;
    split.magic[1] = ((1u << 20) + kWinPerCol - split.rows - 1) / (kWinPerCol - split.rows);
  }
  auto image_map = [&](void* base, cuuint32_t c, cuuint32_t w, cuuint32_t h, CUtensorMapSwizzle swizzle) {
    CUtensorMap tm;
    const cuuint64_t dims[3] = {(cuuint64_t)kCh, (cuuint64_t)kImg, (cuuint64_t)kImg};
    const cuuint64_t strides[2] = {(cuuint64_t)kCh * 2, (cuuint64_t)kCh * 2 * kImg};
    const cuuint32_t box[3] = {c, w, h};
    const cuuint32_t estr[3] = {1, 1, 1};
    encode(&tm, CU_TENSOR_MAP_DATA_TYPE_BFLOAT16, 3, base, dims, strides, box, estr, CU_TENSOR_MAP_INTERLEAVE_NONE, swizzle,
           CU_TENSOR_MAP_L2_PROMOTION_L2_128B, CU_TENSOR_MAP_FLOAT_OOB_FILL_NONE);
    return tm;
  };
  auto weight_map = [&](void* base, cuuint64_t cols, cuuint32_t rows) {
    CUtensorMap tm;
    const cuuint64_t dims[2] = {cols, (cuuint64_t)kCh};
    const cuuint64_t strides[1] = {cols * 2};
    const cuuint32_t box[2] = {32, rows};
    const cuuint32_t estr[2] = {1, 1};
    encode(&tm, CU_TENSOR_MAP_DATA_TYPE_BFLOAT16, 2, base, dims, strides, box, estr, CU_TENSOR_MAP_INTERLEAVE_NONE,
           CU_TENSOR_MAP_SWIZZLE_64B, CU_TENSOR_MAP_L2_PROMOTION_L2_128B, CU_TENSOR_MAP_FLOAT_OOB_FILL_NONE);
    return tm;
  };
  davit_window_attn_kernel<<<grid, 512, SMEM_BYTES, cudaStreamPerThread>>>(
      image_map(d_in[0], 64, 9, 1, CU_TENSOR_MAP_SWIZZLE_NONE), image_map(d_in[0], 64, 9, 7, CU_TENSOR_MAP_SWIZZLE_NONE),
      image_map(d_in[0], 192, 9, 7, CU_TENSOR_MAP_SWIZZLE_NONE), image_map(d_out, 32, 7, 7, CU_TENSOR_MAP_SWIZZLE_64B),
      weight_map(d_in[2], 576, 192), weight_map(d_in[3], 192, 32),
      (const __nv_bfloat16*)d_in[1], (const __nv_bfloat16*)d_in[0], (const __nv_bfloat16*)d_in[2], (const __nv_bfloat16*)d_in[3],
      (__nv_bfloat16*)d_out, (Scratch*)scratch, split);
}
```

```cpp
#include <cuda.h>
#include <cuda_bf16.h>
#include <cuda_runtime.h>
#include <stdint.h>

namespace {

constexpr int kImg = 511;
constexpr int kCh = 192;
constexpr int kWinPerCol = 73;
constexpr int kNumWin = 73 * 73;

constexpr uint32_t W_PART = 36864;
constexpr uint32_t W_STEP = 3072;
constexpr uint32_t WO_STEP = 6144;
constexpr uint32_t W_BYTES = 8 * W_PART;

struct Scratch {
  uint8_t weights[W_BYTES];
  uint32_t ready;
  uint32_t passed;
  uint32_t claims;
  uint8_t redo[2 * kNumWin];
};
__device__ __align__(128) Scratch g_scratch;

constexpr uint32_t OFF_RING = 0;
constexpr uint32_t OFF_X0 = 3 * W_PART;
constexpr uint32_t kRows = 19;
constexpr uint32_t X0_ROW = 7 * 128;
constexpr uint32_t X0_CHUNK = kRows * X0_ROW;
constexpr uint32_t OFF_HALO = OFF_X0 + 3 * X0_CHUNK;
constexpr uint32_t HALO_ROW = 9 * 128;
constexpr uint32_t OFF_KV = OFF_HALO + 9 * HALO_ROW;
constexpr uint32_t K_CHUNK = 784;
constexpr uint32_t V_GROUP = 768;
constexpr uint32_t A_K0 = 0;
constexpr uint32_t A_V0 = 6 * K_CHUNK;
constexpr uint32_t A_ONES = A_V0 + 6 * V_GROUP;
constexpr uint32_t A_V1 = A_ONES + V_GROUP;
constexpr uint32_t A_K1 = A_V1 + 6 * V_GROUP;
constexpr uint32_t A_LAST = A_K1 + 6 * K_CHUNK;
constexpr uint32_t KV_SIZE = 19840;
constexpr uint32_t OUT_GROUP = 3328;
static_assert(A_LAST + 256 <= KV_SIZE && 5 * OUT_GROUP + 3136 <= KV_SIZE && KV_SIZE % 128 == 0 && 42 * HALO_ROW <= 3 * KV_SIZE &&
              21 * HALO_ROW >= KV_SIZE, "consumer area");
constexpr uint32_t OFF_TAIL = OFF_KV + 3 * KV_SIZE;
constexpr uint32_t SMEM_BYTES = OFF_TAIL + 360;
static_assert(SMEM_BYTES <= 232448, "shared memory");

constexpr uint32_t T_FULL = 0;
constexpr uint32_t T_EMPTY = 24;
constexpr uint32_t T_X0FULL = 48;
constexpr uint32_t T_X0FREE = 72;
constexpr uint32_t T_HALO = 88;
constexpr uint32_t T_WG = 160;
constexpr uint32_t B_KVRDY = 0;
constexpr uint32_t B_KVFREE = 8;
constexpr uint32_t B_OUTRDY = 16;
constexpr uint32_t B_OUTFREE = 24;
constexpr uint32_t T_RAW = 256;
constexpr uint32_t T_CLAIM = 264;
constexpr uint32_t T_ZERO = 272;
constexpr uint32_t T_SCALE = 288;
constexpr uint32_t T_ALL = 292;
constexpr uint32_t T_ANY = 296;
constexpr uint32_t T_DUMP = 300;
constexpr uint32_t T_ROW = 304;
constexpr uint32_t T_EXTRA = 352;

__device__ __forceinline__ void hmma_n96_first(uint32_t (&d)[24], uint32_t a0, uint32_t a1, uint32_t a2, uint32_t a3, uint64_t desc) {
  asm volatile("wgmma.mma_async.sync.aligned.m64n96k16.f16.f16.f16 "
               "{%0, %1, %2, %3, %4, %5, %6, %7, %8, %9, %10, %11, %12, %13, %14, %15, "
               "%16, %17, %18, %19, %20, %21, %22, %23}, "
               "{%24, %25, %26, %27}, %28, 0, 1, 1, 0;\n"
               : "=r"(d[0]), "=r"(d[1]), "=r"(d[2]), "=r"(d[3]), "=r"(d[4]), "=r"(d[5]), "=r"(d[6]), "=r"(d[7]),
                 "=r"(d[8]), "=r"(d[9]), "=r"(d[10]), "=r"(d[11]), "=r"(d[12]), "=r"(d[13]), "=r"(d[14]), "=r"(d[15]),
                 "=r"(d[16]), "=r"(d[17]), "=r"(d[18]), "=r"(d[19]), "=r"(d[20]), "=r"(d[21]), "=r"(d[22]), "=r"(d[23])
               : "r"(a0), "r"(a1), "r"(a2), "r"(a3), "l"(desc));
}
__device__ __forceinline__ void hmma_n96(uint32_t (&d)[24], uint32_t a0, uint32_t a1, uint32_t a2, uint32_t a3, uint64_t desc) {
  asm volatile("wgmma.mma_async.sync.aligned.m64n96k16.f16.f16.f16 "
               "{%0, %1, %2, %3, %4, %5, %6, %7, %8, %9, %10, %11, %12, %13, %14, %15, "
               "%16, %17, %18, %19, %20, %21, %22, %23}, "
               "{%24, %25, %26, %27}, %28, 1, 1, 1, 0;\n"
               : "+r"(d[0]), "+r"(d[1]), "+r"(d[2]), "+r"(d[3]), "+r"(d[4]), "+r"(d[5]), "+r"(d[6]), "+r"(d[7]),
                 "+r"(d[8]), "+r"(d[9]), "+r"(d[10]), "+r"(d[11]), "+r"(d[12]), "+r"(d[13]), "+r"(d[14]), "+r"(d[15]),
                 "+r"(d[16]), "+r"(d[17]), "+r"(d[18]), "+r"(d[19]), "+r"(d[20]), "+r"(d[21]), "+r"(d[22]), "+r"(d[23])
               : "r"(a0), "r"(a1), "r"(a2), "r"(a3), "l"(desc));
}
__device__ __forceinline__ void hmma_n96_over(uint32_t (&d)[24], uint32_t a0, uint32_t a1, uint32_t a2, uint32_t a3, uint64_t desc) {
  asm volatile("wgmma.mma_async.sync.aligned.m64n96k16.f16.f16.f16 "
               "{%0, %1, %2, %3, %4, %5, %6, %7, %8, %9, %10, %11, %12, %13, %14, %15, "
               "%16, %17, %18, %19, %20, %21, %22, %23}, "
               "{%24, %25, %26, %27}, %28, 0, 1, 1, 0;\n"
               : "+r"(d[0]), "+r"(d[1]), "+r"(d[2]), "+r"(d[3]), "+r"(d[4]), "+r"(d[5]), "+r"(d[6]), "+r"(d[7]),
                 "+r"(d[8]), "+r"(d[9]), "+r"(d[10]), "+r"(d[11]), "+r"(d[12]), "+r"(d[13]), "+r"(d[14]), "+r"(d[15]),
                 "+r"(d[16]), "+r"(d[17]), "+r"(d[18]), "+r"(d[19]), "+r"(d[20]), "+r"(d[21]), "+r"(d[22]), "+r"(d[23])
               : "r"(a0), "r"(a1), "r"(a2), "r"(a3), "l"(desc));
}
__device__ __forceinline__ void hmma_n56_first(uint32_t (&d)[14], uint32_t a0, uint32_t a1, uint32_t a2, uint32_t a3, uint64_t desc) {
  asm volatile("wgmma.mma_async.sync.aligned.m64n56k16.f16.f16.f16 "
               "{%0, %1, %2, %3, %4, %5, %6, %7, %8, %9, %10, %11, %12, %13}, "
               "{%14, %15, %16, %17}, %18, 0, 1, 1, 0;\n"
               : "=r"(d[0]), "=r"(d[1]), "=r"(d[2]), "=r"(d[3]), "=r"(d[4]), "=r"(d[5]), "=r"(d[6]), "=r"(d[7]),
                 "=r"(d[8]), "=r"(d[9]), "=r"(d[10]), "=r"(d[11]), "=r"(d[12]), "=r"(d[13])
               : "r"(a0), "r"(a1), "r"(a2), "r"(a3), "l"(desc));
}
__device__ __forceinline__ void hmma_n56(uint32_t (&d)[14], uint32_t a0, uint32_t a1, uint32_t a2, uint32_t a3, uint64_t desc) {
  asm volatile("wgmma.mma_async.sync.aligned.m64n56k16.f16.f16.f16 "
               "{%0, %1, %2, %3, %4, %5, %6, %7, %8, %9, %10, %11, %12, %13}, "
               "{%14, %15, %16, %17}, %18, 1, 1, 1, 0;\n"
               : "+r"(d[0]), "+r"(d[1]), "+r"(d[2]), "+r"(d[3]), "+r"(d[4]), "+r"(d[5]), "+r"(d[6]), "+r"(d[7]),
                 "+r"(d[8]), "+r"(d[9]), "+r"(d[10]), "+r"(d[11]), "+r"(d[12]), "+r"(d[13])
               : "r"(a0), "r"(a1), "r"(a2), "r"(a3), "l"(desc));
}
__device__ __forceinline__ void hmma_n192(uint32_t (&d)[48], uint32_t a0, uint32_t a1, uint32_t a2, uint32_t a3, uint64_t desc) {
  asm volatile("wgmma.mma_async.sync.aligned.m64n192k16.f16.f16.f16 "
               "{%0, %1, %2, %3, %4, %5, %6, %7, %8, %9, %10, %11, %12, %13, %14, %15, "
               "%16, %17, %18, %19, %20, %21, %22, %23, %24, %25, %26, %27, %28, %29, %30, %31, "
               "%32, %33, %34, %35, %36, %37, %38, %39, %40, %41, %42, %43, %44, %45, %46, %47}, "
               "{%48, %49, %50, %51}, %52, 1, 1, 1, 0;\n"
               : "+r"(d[0]), "+r"(d[1]), "+r"(d[2]), "+r"(d[3]), "+r"(d[4]), "+r"(d[5]), "+r"(d[6]), "+r"(d[7]),
                 "+r"(d[8]), "+r"(d[9]), "+r"(d[10]), "+r"(d[11]), "+r"(d[12]), "+r"(d[13]), "+r"(d[14]), "+r"(d[15]),
                 "+r"(d[16]), "+r"(d[17]), "+r"(d[18]), "+r"(d[19]), "+r"(d[20]), "+r"(d[21]), "+r"(d[22]), "+r"(d[23]),
                 "+r"(d[24]), "+r"(d[25]), "+r"(d[26]), "+r"(d[27]), "+r"(d[28]), "+r"(d[29]), "+r"(d[30]), "+r"(d[31]),
                 "+r"(d[32]), "+r"(d[33]), "+r"(d[34]), "+r"(d[35]), "+r"(d[36]), "+r"(d[37]), "+r"(d[38]), "+r"(d[39]),
                 "+r"(d[40]), "+r"(d[41]), "+r"(d[42]), "+r"(d[43]), "+r"(d[44]), "+r"(d[45]), "+r"(d[46]), "+r"(d[47])
               : "r"(a0), "r"(a1), "r"(a2), "r"(a3), "l"(desc));
}

__device__ __forceinline__ void wg_fence() { asm volatile("wgmma.fence.sync.aligned;\n" ::: "memory"); }
__device__ __forceinline__ void wg_commit() { asm volatile("wgmma.commit_group.sync.aligned;\n" ::: "memory"); }
template <int N> __device__ __forceinline__ void wg_wait() { asm volatile("wgmma.wait_group.sync.aligned %0;\n" ::"n"(N) : "memory"); }
__device__ __forceinline__ uint64_t make_desc(uint32_t addr, uint32_t lbo, uint32_t sbo) {
  return (uint64_t)((addr & 0x3FFFF) >> 4) | ((uint64_t)(lbo >> 4) << 16) | ((uint64_t)(sbo >> 4) << 32);
}
__device__ __forceinline__ uint64_t desc_add(uint64_t d, uint32_t bytes) { return d + (bytes >> 4); }
__device__ __forceinline__ uint64_t desc_at(uint64_t d, uint32_t bytes) {
  uint64_t r;
  asm volatile("mov.b64 %0, %1;" : "=l"(r) : "l"(d));
  return desc_add(r, bytes);
}

__device__ __forceinline__ void mbar_init(uint32_t bar, uint32_t count) {
  asm volatile("mbarrier.init.shared::cta.b64 [%0], %1;" ::"r"(bar), "r"(count) : "memory");
}
__device__ __forceinline__ void mbar_expect_tx(uint32_t bar, uint32_t bytes) {
  asm volatile("mbarrier.arrive.expect_tx.shared::cta.b64 _, [%0], %1;" ::"r"(bar), "r"(bytes) : "memory");
}
__device__ __forceinline__ void mbar_wait(uint32_t bar, uint32_t parity) {
  asm volatile("{\n.reg .pred p;\n.reg .u32 c;\n"
               "mbarrier.try_wait.parity.shared::cta.b64 p, [%0], %1;\n"
               "@p bra DONE;\n"
               "mov.u32 c, 0;\n"
               "SPIN:\n"
               "mbarrier.try_wait.parity.shared::cta.b64 p, [%0], %1, 4000;\n"
               "@p bra DONE;\n"
               "add.u32 c, c, 1;\n"
               "setp.lt.u32 p, c, 1048576;\n"
               "@!p trap;\n"
               "bra SPIN;\n"
               "DONE:\n}" ::"r"(bar), "r"(parity) : "memory");
}
__device__ __forceinline__ void bar_sync(uint32_t id) { asm volatile("bar.sync %0, 128;" ::"r"(id) : "memory"); }
__device__ __forceinline__ void mbar_arrive(uint32_t bar) { asm volatile("mbarrier.arrive.shared::cta.b64 _, [%0];" ::"r"(bar) : "memory"); }
__device__ __forceinline__ void warp_arrive(uint32_t bar, bool first) {
  __syncwarp();
  if (first) mbar_arrive(bar);
}
__device__ __forceinline__ void arrive_elected(uint32_t bar) {
  asm volatile("{\n.reg .pred p;\nelect.sync _|p, 0xffffffff;\n@p mbarrier.arrive.shared::cta.b64 _, [%0];\n}" ::"r"(bar) : "memory");
}
__device__ __forceinline__ void fence_async() { asm volatile("fence.proxy.async.shared::cta;" ::: "memory"); }
__device__ __forceinline__ uint32_t lds32(uint32_t a) {
  uint32_t v;
  asm volatile("ld.shared.b32 %0, [%1];" : "=r"(v) : "r"(a) : "memory");
  return v;
}
__device__ __forceinline__ void lds64(uint32_t a, uint32_t& v0, uint32_t& v1) {
  asm volatile("ld.shared.v2.b32 {%0, %1}, [%2];" : "=r"(v0), "=r"(v1) : "r"(a) : "memory");
}
__device__ __forceinline__ void sts32(uint32_t a, uint32_t v) { asm volatile("st.shared.b32 [%0], %1;" ::"r"(a), "r"(v) : "memory"); }
__device__ __forceinline__ void sts64(uint32_t a, uint32_t v0, uint32_t v1) {
  asm volatile("st.shared.v2.b32 [%0], {%1, %2};" ::"r"(a), "r"(v0), "r"(v1) : "memory");
}
__device__ __forceinline__ void sts32_if(bool on, uint32_t a, uint32_t v) {
  asm volatile("{\n.reg .pred p;\nsetp.ne.u32 p, %2, 0;\n@p st.shared.b32 [%0], %1;\n}" ::"r"(a), "r"(v), "r"((uint32_t)on) : "memory");
}
__device__ __forceinline__ void ldsm4(uint32_t a, uint32_t& r0, uint32_t& r1, uint32_t& r2, uint32_t& r3) {
  asm volatile("ldmatrix.sync.aligned.m8n8.x4.shared.b16 {%0, %1, %2, %3}, [%4];" : "=r"(r0), "=r"(r1), "=r"(r2), "=r"(r3) : "r"(a) : "memory");
}
__device__ __forceinline__ void stsm4(uint32_t a, uint32_t r0, uint32_t r1, uint32_t r2, uint32_t r3) {
  asm volatile("stmatrix.sync.aligned.m8n8.x4.shared.b16 [%0], {%1, %2, %3, %4};" ::"r"(a), "r"(r0), "r"(r1), "r"(r2), "r"(r3) : "memory");
}
__device__ __forceinline__ void stsm4_t(uint32_t a, uint32_t r0, uint32_t r1, uint32_t r2, uint32_t r3) {
  asm volatile("stmatrix.sync.aligned.m8n8.x4.trans.shared.b16 [%0], {%1, %2, %3, %4};" ::"r"(a), "r"(r0), "r"(r1), "r"(r2), "r"(r3) : "memory");
}
__device__ __forceinline__ uint32_t pack_bf16(float lo, float hi) {
  uint32_t r;
  asm("cvt.rn.bf16x2.f32 %0, %1, %2;" : "=r"(r) : "f"(hi), "f"(lo));
  return r;
}
__device__ __forceinline__ uint32_t pack_f16(float lo, float hi) {
  uint32_t r;
  asm("cvt.rn.f16x2.f32 %0, %1, %2;" : "=r"(r) : "f"(hi), "f"(lo));
  return r;
}
__device__ __forceinline__ float bf_lo(uint32_t v) { return __uint_as_float(v << 16); }
__device__ __forceinline__ float bf_hi(uint32_t v) { return __uint_as_float(v & 0xffff0000u); }
__device__ __forceinline__ float h_lo(uint32_t v) {
  float r;
  asm("{\n.reg .b16 l, h;\nmov.b32 {l, h}, %1;\ncvt.f32.f16 %0, l;\n}" : "=f"(r) : "r"(v));
  return r;
}
__device__ __forceinline__ float h_hi(uint32_t v) {
  float r;
  asm("{\n.reg .b16 l, h;\nmov.b32 {l, h}, %1;\ncvt.f32.f16 %0, h;\n}" : "=f"(r) : "r"(v));
  return r;
}
__device__ __forceinline__ uint32_t bf16x2_to_f16x2(uint32_t v) { return pack_f16(bf_lo(v), bf_hi(v)); }
__device__ __forceinline__ uint32_t f16x2_to_bf16x2(uint32_t v) { return pack_bf16(h_lo(v), h_hi(v)); }
__device__ __forceinline__ uint32_t bmul2(uint32_t a, uint32_t b) {
  uint32_t r;
  asm("mul.rn.bf16x2 %0, %1, %2;" : "=r"(r) : "r"(a), "r"(b));
  return r;
}
__device__ __forceinline__ uint32_t badd2(uint32_t a, uint32_t b) {
  uint32_t r;
  asm("add.rn.bf16x2 %0, %1, %2;" : "=r"(r) : "r"(a), "r"(b));
  return r;
}
__device__ __forceinline__ uint32_t bfma2(uint32_t a, uint32_t b, uint32_t c) {
  uint32_t r;
  asm("fma.rn.bf16x2 %0, %1, %2, %3;" : "=r"(r) : "r"(a), "r"(b), "r"(c));
  return r;
}
__device__ __forceinline__ uint32_t hadd2(uint32_t a, uint32_t b) {
  uint32_t d;
  asm("add.rn.f16x2 %0, %1, %2;" : "=r"(d) : "r"(a), "r"(b));
  return d;
}
__device__ __forceinline__ uint32_t hmax2(uint32_t a, uint32_t b) {
  uint32_t d;
  asm("max.f16x2 %0, %1, %2;" : "=r"(d) : "r"(a), "r"(b));
  return d;
}
__device__ __forceinline__ uint32_t hmul2(uint32_t a, uint32_t b) {
  uint32_t d;
  asm("mul.rn.f16x2 %0, %1, %2;" : "=r"(d) : "r"(a), "r"(b));
  return d;
}
__device__ __forceinline__ uint32_t hmul2_lo(uint32_t a, uint32_t r) {
  uint32_t d;
  asm("{\n.reg .b16 l, h;\n.reg .b32 t;\nmov.b32 {l, h}, %2;\nmov.b32 t, {l, l};\nmul.rn.f16x2 %0, %1, t;\n}" : "=r"(d) : "r"(a), "r"(r));
  return d;
}
__device__ __forceinline__ uint32_t hmul2_hi(uint32_t a, uint32_t r) {
  uint32_t d;
  asm("{\n.reg .b16 l, h;\n.reg .b32 t;\nmov.b32 {l, h}, %2;\nmov.b32 t, {h, h};\nmul.rn.f16x2 %0, %1, t;\n}" : "=r"(d) : "r"(a), "r"(r));
  return d;
}
__device__ __forceinline__ float rcp(float x) {
  float r;
  asm("rcp.approx.ftz.f32 %0, %1;" : "=f"(r) : "f"(x));
  return r;
}
__device__ __forceinline__ float rsqrt_fast(float x) {
  float r;
  asm("rsqrt.approx.ftz.f32 %0, %1;" : "=f"(r) : "f"(x));
  return r;
}
template <int N> __device__ __forceinline__ void fence_regs(uint32_t (&d)[N]) {
#pragma unroll
  for (int i = 0; i < N; i++) asm volatile("" : "+r"(d[i])::"memory");
}

__device__ __forceinline__ void row_stats(const uint32_t (&x)[48], bool odd, float& sum, float& squares) {
  float s0 = 0.f, q0 = 0.f, s1 = 0.f, q1 = 0.f;
#pragma unroll
  for (int i = 0; i < 48; i++) {
    const float lo = h_lo(x[i]), hi = h_hi(x[i]);
    if (i & 1) {
      s1 += lo; q1 = fmaf(lo, lo, q1);
      s1 += hi; q1 = fmaf(hi, hi, q1);
    } else {
      s0 += lo; q0 = fmaf(lo, lo, q0);
      s0 += hi; q0 = fmaf(hi, hi, q0);
    }
  }
  sum = (odd ? s1 : s0) + __shfl_xor_sync(0xffffffffu, odd ? s0 : s1, 1);
  squares = (odd ? q1 : q0) + __shfl_xor_sync(0xffffffffu, odd ? q0 : q1, 1);
  sum += __shfl_xor_sync(0xffffffffu, sum, 2);
  squares += __shfl_xor_sync(0xffffffffu, squares, 2);
}
__device__ __forceinline__ void lane_stats_packed(const uint32_t (&x)[48], uint32_t (&t)[2]) {
  uint32_t s[4] = {x[0], x[1], x[2], x[3]}, q[4];
#pragma unroll
  for (int r = 0; r < 4; r++) q[r] = hmul2(x[r], x[r]);
#pragma unroll
  for (int i = 4; i < 48; i++) {
    asm("add.rn.f16x2 %0, %0, %1;" : "+r"(s[i & 3]) : "r"(x[i]));
    asm("fma.rn.f16x2 %0, %1, %1, %0;" : "+r"(q[i & 3]) : "r"(x[i]));
  }
#pragma unroll
  for (int r = 0; r < 2; r++) {
    const uint32_t a = hadd2(s[r], s[r + 2]), b = hadd2(q[r], q[r + 2]);
    t[r] = hadd2(__byte_perm(a, b, 0x5410), __byte_perm(a, b, 0x7632));
  }
}
__device__ __forceinline__ uint32_t quad_stats_packed(const uint32_t (&t)[2], bool odd) {
  const uint32_t u = hadd2(__shfl_xor_sync(0xffffffffu, odd ? t[0] : t[1], 1), odd ? t[1] : t[0]);
  return hadd2(u, __shfl_xor_sync(0xffffffffu, u, 2));
}

__device__ __forceinline__ void store_k(const uint32_t (&k)[24], uint32_t k_st, bool full, bool first_row, uint32_t r) {
  if (full) {
#pragma unroll
    for (int j = 0; j < 12; j += 2)
      stsm4(k_st + (j / 6) * A_K1 + (j % 6) * K_CHUNK, hmul2_lo(k[2 * j], r), hmul2_hi(k[2 * j + 1], r), hmul2_lo(k[2 * j + 2], r),
            hmul2_hi(k[2 * j + 3], r));
  } else {
#pragma unroll
    for (int j = 0; j < 12; j++) sts32_if(first_row, k_st + (j / 6) * A_K1 + (j % 6) * K_CHUNK, hmul2_lo(k[2 * j], r));
    __syncwarp();
  }
}
template <int HALF> __device__ __forceinline__ uint32_t both(uint32_t v) {
  uint32_t d;
  if (HALF == 0) asm("{\n.reg .b16 l, h;\nmov.b32 {l, h}, %1;\nmov.b32 %0, {l, l};\n}" : "=r"(d) : "r"(v));
  else asm("{\n.reg .b16 l, h;\nmov.b32 {l, h}, %1;\nmov.b32 %0, {h, h};\n}" : "=r"(d) : "r"(v));
  return d;
}
__device__ __forceinline__ uint32_t exp2_scaled(uint32_t s, uint32_t c, uint32_t off) {
  uint32_t d;
  asm("{\n.reg .b32 t;\nfma.rn.f16x2 t, %1, %2, %3;\nex2.approx.f16x2 %0, t;\n}" : "=r"(d) : "r"(s), "r"(c), "r"(off));
  return d;
}
__device__ __forceinline__ uint32_t softmax_top(const uint32_t (&s)[14], uint32_t lane, uint32_t c, uint32_t& last) {
  last = __shfl_sync(0xffffffffu, __byte_perm(s[12], s[13], 0x5410), lane & 28);
  const uint32_t a = hmax2(hmax2(hmax2(s[0], s[2]), s[4]), hmax2(hmax2(s[6], s[8]), s[10]));
  const uint32_t b = hmax2(hmax2(hmax2(s[1], s[3]), s[5]), hmax2(hmax2(s[7], s[9]), s[11]));
  uint32_t m = hmax2(__byte_perm(a, b, 0x5410), __byte_perm(a, b, 0x7632));
  m = hmax2(m, __shfl_xor_sync(0xffffffffu, m, 1));
  m = hmax2(hmax2(m, last), __shfl_xor_sync(0xffffffffu, m, 2));
  return hmul2(m, c);
}
__device__ __forceinline__ void lds128(uint32_t a, uint32_t* v) {
  asm volatile("ld.shared.v4.b32 {%0, %1, %2, %3}, [%4];" : "=r"(v[0]), "=r"(v[1]), "=r"(v[2]), "=r"(v[3]) : "r"(a) : "memory");
}
template <int SUM, int VAL>
__device__ __forceinline__ void softmax_rows(const uint32_t (&s)[14], uint32_t top, uint32_t last, uint32_t c, uint32_t pad,
                                             uint32_t v_last, uint32_t (&pa)[12], uint32_t (&ov)[14]) {
  uint32_t off, v[6];
  lds128(v_last, v);
  lds64(v_last + 16, v[4], v[5]);
  asm("sub.rn.f16x2 %0, %1, %2;" : "=r"(off) : "r"(pad), "r"(top));
#pragma unroll
  for (int j = 0; j < 6; j++) {
    pa[2 * j] = exp2_scaled(s[2 * j], both<0>(c), both<0>(off));
    pa[2 * j + 1] = exp2_scaled(s[2 * j + 1], both<1>(c), both<1>(off));
  }
  const uint32_t p = exp2_scaled(last, c, off);
#pragma unroll
  for (int j = 0; j < 6; j++) {
    ov[VAL + 2 * j] = hmul2_lo(v[j], p);
    ov[VAL + 2 * j + 1] = hmul2_hi(v[j], p);
  }
  ov[SUM] = __byte_perm(p, p, 0x1010);
  ov[SUM + 1] = __byte_perm(p, p, 0x3232);
}
__device__ __forceinline__ void issue_pv(uint32_t (&ov)[14], const uint32_t (&pa)[12], uint64_t v_desc) {
#pragma unroll
  for (int k = 0; k < 3; k++) hmma_n56(ov, pa[4 * k], pa[4 * k + 1], pa[4 * k + 2], pa[4 * k + 3], desc_add(v_desc, k * 256));
}
__device__ __forceinline__ void sts128_if(bool on, uint32_t a, uint32_t v0, uint32_t v1, uint32_t v2, uint32_t v3) {
  asm volatile("{\n.reg .pred p;\nsetp.ne.u32 p, %5, 0;\n@p st.shared.v4.b32 [%0], {%1, %2, %3, %4};\n}"
               ::"r"(a), "r"(v0), "r"(v1), "r"(v2), "r"(v3), "r"((uint32_t)on) : "memory");
}
__device__ __forceinline__ void store_v(const uint32_t (&v)[24], uint32_t v_st, uint32_t v_last, bool full, bool first_row, uint32_t r) {
  if (full) {
#pragma unroll
    for (int j = 0; j < 12; j += 2)
      stsm4_t(v_st + (j / 6) * (A_V1 - A_V0) + (j % 6) * V_GROUP, hmul2_lo(v[2 * j], r), hmul2_hi(v[2 * j + 1], r), hmul2_lo(v[2 * j + 2], r),
              hmul2_hi(v[2 * j + 3], r));
  } else {
#pragma unroll
    for (int h = 0; h < 2; h++) {
      sts128_if(first_row, v_last + h * 128, hmul2_lo(v[12 * h], r), hmul2_lo(v[12 * h + 2], r), hmul2_lo(v[12 * h + 4], r),
                hmul2_lo(v[12 * h + 6], r));
      sts128_if(first_row, v_last + h * 128 + 16, hmul2_lo(v[12 * h + 8], r), hmul2_lo(v[12 * h + 10], r), 0u, 0u);
    }
    __syncwarp();
  }
}
__device__ __forceinline__ void issue_s(uint32_t (&s)[14], const uint32_t* qa, uint64_t k_desc) {
  hmma_n56_first(s, qa[0], qa[1], qa[2], qa[3], k_desc);
#pragma unroll
  for (int k = 1; k < 3; k++) hmma_n56(s, qa[4 * k], qa[4 * k + 1], qa[4 * k + 2], qa[4 * k + 3], desc_add(k_desc, k * 2 * K_CHUNK));
}
template <int SUM, int VAL>
__device__ __forceinline__ void pack_o(const uint32_t (&ov)[14], uint32_t* o) {
  const uint32_t p = pack_f16(rcp(fmaxf(h_lo(ov[SUM]), 0.5f)), rcp(fmaxf(h_lo(ov[SUM + 1]), 0.5f)));
#pragma unroll
  for (int j = 0; j < 6; j++) {
    o[2 * j] = hmul2_lo(ov[VAL + 2 * j], p);
    o[2 * j + 1] = hmul2_hi(ov[VAL + 2 * j + 1], p);
  }
}
template <int FIRST>
__device__ __forceinline__ void issue_half(uint32_t (&d)[24], const uint32_t (&x)[48], uint64_t desc) {
  if (FIRST == 2) hmma_n96_over(d, x[0], x[1], x[2], x[3], desc);
  if (FIRST == 1) hmma_n96_first(d, x[0], x[1], x[2], x[3], desc);
#pragma unroll
  for (int s = FIRST ? 1 : 6; s < (FIRST ? 6 : 12); s++) hmma_n96(d, x[4 * s], x[4 * s + 1], x[4 * s + 2], x[4 * s + 3], desc_add(desc, s * W_STEP));
}
template <int N>
__device__ __forceinline__ void issue_out(uint32_t (&d)[48], const uint32_t* o, uint64_t desc) {
#pragma unroll
  for (int s = 0; s < N; s++) hmma_n192(d, o[4 * s], o[4 * s + 1], o[4 * s + 2], o[4 * s + 3], desc_add(desc, s * WO_STEP));
}

__device__ __forceinline__ void mma_bf16(float (&c)[4], uint32_t a0, uint32_t a1, uint32_t a2, uint32_t a3, uint32_t b0, uint32_t b1) {
  asm("mma.sync.aligned.m16n8k16.row.col.f32.bf16.bf16.f32 {%0, %1, %2, %3}, {%4, %5, %6, %7}, {%8, %9}, {%0, %1, %2, %3};"
      : "+f"(c[0]), "+f"(c[1]), "+f"(c[2]), "+f"(c[3]) : "r"(a0), "r"(a1), "r"(a2), "r"(a3), "r"(b0), "r"(b1));
}
__device__ __forceinline__ void mma_bf16_k8(float (&d)[4], uint32_t a0, uint32_t a1, uint32_t b, const float (&c)[4]) {
  asm("mma.sync.aligned.m16n8k8.row.col.f32.bf16.bf16.f32 {%0, %1, %2, %3}, {%4, %5}, {%6}, {%7, %8, %9, %10};"
      : "=f"(d[0]), "=f"(d[1]), "=f"(d[2]), "=f"(d[3]) : "r"(a0), "r"(a1), "r"(b), "f"(c[0]), "f"(c[1]), "f"(c[2]), "f"(c[3]));
}
__device__ __forceinline__ bool on_diagonal(uint32_t lane) { return (lane & 3) == (lane >> 3); }
__device__ __forceinline__ float column_stats(const uint32_t (&v)[24], uint32_t lane, uint32_t& hi, uint32_t& lo) {
  float sum[2][4] = {}, sq[2][4] = {}, sr[2][4] = {};
#pragma unroll
  for (int c = 0; c < 24; c += 4) mma_bf16(sum[(c >> 2) & 1], v[c], v[c + 1], v[c + 2], v[c + 3], 0x3F803F80u, 0x3F803F80u);
#pragma unroll
  for (int c = 0; c < 24; c += 2) {
    mma_bf16_k8(sq[(c >> 1) & 1], v[c], v[c + 1], v[c], sq[(c >> 1) & 1]);
    mma_bf16_k8(sr[(c >> 1) & 1], v[c], v[c + 1], v[c + 1], sr[(c >> 1) & 1]);
  }
  const float total = (sum[0][0] + sum[0][2]) + (sum[1][0] + sum[1][2]), mean = total * (1.f / 192.f);
  const bool diag = on_diagonal(lane);
  const float n2 = (lane & 4) ? (sq[0][1] + sq[1][1]) + (sr[0][3] + sr[1][3]) : (sq[0][0] + sq[1][0]) + (sr[0][2] + sr[1][2]);
  hi = diag ? __float_as_uint(n2) : 0u;
  lo = __float_as_uint((diag && n2 > 0.f) ? fmaxf(fmaf(-total, mean, n2), 0.f) : INFINITY);
  return mean;
}
__device__ __forceinline__ uint32_t warp_max_abs(const uint32_t (&v)[8]) {
  uint32_t m = v[0];
#pragma unroll
  for (int c = 1; c < 8; c++) asm("max.NaN.xorsign.abs.bf16x2 %0, %0, %1;" : "+r"(m) : "r"(v[c]));
  return __reduce_max_sync(0xffffffffu, max(m & 0x7fffu, (m >> 16) & 0x7fffu));
}
__device__ __forceinline__ bool norms_in_range(uint32_t hi, uint32_t lo) {
  return hi - 0x08800000u <= 0x7B000000u - 0x08800000u && lo >= hi - (12u << 23);
}
__device__ __forceinline__ int norm_exponent(uint32_t n2) { return (int)(0x453B8000u - n2) >> 24; }
__device__ __forceinline__ void scale_to_f16(uint32_t (&v)[8], uint32_t lane, int e, float mean) {
  const uint32_t ident = on_diagonal(lane) ? (uint32_t)(e + 127) << ((lane & 4) ? 23 : 7) : 0u;
  const float c0 = -mean * __uint_as_float((uint32_t)(e + 127) << 23), c[4] = {c0, c0, c0, c0};
#pragma unroll
  for (int i = 0; i < 8; i += 2) {
    float d[4];
    mma_bf16_k8(d, v[i], v[i + 1], ident, c);
    v[i] = pack_f16(d[0], d[1]);
    v[i + 1] = pack_f16(d[2], d[3]);
  }
}
__device__ __forceinline__ float pow2(int e) { return __uint_as_float((uint32_t)(min(max(e, -126), 127) + 127) << 23); }

constexpr uint32_t kUnits = 24;
constexpr uint32_t RAW_O = W_PART, RAW_RED = RAW_O + 32 * 384;
__device__ __forceinline__ void tile_load(uint32_t dst, const CUtensorMap* tm, uint32_t c0, uint32_t c1, uint32_t bar) {
  asm volatile("cp.async.bulk.tensor.2d.shared::cluster.global.tile.mbarrier::complete_tx::bytes [%0], [%1, {%2, %3}], [%4];"
               ::"r"(dst), "l"(tm), "r"(c0), "r"(c1), "r"(bar) : "memory");
}
__device__ __forceinline__ void request_unit(uint32_t u, uint32_t raw, uint32_t bar, const CUtensorMap* tmw, const CUtensorMap* tmwo) {
  const bool is_o = (u & 7) >= 6;
  const uint32_t pair = is_o ? u & 1 : (u & 7) / 3, part = is_o ? 1 : (u & 7) % 3;
  mbar_expect_tx(bar, is_o ? W_PART + 32 * 384 : W_PART);
#pragma unroll
  for (uint32_t i = 0; i < 3; i++) tile_load(raw + i * (192 * 64), tmw, ((part + 1) % 3) * 192 + pair * 96 + 32 * i, 0, bar);
  if (is_o) {
#pragma unroll
    for (uint32_t i = 0; i < 6; i++) tile_load(raw + RAW_O + i * (32 * 64), tmwo, 32 * i, pair * 96 + (u >> 3) * 32, bar);
  }
}
__device__ __forceinline__ void ldsm4_t(uint32_t a, uint32_t* v) {
  asm volatile("ldmatrix.sync.aligned.m8n8.x4.trans.shared.b16 {%0, %1, %2, %3}, [%4];" : "=r"(v[0]), "=r"(v[1]), "=r"(v[2]), "=r"(v[3]) : "r"(a) : "memory");
}
__device__ __forceinline__ void prepare_unit(uint32_t u, uint32_t wid, uint32_t lane, uint32_t raw, Scratch* scr) {
  const bool is_o = (u & 7) >= 6;
  const uint32_t third = u >> 3;
  uint32_t v[24], w[8];
  const uint32_t src = raw + (wid >> 2) * (192 * 64) + lane * 64 + (((wid ^ (lane >> 1)) & 3) << 4);
#pragma unroll
  for (int m = 0; m < 6; m++) ldsm4_t(src + m * (32 * 64), &v[4 * m]);
  uint32_t hi, lo, top = 0;
  const float mean = column_stats(v, lane, hi, lo);
  if (is_o) {
#pragma unroll
    for (int m = 0; m < 2; m++)
      ldsm4_t(raw + RAW_O + (wid >> 1) * (32 * 64) + lane * 64 + ((((2 * wid + m) ^ (lane >> 1)) & 3) << 4), &w[4 * m]);
    top = warp_max_abs(w);
  } else {
#pragma unroll
    for (int m = 0; m < 2; m++) ldsm4_t(src + (2 * third + m) * (32 * 64), &w[4 * m]);
  }
  hi = __reduce_max_sync(0xffffffffu, hi);
  lo = __reduce_min_sync(0xffffffffu, lo);
  if (lane == 0) {
    sts64(raw + RAW_RED + wid * 16, hi, lo);
    sts32(raw + RAW_RED + wid * 16 + 8, top);
  }
  asm volatile("bar.sync 4, 384;" ::: "memory");
  lds64(raw + RAW_RED + (lane % 12) * 16, hi, lo);
  top = lds32(raw + RAW_RED + (lane % 12) * 16 + 8);
  hi = __reduce_max_sync(0xffffffffu, hi);
  lo = __reduce_min_sync(0xffffffffu, lo);
  top = __reduce_max_sync(0xffffffffu, top);
  const int e = norm_exponent(hi);
  scale_to_f16(w, lane, is_o ? -e : e - 4, is_o ? 0.f : mean);
  const uint32_t mat = lane >> 3, at = (mat & 1) * 128 + (lane & 7) * 16;
#pragma unroll
  for (int m = 0; m < 2; m++)
    stsm4(raw + at + (is_o ? (mat >> 1) * WO_STEP + (2 * wid + m) * 256 : (2 * m + (mat >> 1)) * W_STEP + wid * 256), w[4 * m], w[4 * m + 1],
          w[4 * m + 2], w[4 * m + 3]);
  fence_async();
  asm volatile("bar.sync 4, 384;" ::: "memory");
  if (wid == 0 && lane == 0) {
    asm volatile("cp.async.bulk.global.shared::cta.bulk_group [%0], [%1], %2;\ncp.async.bulk.commit_group;"
                 ::"l"(scr->weights + (u & 7) * W_PART + third * (W_PART / 3)), "r"(raw), "n"(W_PART / 3) : "memory");
    const bool bad = is_o ? !(__uint_as_float(top << 16) * pow2(-e) <= 0.25f) : !norms_in_range(hi, lo);
    const uint32_t exponent = (!is_o && third == 0 && u % 3 != 1) ? (uint32_t)(e + 64) << (u < 3 ? 10 : 19) : 0u;
    asm volatile("cp.async.bulk.wait_group 0;" ::: "memory");
    asm volatile("red.relaxed.gpu.global.add.u32 [%0], %1;" ::"l"(&scr->ready), "r"(bad ? 33u : 1u + exponent) : "memory");
  }
  __syncwarp();
}

constexpr uint32_t REDO_BYTES = 75776;
static_assert(3 * REDO_BYTES <= OFF_TAIL && (3 * 49 * 192 + 49 * 144) * 2 <= REDO_BYTES, "redo scratch");
__device__ __forceinline__ float round_bf16(float x) { return __bfloat162float(__float2bfloat16(x)); }
__device__ __forceinline__ void redo_window(int c0, int y0, int t, uint32_t bar, uint8_t* scratch, const __nv_bfloat16* x,
                                            const __nv_bfloat16* dw, const __nv_bfloat16* wqkv, const __nv_bfloat16* wo,
                                            __nv_bfloat16* out) {
  __nv_bfloat16* x0 = reinterpret_cast<__nv_bfloat16*>(scratch);
  __nv_bfloat16* h = x0 + 49 * 192;
  __nv_bfloat16* o = h + 49 * 192;
  __nv_bfloat16* qkv = o + 49 * 192;
  bar_sync(bar);
#pragma unroll 1
  for (int i = t; i < 49 * 192; i += 128) {
    const int tok = i / 192, c = i % 192, y = y0 + tok / 7, xx = c0 + tok % 7;
    float pe = 0.f;
#pragma unroll 1
    for (int k = 0; k < 9; k++) {
      const int yy = y + k / 3 - 1, xj = xx + k % 3 - 1;
      const bool in = (uint32_t)yy < kImg && (uint32_t)xj < kImg;
      const float v = in ? __bfloat162float(x[((size_t)yy * kImg + xj) * kCh + c]) : 0.f;
      pe = round_bf16(pe + round_bf16(v * __bfloat162float(dw[k * kCh + c])));
    }
    x0[i] = __float2bfloat16(__bfloat162float(x[((size_t)y * kImg + xx) * kCh + c]) + pe);
  }
  bar_sync(bar);
  if (t < 49) {
    float s = 0.f, v = 0.f;
#pragma unroll 1
    for (int c = 0; c < 192; c++) s += __bfloat162float(x0[t * 192 + c]);
    const float mean = s * (1.f / 192.f);
#pragma unroll 1
    for (int c = 0; c < 192; c++) {
      const float d = __bfloat162float(x0[t * 192 + c]) - mean;
      v = fmaf(d, d, v);
    }
    const float m = round_bf16(mean), sd = round_bf16(sqrtf(round_bf16(round_bf16(v * (1.f / 192.f)) + 1e-5f)));
#pragma unroll 1
    for (int c = 0; c < 192; c++) h[t * 192 + c] = __float2bfloat16(round_bf16(__bfloat162float(x0[t * 192 + c]) - m) / sd);
  }
#pragma unroll 1
  for (int head = 0; head < 4; head++) {
    bar_sync(bar);
#pragma unroll 1
    for (int i = t; i < 49 * 144; i += 128) {
      const int tok = i / 144, n = i % 144, col = (n / 48) * 192 + head * 48 + n % 48;
      float a = 0.f;
#pragma unroll 4
      for (int c = 0; c < 192; c++) a = fmaf(__bfloat162float(h[tok * 192 + c]), __bfloat162float(wqkv[c * 576 + col]), a);
      qkv[i] = __float2bfloat16(a);
    }
    bar_sync(bar);
    if (t < 49) {
      float p[49], m = -INFINITY, s = 0.f;
#pragma unroll
      for (int b = 0; b < 49; b++) {
        float a = 0.f;
#pragma unroll 4
        for (int d = 0; d < 48; d++) a = fmaf(__bfloat162float(qkv[t * 144 + d]), __bfloat162float(qkv[b * 144 + 48 + d]), a);
        p[b] = round_bf16(round_bf16(a) * 0.14433757f);
        m = fmaxf(m, p[b]);
      }
#pragma unroll
      for (int b = 0; b < 49; b++) {
        p[b] = expf(p[b] - m);
        s += p[b];
      }
#pragma unroll
      for (int b = 0; b < 49; b++) p[b] = round_bf16(p[b] / s);
#pragma unroll 1
      for (int d = 0; d < 48; d++) {
        float a = 0.f;
#pragma unroll
        for (int b = 0; b < 49; b++) a = fmaf(p[b], __bfloat162float(qkv[b * 144 + 96 + d]), a);
        o[t * 192 + head * 48 + d] = __float2bfloat16(a);
      }
    }
  }
  bar_sync(bar);
#pragma unroll 1
  for (int i = t; i < 49 * 192; i += 128) {
    const int tok = i / 192, n = i % 192;
    float a = 0.f;
#pragma unroll 4
    for (int c = 0; c < 192; c++) a = fmaf(__bfloat162float(o[tok * 192 + c]), __bfloat162float(wo[c * kCh + n]), a);
    out[((size_t)(y0 + tok / 7) * kImg + c0 + tok % 7) * kCh + n] = __float2bfloat16(__bfloat162float(x0[tok * 192 + n]) + round_bf16(a));
  }
}

__device__ __forceinline__ uint32_t fresh_tid() {
  uint32_t t;
  asm volatile("mov.u32 %0, %%tid.x;" : "=r"(t));
  return t;
}
struct Split {
  uint32_t top, rows, alone, share, pool;
  uint32_t magic[2];
};
struct Windows {
  uint32_t first, count, alone, jump, height, row0, magic;
  __device__ __forceinline__ explicit Windows(const Split& s) {
    uint32_t b;
    asm volatile("mov.u32 %0, %%ctaid.x;" : "=r"(b));
    const bool upper = b < s.top;
    const uint32_t i = upper ? 0 : b - s.top;
    height = upper ? s.rows : kWinPerCol - s.rows;
    row0 = upper ? 0 : s.rows;
    magic = upper ? s.magic[0] : s.magic[1];
    alone = upper ? s.rows : s.alone;
    first = upper ? b * s.rows : i * s.alone;
    count = upper ? s.rows : s.alone + s.share;
    jump = (gridDim.x - s.top - 1 - i) * s.alone + i * s.share;
  }
  __device__ __forceinline__ bool at(uint32_t j, uint32_t& col, uint32_t& row) const {
    const uint32_t v = first + j + (j >= alone ? jump : 0);
    col = (v * magic) >> 20;
    row = v - col * height + row0;
    return row == row0 || j == alone;
  }
  __device__ __forceinline__ void at(uint32_t j, uint32_t& col, uint32_t& row, uint32_t extra) const {
    at(j, col, row);
    if (j == count) {
      col = extra & 255;
      row = extra >> 8;
    }
  }
};
template <uint32_t BYTES>
__device__ __forceinline__ void load_rows(uint32_t dst, const CUtensorMap* tm, uint32_t ch, int x, int y, uint32_t bar) {
  asm volatile("{\n.reg .pred p;\nelect.sync _|p, 0xffffffff;\n"
               "@p mbarrier.arrive.expect_tx.shared::cta.b64 _, [%5], %6;\n"
               "@p cp.async.bulk.tensor.3d.shared::cluster.global.tile.mbarrier::complete_tx::bytes [%0], [%1, {%2, %3, %4}], [%5];\n}"
               ::"r"(dst), "l"(tm), "r"(ch), "r"(x), "r"(y), "r"(bar), "n"(BYTES) : "memory");
}
__device__ __forceinline__ void load_part(uint32_t dst, const void* src, uint32_t bar) {
  asm volatile("{\n.reg .pred p;\nelect.sync _|p, 0xffffffff;\n@p mbarrier.arrive.expect_tx.shared::cta.b64 _, [%3], %2;\n"
               "@p cp.async.bulk.shared::cluster.global.mbarrier::complete_tx::bytes [%0], [%1], %2, [%3];\n}"
               ::"r"(dst), "l"(src), "n"(W_PART), "r"(bar) : "memory");
}
__device__ __forceinline__ void prefetch_box(const CUtensorMap* tm, int x, int y) {
  asm volatile("cp.async.bulk.prefetch.tensor.3d.L2.global.tile [%0, {%1, %2, %3}];" ::"l"(tm), "r"(0), "r"(x), "r"(y) : "memory");
}
__device__ __forceinline__ void prefetch_rows(const CUtensorMap* tm, int x, int y) {
  asm volatile("{\n.reg .pred p;\nelect.sync _|p, 0xffffffff;\n"
               "@p cp.async.bulk.prefetch.tensor.3d.L2.global.tile [%0, {%1, %2, %3}];\n}" ::"l"(tm), "r"(0), "r"(x), "r"(y) : "memory");
}
__device__ __forceinline__ void store_window(const CUtensorMap* tm, uint32_t src, uint32_t x, uint32_t y) {
  asm volatile("{\n.reg .pred p;\n.reg .u32 a;\nelect.sync _|p, 0xffffffff;\n"
               "add.u32 a, %1, 0;\n@p cp.async.bulk.tensor.3d.global.shared::cta.tile.bulk_group [%0, {0, %2, %3}], [a];\n"
               "add.u32 a, %1, 3328;\n@p cp.async.bulk.tensor.3d.global.shared::cta.tile.bulk_group [%0, {32, %2, %3}], [a];\n"
               "add.u32 a, %1, 6656;\n@p cp.async.bulk.tensor.3d.global.shared::cta.tile.bulk_group [%0, {64, %2, %3}], [a];\n"
               "add.u32 a, %1, 9984;\n@p cp.async.bulk.tensor.3d.global.shared::cta.tile.bulk_group [%0, {96, %2, %3}], [a];\n"
               "add.u32 a, %1, 13312;\n@p cp.async.bulk.tensor.3d.global.shared::cta.tile.bulk_group [%0, {128, %2, %3}], [a];\n"
               "add.u32 a, %1, 16640;\n@p cp.async.bulk.tensor.3d.global.shared::cta.tile.bulk_group [%0, {160, %2, %3}], [a];\n"
               "cp.async.bulk.commit_group;\n}" ::"l"(tm), "r"(src), "r"(x), "r"(y) : "memory");
}
static_assert(OUT_GROUP == 3328, "store_window");

template <int N> struct Int { static constexpr int value = N; };
struct Conv {
  uint32_t wt[9], prev[9], acc[7];
  __device__ __forceinline__ void begin(const uint32_t (&cur)[9]) {
#pragma unroll
    for (int x = 0; x < 7; x++) {
      uint32_t a = bmul2(prev[x], wt[0]);
      a = bfma2(prev[x + 1], wt[1], a);
      a = bfma2(prev[x + 2], wt[2], a);
#pragma unroll
      for (int t = 0; t < 3; t++) a = bfma2(cur[x + t], wt[3 + t], a);
      acc[x] = a;
    }
#pragma unroll
    for (int x = 0; x < 9; x++) prev[x] = cur[x];
  }
  __device__ __forceinline__ void start_column(uint32_t slot0, uint32_t bar0, uint32_t parity0, uint32_t slot1, uint32_t bar1,
                                               uint32_t parity1, uint32_t lane, uint32_t dump, bool request, const CUtensorMap* tm,
                                               uint32_t ch, int x, int y) {
    uint32_t cur[9];
    mbar_wait(bar0, parity0);
#pragma unroll
    for (int i = 0; i < 9; i++) prev[i] = lds32(slot0 + lane * 4 + i * 128);
    sts32(dump, prev[0] ^ prev[1] ^ prev[2] ^ prev[3] ^ prev[4] ^ prev[5] ^ prev[6] ^ prev[7] ^ prev[8]);
    if (request) load_rows<HALO_ROW>(slot0, tm, ch, x, y, bar0);
    mbar_wait(bar1, parity1);
#pragma unroll
    for (int i = 0; i < 9; i++) cur[i] = lds32(slot1 + lane * 4 + i * 128);
    begin(cur);
    sts32(dump, acc[0] ^ acc[3] ^ acc[6]);
    if (request) load_rows<HALO_ROW>(slot1, tm, ch, x, y + 1, bar1);
  }
  __device__ __forceinline__ void row_at(uint32_t src, uint32_t dst, uint32_t t) {
    uint32_t cur[9];
#pragma unroll
    for (int x = 0; x < 9; x++) cur[x] = lds32(src + x * 128);
#pragma unroll
    for (int x = 0; x < 7; x++) {
      uint32_t a = acc[x];
#pragma unroll
      for (int i = 0; i < 3; i++) a = bfma2(cur[x + i], wt[6 + i], a);
      sts32((dst ^ (((t + x) & 7) << 4)) + x * 128, bf16x2_to_f16x2(badd2(prev[x + 1], a)));
    }
    begin(cur);
  }
  template <int R>
  __device__ __forceinline__ void row(uint32_t src, uint32_t dst, uint32_t at) {
    uint32_t cur[9];
#pragma unroll
    for (int x = 0; x < 9; x++) cur[x] = lds32(src + x * 128);
#pragma unroll
    for (int x = 0; x < 7; x++) {
      uint32_t a = acc[x];
#pragma unroll
      for (int t = 0; t < 3; t++) a = bfma2(cur[x + t], wt[6 + t], a);
      sts32((dst ^ (((R * 7 + x) & 7) << 4)) + at + x * 128, bf16x2_to_f16x2(badd2(prev[x + 1], a)));
    }
    begin(cur);
  }
};

__global__ void __launch_bounds__(512, 1)
davit_window_attn_kernel(const __grid_constant__ CUtensorMap tm1, const __grid_constant__ CUtensorMap tm7c,
                         const __grid_constant__ CUtensorMap tm7, const __grid_constant__ CUtensorMap tmo,
                         const __grid_constant__ CUtensorMap tmw, const __grid_constant__ CUtensorMap tmwo,
                         const __nv_bfloat16* __restrict__ dw, const __nv_bfloat16* __restrict__ x_raw,
                         const __nv_bfloat16* __restrict__ wqkv_raw, const __nv_bfloat16* __restrict__ wo_raw,
                         __nv_bfloat16* __restrict__ out, Scratch* __restrict__ scr, const Split split) {
  extern __shared__ __align__(1024) uint8_t smem_raw[];
  const uint32_t sb = (uint32_t)__cvta_generic_to_shared(smem_raw);
  const uint32_t tail = sb + OFF_TAIL;
  uint32_t wt[9];
  {
    const uint32_t tid = threadIdx.x;
    const uint32_t wid = __shfl_sync(0xffffffffu, tid >> 5, 0), lane = tid & 31;
    if (wid > 12) {
      const uint32_t chunk = wid - 13, hbar = tail + T_HALO + 24 * chunk, rbar = tail + T_ROW + 16 * chunk;
      if (lane == 0) {
        mbar_init(hbar, 1);
        mbar_init(hbar + 8, 1);
        mbar_init(hbar + 16, 1);
        mbar_init(rbar, 1);
        mbar_init(rbar + 8, 1);
        if (wid == 13) mbar_init(tail + T_RAW, 1);
        if (wid == 14) mbar_init(tail + T_CLAIM, 1);
        fence_async();
      }
      __syncwarp();
      if (blockIdx.x < kUnits) {
        if (wid == 13 && lane == 0) request_unit(blockIdx.x, sb + OFF_RING, tail + T_RAW, &tmw, &tmwo);
        asm volatile("bar.sync 5, 96;" ::: "memory");
      }
      uint32_t col, row;
      Windows(split).at(0, col, row);
      const int x = (int)col * 7 - 1, y = (int)row * 7;
      const uint32_t halo = sb + OFF_HALO + chunk * 3 * HALO_ROW;
      load_rows<HALO_ROW>(halo, &tm1, chunk * 64, x, y - 1, hbar);
      load_rows<HALO_ROW>(halo + HALO_ROW, &tm1, chunk * 64, x, y, hbar + 8);
      load_rows<7 * HALO_ROW>(sb + OFF_KV + chunk * 7 * HALO_ROW, &tm7c, chunk * 64, x, y + 1, rbar);
#pragma unroll
      for (int i = 0; i < 9; i++) wt[i] = __ldg(reinterpret_cast<const uint32_t*>(dw) + i * (kCh / 2) + chunk * 32 + lane);
    } else {
      if (lane == 0 && wid < 12) {
        const uint32_t i = 2 * wid, counts = (uint32_t)((wid < 8 ? 0x4144444333CCC111ull >> (8 * wid) : 0x01444144u >> (8 * wid - 64)));
        mbar_init(tail + 8 * (i < 11 ? i : i + 9), counts & 15);
        if (wid < 11) mbar_init(tail + 8 * (i < 10 ? i + 1 : i + 10), (counts >> 4) & 15);
        fence_async();
      }
      if (wid == 12) {
        for (uint32_t line = blockIdx.x + gridDim.x * lane; line < 2304; line += gridDim.x * 32) {
          const uint8_t* p = (line < 1728) ? reinterpret_cast<const uint8_t*>(wqkv_raw) + line * 128
                                           : reinterpret_cast<const uint8_t*>(wo_raw) + (line - 1728) * 128;
          asm volatile("prefetch.global.L2 [%0];" ::"l"(p));
        }
        if (lane < 7) sts32(tail + T_ZERO + 4 * lane, 0u);
      }
    }
    __syncthreads();
    if (wid < 12) {
#pragma unroll 1
      for (uint32_t u = blockIdx.x, i = 0; u < kUnits; u += gridDim.x, i++) {
        if (i) {
          asm volatile("bar.sync 4, 384;" ::: "memory");
          if (tid == 0) request_unit(u, sb + OFF_RING, tail + T_RAW, &tmw, &tmwo);
        }
        mbar_wait(tail + T_RAW, i & 1);
        prepare_unit(u, wid, lane, sb + OFF_RING, scr);
      }
    }
  }

  if (threadIdx.x >= 384) {
    asm volatile("setmaxnreg.dec.sync.aligned.u32 %0;" ::"n"(56));
    const uint32_t tid = fresh_tid();
    const uint32_t warp = __shfl_sync(0xffffffffu, (tid >> 5) & 3, 0), lane = tid & 31;
    if (warp == 0) {
      const Windows win(split);
      uint32_t spins = 0, seen;
      do {
        asm volatile("ld.acquire.gpu.global.u32 %0, [%1];" : "=r"(seen) : "l"(&scr->ready) : "memory");
        seen = __shfl_sync(0xffffffffu, seen, 0);
        if (++spins > (1u << 22)) __trap();
      } while ((seen & 31) != kUnits);
      asm volatile("fence.proxy.async.global;" ::: "memory");
      {
        const int e0 = (int)((seen >> 10) & 511) - 128, e1 = (int)(seen >> 19) - 128;
        sts32(tail + T_SCALE, pack_f16(fmaxf(0.20823509f * pow2(9 - e0), 0x1p-24f), fmaxf(0.20823509f * pow2(9 - e1), 0x1p-24f)));
        if ((seen & 0x3E0u) || e0 < 1 || e1 < 1) sts32(tail + T_ALL, 1u);
        __syncwarp();
      }
#pragma unroll
      for (uint32_t s = 0; s < 3; s++) load_part(sb + OFF_RING + s * W_PART, scr->weights + s * W_PART, tail + T_FULL + 8 * s);
#pragma unroll 1
      for (uint32_t j = 2; j < 4; j++) {
        uint32_t col, row;
        const bool fresh = win.at(j, col, row);
        if (j == 3 || fresh) prefetch_rows(&tm7, 7 * col - 1, 7 * row + 1);
        if (fresh) prefetch_rows(&tm7, 7 * col - 1, 7 * row - 1);
      }
      if (lane == 0 && atomicInc(&scr->passed, gridDim.x - 1) == gridDim.x - 1) scr->ready = 0;
      __syncwarp();
      const uint32_t uses = 8 * (win.count / 3 + 1);
#pragma unroll 1
      for (uint32_t u = 3; u < uses; u++) {
        const uint32_t m = u / 3, s = u - 3 * m;
        mbar_wait(tail + T_EMPTY + 8 * s, (m & 1) ^ 1);
        load_part(sb + OFF_RING + s * W_PART, scr->weights + (u & 7) * W_PART, tail + T_FULL + 8 * s);
      }
    } else {
      Conv cv;
#pragma unroll
      for (int i = 0; i < 9; i++) cv.wt[i] = wt[i];
      {
        const uint32_t chunk = warp - 1, halo = sb + OFF_HALO + chunk * 3 * HALO_ROW, hbar = tail + T_HALO + 24 * chunk;
        const Windows win(split);
        uint32_t col, row, cn, rn;
        const uint32_t staged = (win.count > 1 && !win.at(1, col, row)) ? 2 : 1;
        const bool fresh = win.at(staged, cn, rn);
        const int xn = 7 * cn - 1, yn = fresh ? 7 * rn - 1 : 7 * rn + 1;
        if (staged < win.count) load_rows<HALO_ROW>(halo + 2 * HALO_ROW, &tm1, chunk * 64, xn, yn, hbar + 16);
        cv.start_column(halo, hbar, 0, halo + HALO_ROW, hbar + 8, 0, lane, tail + T_DUMP, staged < win.count, &tm1, chunk * 64, xn, yn + 1);
        if (staged == 2)
          load_rows<7 * HALO_ROW>(sb + OFF_KV + (3 + chunk) * 7 * HALO_ROW, &tm7c, chunk * 64, 7 * col - 1, 7 * row + 1,
                                  tail + T_ROW + 16 * chunk + 8);
#pragma unroll 1
        for (uint32_t i = 0; i < staged; i++) {
          mbar_wait(tail + T_ROW + 16 * chunk + 8 * i, 0);
#pragma unroll 1
          for (uint32_t r = 0; r < 7; r++)
            cv.row_at(sb + OFF_KV + ((3 * i + chunk) * 7 + r) * HALO_ROW + lane * 4,
                      sb + OFF_X0 + chunk * X0_CHUNK + lane * 4 + (7 * i + r) * X0_ROW, 7 * r);
          __syncwarp();
          arrive_elected(tail + T_X0FULL + 8 * i);
          if (i == 0 && chunk == 0 && staged < win.count) prefetch_rows(&tm7, xn, yn + 3);
        }
      }
      const uint32_t chunk = __shfl_sync(0xffffffffu, (fresh_tid() >> 5) & 3, 0) - 1, ch = chunk * 64;
      const uint32_t halo = sb + OFF_HALO + chunk * 3 * HALO_ROW, hbar = tail + T_HALO + 24 * chunk;
      const uint32_t src = halo + lane * 4, dst = sb + OFF_X0 + chunk * X0_CHUNK + lane * 4;
      const Windows win(split);
      uint32_t count = win.count;
      uint32_t col, row;
      const uint32_t staged = (count > 1 && !win.at(1, col, row)) ? 2 : 1;
      bool fresh = win.at(staged, col, row);
      uint32_t s0 = 2, p0 = 0;
#pragma unroll 1
      for (uint32_t j = staged; j < count; j++) {
        int x = (int)col * 7 - 1, y = (int)row * 7;
        uint32_t at = 7 * j % kRows * X0_ROW;
        if (fresh) {
          const uint32_t s1 = (s0 == 2) ? 0 : s0 + 1;
          cv.start_column(halo + s0 * HALO_ROW, hbar + 8 * s0, p0, halo + s1 * HALO_ROW, hbar + 8 * s1, p0 ^ (s0 == 2), lane, tail + T_DUMP, true,
                          &tm1, ch, x, y + 2);
          p0 ^= (s0 != 0);
          s0 = (s0 == 0) ? 2 : s0 - 1;
        }
        const uint32_t slot[3] = {s0, (s0 == 2) ? 0 : s0 + 1, (s0 == 0) ? 2 : s0 - 1}, parity[3] = {p0, p0 ^ (s0 == 2), p0 ^ (s0 != 0)};
        if (chunk == 0 && j + 1 == win.count) {
          if (lane == 0) {
            const uint32_t i = atomicInc(&scr->claims, gridDim.x - 1);
            uint32_t extra = ~0u;
            if (i < split.pool) {
              const uint32_t v = kWinPerCol * (kWinPerCol - split.rows) - split.pool + i, c = (v * split.magic[1]) >> 20;
              extra = c + 256 * (v - c * (kWinPerCol - split.rows) + split.rows);
              prefetch_box(&tm7, 7 * c - 1, 7 * (extra >> 8) - 1);
              prefetch_box(&tm7, 7 * c - 1, 7 * (extra >> 8) + 1);
            }
            sts32(tail + T_EXTRA, extra);
            mbar_arrive(tail + T_CLAIM);
          }
          __syncwarp();
        }
        if (chunk == 0 && j + 2 < win.count) {
          if (win.at(j + 2, col, row)) prefetch_rows(&tm7, 7 * col - 1, 7 * row - 1);
          prefetch_rows(&tm7, 7 * col - 1, 7 * row + 1);
        }
        fresh = win.at(j + 1, col, row);
        auto step = [&](auto r) {
          constexpr int R = decltype(r)::value;
          if (R == kRows - 14) {
            mbar_wait(tail + T_X0FREE + 8 * (j & 1), ((j >> 1) & 1) ^ 1);
          }
          if (R == 4) {
            if (j + 1 == win.count) {
              mbar_wait(tail + T_CLAIM, 0);
              const uint32_t extra = __shfl_sync(0xffffffffu, lds32(tail + T_EXTRA), 0);
              count += (extra != ~0u);
              col = extra & 255;
              row = extra >> 8;
              fresh = true;
            }
            x = (int)col * 7 - 1;
            y = (int)row * 7 - (fresh ? 9 : 7);
          }
          mbar_wait(hbar + 8 * slot[R % 3], parity[R % 3] ^ ((R / 3) & 1));
          cv.template row<R>(src + slot[R % 3] * HALO_ROW, dst, at);
          if (R < 4 || j + 1 < count) load_rows<HALO_ROW>(halo + slot[R % 3] * HALO_ROW, &tm1, ch, x, y + R + 4, hbar + 8 * slot[R % 3]);
          at = (at == (kRows - 1) * X0_ROW) ? 0 : at + X0_ROW;
        };
        step(Int<0>()); step(Int<1>()); step(Int<2>()); step(Int<3>()); step(Int<4>()); step(Int<5>()); step(Int<6>());
        __syncwarp();
        arrive_elected(tail + T_X0FULL + 8 * (j % 3));
        s0 = slot[1];
        p0 = parity[1];
      }
    }
    __syncwarp();
    asm volatile("bar.sync 0, 512;" ::: "memory");
  } else {
    asm volatile("setmaxnreg.inc.sync.aligned.u32 %0;" ::"n"(152));
    const uint32_t wid = __shfl_sync(0xffffffffu, fresh_tid() >> 5, 0);
    const uint32_t wg = wid >> 2, warp = wid & 3;
    uint32_t lane;
    asm volatile("mov.u32 %0, %%laneid;" : "=r"(lane));
    const uint32_t count = Windows(split).count;
    const uint32_t q = lane & 3, mat = lane >> 3, row = lane & 7;
    const uint32_t area = sb + OFF_KV + wg * KV_SIZE;
    const uint32_t bars = tail + T_WG + 32 * wg;
    const bool full = warp < 3;
    const bool valid = full || lane < 4;
    const bool lead = lane == 0;
    uint32_t k_st, v_st, x_ld, x_mask, x_row, o_st;
    {
      const uint32_t rowg = full ? 2 * warp + (mat & 1) : 6, colg = full ? (mat >> 1) : (mat & 1);
      k_st = full ? area + A_K0 + colg * K_CHUNK + rowg * 128 + row * 16 : area + A_K0 + 768 + q * 4;
      v_st = full ? area + A_V0 + colg * V_GROUP + rowg * 128 + row * 16 : area + A_ONES + lane * 16;
      const uint32_t t = 16 * warp + row + 8 * (mat & 1);
      x_ld = (t < 49) ? sb + OFF_X0 + t * 128 + (((mat >> 1) ^ row) << 4) : tail + T_ZERO;
      x_mask = (t < 49) ? ~0u : 0u;
      x_row = t / 7;
      const uint32_t a = area + (full ? t : 48) * 64;
      o_st = a + (((full ? (mat >> 1) : 0) ^ ((a >> 7) & 3)) << 4) + (full ? 0 : 4 * q);
    }
    const uint32_t v_last = area + A_LAST + q * 32;
    const uint32_t pad = (valid ? 0u : 0xFC00u) | (full ? 0u : 0xFC000000u);
    const uint64_t k_desc = make_desc(area + A_K0, K_CHUNK, 128);
    const uint64_t v_desc = make_desc(area + A_V0, 128, V_GROUP);
    const uint64_t w_desc = make_desc(sb + OFF_RING, 128, 256);
    if (wg == 2) asm volatile("bar.arrive 8, 256;" ::: "memory");
    auto send_output = [&](uint32_t j, uint32_t parity, bool last) {
      uint32_t col, row;
      if (last) Windows(split).at(j, col, row, __shfl_sync(0xffffffffu, lds32(tail + T_EXTRA), 0));
      else Windows(split).at(j, col, row);
      mbar_wait(bars + B_OUTRDY, parity);
      store_window(&tmo, area, 7 * col, 7 * row);
    };
    uint32_t round = 0;
#pragma unroll 1
    for (; 3 * round + wg <= count; round++) {
      const uint32_t r = __shfl_sync(0xffffffffu, round, 0), j = 3 * r + wg, ph = r & 1;
      if (j == count) {
        mbar_wait(tail + T_CLAIM, 0);
        if (__shfl_sync(0xffffffffu, lds32(tail + T_EXTRA), 0) == ~0u) break;
      }
      const uint32_t m = 8 * r / 3, rot = 8 * r - 3 * m;
      const uint32_t ra = 8 * rot, rb = (rot == 2) ? 0 : ra + 8, rc = (rot == 0) ? 16 : ra - 8;
      const uint32_t pa = m & 1, pb = pa ^ (rot == 2), pc = pa ^ (rot != 0);
      uint32_t x[48], ka[24], va[24], oa[24], ob[24], rr, scales;
      uint32_t (&qa)[24] = ka;
      uint32_t sc0[14], sc1[14], pa0[12], pa1[12], ov0[14], ov1[14];
      mbar_wait(tail + T_X0FULL + 8 * wg, ph);
      asm volatile("" : "+r"(x_mask));
      const uint32_t x_at = 7 * j % kRows;
      const uint32_t x_a = x_ld + ((x_at * X0_ROW - (x_row >= kRows - x_at ? X0_CHUNK : 0)) & x_mask);
      auto load_x = [&](auto s0, auto s1) {
#pragma unroll
        for (int s = decltype(s0)::value; s < decltype(s1)::value; s++)
          ldsm4((x_a ^ (((s & 3) << 5) & x_mask)) + ((s >> 2) * X0_CHUNK & x_mask), x[4 * s], x[4 * s + 1], x[4 * s + 2], x[4 * s + 3]);
      };
      load_x(Int<0>(), Int<6>());
#pragma unroll
      for (int p = 0; p < 2; p++) {
        asm volatile("bar.sync %0, 256;" ::"r"(8 + wg) : "memory");
        mbar_wait(tail + T_FULL + ra, pa ^ p);
        if (p == 0) {
          load_x(Int<6>(), Int<12>());
          warp_arrive(tail + T_X0FREE + 8 * (j & 1), lead);
        }
        wg_fence();
        {
          const uint64_t d = desc_at(w_desc, ra * (W_PART / 8));
          issue_half<1>(ka, x, d);
          if (p == 0) wg_fence();
          issue_half<0>(ka, x, d);
        }
        wg_commit();
        if (p == 0) {
          if (!full && r > 0) send_output(j - 3, ph ^ 1, false);
        }
        if (p == 1) {
          wg_wait<1>();
          fence_regs(ov1);
          if (lead) mbar_arrive(bars + B_KVFREE);
          pack_o<0, 2>(ov1, &oa[12]);
        }
        mbar_wait(tail + T_FULL + rb, pb ^ p);
        wg_fence();
        {
          const uint64_t d = desc_at(w_desc, rb * (W_PART / 8));
          issue_half<1>(va, x, d);
          wg_commit();
          wg_wait<1>();
          if (lead) mbar_arrive(tail + T_EMPTY + ra);
          __syncwarp();
          issue_half<0>(va, x, d);
          wg_commit();
        }
        asm volatile("bar.arrive %0, 256;" ::"r"(wg == 2 ? 8 : 9 + wg) : "memory");
        if (p == 0) {
          scales = __shfl_sync(0xffffffffu, lds32(tail + T_SCALE), 0);
          const bool odd = q & 1;
          uint32_t lane_sums[2];
          lane_stats_packed(x, lane_sums);
          const uint32_t packed = quad_stats_packed(lane_sums, odd);
          float sum = h_lo(packed), squares = h_hi(packed);
          const bool fine = (squares >= 0.1875f || (pad & (odd ? 0xFC000000u : 0xFC00u))) & (squares <= 65504.f) & (sum * sum <= 96.f * squares);
          const bool exact = !__all_sync(0xffffffffu, fine);
          if (exact) {
            wg_wait<0>();
            row_stats(x, odd, sum, squares);
          }
          const float mean = sum * (1.f / 192.f);
          const float rs = 16.f * rsqrt_fast(fmaxf(fmaf(squares, 1.f / 192.f, -mean * mean), 0.f) + 1e-5f);
          if (exact) {
            const uint32_t range = __reduce_max_sync(0xffffffffu, __float_as_uint(squares * fmaxf(rs * rs, 1.f)));
            if ((range > 0x4D400000u || (range != 0u && range < 0x4585A800u)) && lead) {
              scr->redo[blockIdx.x + gridDim.x * j] = 1;
              sts32(tail + T_ANY, 1u);
            }
          }
          const float o = __shfl_xor_sync(0xffffffffu, rs, 1);
          rr = pack_f16(odd ? o : rs, odd ? rs : o);
          if (!full) {
            asm volatile("cp.async.bulk.wait_group.read 0;" ::: "memory");
            warp_arrive(bars + B_OUTFREE, lead);
          }
          mbar_wait(bars + B_OUTFREE, ph);
        } else {
          mbar_wait(bars + B_KVFREE, 0);
        }
        fence_regs(ka);
        store_k(ka, k_st, full, lane < 4, rr);
        mbar_wait(tail + T_FULL + rc, pc ^ p);
        wg_fence();
        {
          const uint64_t d = desc_at(w_desc, rc * (W_PART / 8));
          issue_half<2>(qa, x, d);
          wg_commit();
          wg_wait<1>();
          if (lead) mbar_arrive(tail + T_EMPTY + rb);
          __syncwarp();
          issue_half<0>(qa, x, d);
          wg_commit();
        }
        fence_regs(va);
        if (p == 0 && !full) {
          sts128_if(true, v_st, 0x3C003C00u, 0x3C003C00u, 0x3C003C00u, 0x3C003C00u);
          sts128_if(lane < 16, v_st + 512, 0x3C003C00u, 0x3C003C00u, 0x3C003C00u, 0x3C003C00u);
        }
        store_v(va, v_st, v_last, full, lane < 4, rr);
        fence_async();
        warp_arrive(bars + B_KVRDY, lead);
        wg_wait<0>();
        fence_regs(qa);
        if (lead) mbar_arrive(tail + T_EMPTY + rc);
        {
          const uint32_t rq = hmul2(rr, 0x18001800u);
#pragma unroll
          for (int i = 0; i < 24; i += 2) {
            qa[i] = hmul2_lo(qa[i], rq);
            qa[i + 1] = hmul2_hi(qa[i + 1], rq);
          }
        }
        const uint32_t cr = (p == 0) ? both<0>(scales) : both<1>(scales);
        mbar_wait(bars + B_KVRDY, p);

        wg_fence();
        issue_s(sc0, &qa[0], desc_at(k_desc, 0));
        wg_commit();
        uint32_t top0, top1, last0, last1;
        if (p == 0) {
          issue_s(sc1, &qa[12], desc_at(k_desc, A_K1));
          wg_commit();
          wg_wait<1>();
          fence_regs(sc0);
          top0 = softmax_top(sc0, lane, cr, last0);
          softmax_rows<12, 0>(sc0, top0, last0, cr, pad, v_last, pa0, ov0);
          wg_fence();
          issue_pv(ov0, pa0, desc_at(v_desc, 0));
          wg_commit();
          wg_wait<1>();
          fence_regs(sc1);
          top1 = softmax_top(sc1, lane, cr, last1);
          softmax_rows<0, 2>(sc1, top1, last1, cr, pad, v_last + 128, pa1, ov1);
        } else {
          wg_wait<0>();
          fence_regs(sc0);
          wg_fence();
          issue_s(sc1, &qa[12], desc_at(k_desc, A_K1));
          wg_commit();
          top0 = softmax_top(sc0, lane, cr, last0);
          wg_wait<0>();
          fence_regs(sc1);
          softmax_rows<12, 0>(sc0, top0, last0, cr, pad, v_last, pa0, ov0);
          mbar_wait(tail + T_FULL + ra, pa);
          wg_fence();
          issue_pv(ov0, pa0, desc_at(v_desc, 0));
          wg_commit();
          issue_out<6>(x, oa, desc_at(w_desc, ra * (W_PART / 8)));
          wg_commit();
          top1 = softmax_top(sc1, lane, cr, last1);
          wg_wait<1>();
          fence_regs(ov0);
          softmax_rows<0, 2>(sc1, top1, last1, cr, pad, v_last + 128, pa1, ov1);
        }
        wg_fence();
        issue_pv(ov1, pa1, desc_at(v_desc, A_ONES - A_V0));
        wg_commit();
        wg_wait<1>();
        if (p == 0) fence_regs(ov0);
        else if (lead) mbar_arrive(tail + T_EMPTY + ra);
        {
          uint32_t big;
          asm("{\n.reg .pred p, q;\n.reg .b32 t;\nmax.xorsign.abs.f16x2 t, %1, %2;\nabs.f16x2 t, t;\nsetp.gt.f16x2 p|q, t, %3;\n"
              "or.pred p, p, q;\nselp.u32 %0, 1, 0, p;\n}" : "=r"(big) : "r"(top0), "r"(top1), "r"(0x60006000u));
          if (__any_sync(0xffffffffu, big) && lead) {
            scr->redo[blockIdx.x + gridDim.x * j] = 1;
            sts32(tail + T_ANY, 1u);
          }
          __syncwarp();
        }
        uint32_t (&o)[24] = (p == 0) ? oa : ob;
        pack_o<12, 0>(ov0, &o[0]);
        if (p == 1) {
          mbar_wait(tail + T_FULL + rb, pb);
          wg_fence();
          issue_out<3>(x, &ob[0], desc_at(w_desc, rb * (W_PART / 8)));
          wg_commit();
          wg_wait<1>();
          fence_regs(ov1);
          if (lead) mbar_arrive(bars + B_KVFREE);
          pack_o<0, 2>(ov1, &o[12]);
        }
      }
      wg_fence();
      issue_out<3>(x, &ob[12], desc_at(w_desc, rb * (W_PART / 8) + 3 * WO_STEP));
      wg_commit();
      mbar_wait(bars + B_KVFREE, 1);
      wg_wait<0>();
      fence_regs(x);
      if (lead) mbar_arrive(tail + T_EMPTY + rb);
      asm volatile("" : "+r"(o_st));
      if (full) {
#pragma unroll
        for (int s = 0; s < 12; s++)
          stsm4((o_st ^ (((s ^ (s >> 1)) & 1) << 5)) + (s >> 1) * OUT_GROUP, f16x2_to_bf16x2(x[4 * s]), f16x2_to_bf16x2(x[4 * s + 1]),
                f16x2_to_bf16x2(x[4 * s + 2]), f16x2_to_bf16x2(x[4 * s + 3]));
        fence_async();
        warp_arrive(bars + B_OUTRDY, lead);
      } else {
#pragma unroll
        for (int i = 0; i < 24; i++)
          sts32_if(lane < 4, (o_st ^ (((i ^ ((i >> 1) & 2)) & 3) << 4)) + (i >> 2) * OUT_GROUP, f16x2_to_bf16x2(x[2 * i]));
        fence_async();
        warp_arrive(bars + B_OUTRDY, lead);
      }
    }
    if (!full && round > 0) send_output(3 * round + wg - 3, (round & 1) ^ 1, true);
    if (3 * round <= count) {
#pragma unroll 1
      for (uint32_t i = 0; i < 5; i++) {
        if (i % 3 == 0) {
          asm volatile("bar.sync %0, 256;" ::"r"(8 + wg) : "memory");
          asm volatile("bar.arrive %0, 256;" ::"r"(wg == 2 ? 8 : 9 + wg) : "memory");
        }
        const uint32_t u = 8 * round + i;
        mbar_wait(tail + T_FULL + 8 * (u % 3), (u / 3) & 1);
        if (lead) mbar_arrive(tail + T_EMPTY + 8 * (u % 3));
        __syncwarp();
      }
    }
    asm volatile("cp.async.bulk.wait_group.read 0;" ::: "memory");
    __syncwarp();
    asm volatile("bar.sync 0, 512;" ::: "memory");
    const uint32_t redo_all = lds32(tail + T_ALL);
    if (redo_all | lds32(tail + T_ANY)) {
      const uint32_t t = fresh_tid(), c = t >> 7;
      asm volatile("cp.async.bulk.wait_group 0;\nfence.proxy.async.global;" ::: "memory");
      const Windows win(split);
      const uint32_t extra = lds32(tail + T_EXTRA);
      for (uint32_t j = c; j < win.count + (extra != ~0u); j += 3) {
        uint8_t* flag = &scr->redo[blockIdx.x + gridDim.x * j];
        if (!redo_all && !*reinterpret_cast<volatile uint8_t*>(flag)) continue;
        uint32_t col, row;
        win.at(j, col, row, extra);
        redo_window(7 * col, 7 * row, t & 127, 1 + c, smem_raw + c * REDO_BYTES, x_raw, dw, wqkv_raw, wo_raw, out);
        if ((t & 127) == 0) *flag = 0;
      }
    }
  }
}

typedef CUresult (*EncodeTiledFn)(CUtensorMap*, CUtensorMapDataType, cuuint32_t, void*, const cuuint64_t*, const cuuint64_t*,
                                  const cuuint32_t*, const cuuint32_t*, CUtensorMapInterleave, CUtensorMapSwizzle,
                                  CUtensorMapL2promotion, CUtensorMapFloatOOBfill);

}

extern "C" void kernel_launch(void* const* d_in, const int* in_sizes, int n_in, void* d_out, int out_size) {
  (void)in_sizes; (void)n_in; (void)out_size;
  static EncodeTiledFn encode = nullptr;
  static int grid = 0;
  static void* scratch = nullptr;
  if (!encode) {
    void* fn = nullptr;
    cudaDriverEntryPointQueryResult st;
    cudaGetDriverEntryPoint("cuTensorMapEncodeTiled", &fn, cudaEnableDefault, &st);
    encode = (EncodeTiledFn)fn;
    cudaFuncSetAttribute(davit_window_attn_kernel, cudaFuncAttributeMaxDynamicSharedMemorySize, SMEM_BYTES);
    cudaGetSymbolAddress(&scratch, g_scratch);
    int dev = 0;
    cudaGetDevice(&dev);
    cudaDeviceGetAttribute(&grid, cudaDevAttrMultiProcessorCount, dev);
    if (grid > 1024) grid = 1024;
  }
  Split split = {};
  {
    const uint32_t g = grid, n = kNumWin / g;
    if (g > kWinPerCol && g <= 2 * kWinPerCol && kWinPerCol - n <= n) {
      const uint32_t below = (kWinPerCol - n) * kWinPerCol;
      split.top = kWinPerCol;
      split.rows = (below > (n + 1) * (g - kWinPerCol) && n + 1 < kWinPerCol) ? n + 1 : n;
      split.alone = kWinPerCol - split.rows;
    }
    const uint32_t others = g - split.top, rest = kNumWin - split.top * split.rows - others * split.alone;
    split.share = rest / others;
    split.pool = rest % others;
    split.magic[0] = split.rows ? ((1u << 20) + split.rows - 1) / split.rows : 0;
    split.magic[1] = ((1u << 20) + kWinPerCol - split.rows - 1) / (kWinPerCol - split.rows);
  }
  auto image_map = [&](void* base, cuuint32_t c, cuuint32_t w, cuuint32_t h, CUtensorMapSwizzle swizzle) {
    CUtensorMap tm;
    const cuuint64_t dims[3] = {(cuuint64_t)kCh, (cuuint64_t)kImg, (cuuint64_t)kImg};
    const cuuint64_t strides[2] = {(cuuint64_t)kCh * 2, (cuuint64_t)kCh * 2 * kImg};
    const cuuint32_t box[3] = {c, w, h};
    const cuuint32_t estr[3] = {1, 1, 1};
    encode(&tm, CU_TENSOR_MAP_DATA_TYPE_BFLOAT16, 3, base, dims, strides, box, estr, CU_TENSOR_MAP_INTERLEAVE_NONE, swizzle,
           CU_TENSOR_MAP_L2_PROMOTION_L2_128B, CU_TENSOR_MAP_FLOAT_OOB_FILL_NONE);
    return tm;
  };
  auto weight_map = [&](void* base, cuuint64_t cols, cuuint32_t rows) {
    CUtensorMap tm;
    const cuuint64_t dims[2] = {cols, (cuuint64_t)kCh};
    const cuuint64_t strides[1] = {cols * 2};
    const cuuint32_t box[2] = {32, rows};
    const cuuint32_t estr[2] = {1, 1};
    encode(&tm, CU_TENSOR_MAP_DATA_TYPE_BFLOAT16, 2, base, dims, strides, box, estr, CU_TENSOR_MAP_INTERLEAVE_NONE,
           CU_TENSOR_MAP_SWIZZLE_64B, CU_TENSOR_MAP_L2_PROMOTION_L2_128B, CU_TENSOR_MAP_FLOAT_OOB_FILL_NONE);
    return tm;
  };
  davit_window_attn_kernel<<<grid, 512, SMEM_BYTES, cudaStreamPerThread>>>(
      image_map(d_in[0], 64, 9, 1, CU_TENSOR_MAP_SWIZZLE_NONE), image_map(d_in[0], 64, 9, 7, CU_TENSOR_MAP_SWIZZLE_NONE),
      image_map(d_in[0], 192, 9, 7, CU_TENSOR_MAP_SWIZZLE_NONE), image_map(d_out, 32, 7, 7, CU_TENSOR_MAP_SWIZZLE_64B),
      weight_map(d_in[2], 576, 192), weight_map(d_in[3], 192, 32),
      (const __nv_bfloat16*)d_in[1], (const __nv_bfloat16*)d_in[0], (const __nv_bfloat16*)d_in[2], (const __nv_bfloat16*)d_in[3],
      (__nv_bfloat16*)d_out, (Scratch*)scratch, split);
}
```

```cpp
#include <cuda.h>
#include <cuda_bf16.h>
#include <cuda_runtime.h>
#include <stdint.h>

namespace {

constexpr int kImg = 511;
constexpr int kCh = 192;
constexpr int kWinPerCol = 73;
constexpr int kNumWin = 73 * 73;

constexpr uint32_t W_PART = 36864;
constexpr uint32_t W_STEP = 3072;
constexpr uint32_t WO_STEP = 6144;
constexpr uint32_t W_BYTES = 8 * W_PART;

struct Scratch {
  uint8_t weights[W_BYTES];
  uint32_t ready;
  uint32_t passed;
  uint32_t claims;
  uint8_t redo[2 * kNumWin];
};
__device__ __align__(128) Scratch g_scratch;

constexpr uint32_t OFF_RING = 0;
constexpr uint32_t OFF_X0 = 3 * W_PART;
constexpr uint32_t kRows = 19;
constexpr uint32_t X0_ROW = 7 * 128;
constexpr uint32_t X0_CHUNK = kRows * X0_ROW;
constexpr uint32_t OFF_HALO = OFF_X0 + 3 * X0_CHUNK;
constexpr uint32_t HALO_ROW = 9 * 128;
constexpr uint32_t OFF_KV = OFF_HALO + 9 * HALO_ROW;
constexpr uint32_t K_CHUNK = 784;
constexpr uint32_t V_GROUP = 768;
constexpr uint32_t A_K0 = 0;
constexpr uint32_t A_V0 = 6 * K_CHUNK;
constexpr uint32_t A_ONES = A_V0 + 6 * V_GROUP;
constexpr uint32_t A_V1 = A_ONES + V_GROUP;
constexpr uint32_t A_K1 = A_V1 + 6 * V_GROUP;
constexpr uint32_t A_LAST = A_K1 + 6 * K_CHUNK;
constexpr uint32_t KV_SIZE = 19840;
constexpr uint32_t OUT_GROUP = 3328;
static_assert(A_LAST + 256 <= KV_SIZE && 5 * OUT_GROUP + 3136 <= KV_SIZE && KV_SIZE % 128 == 0 && 42 * HALO_ROW <= 3 * KV_SIZE &&
              21 * HALO_ROW >= KV_SIZE, "consumer area");
constexpr uint32_t OFF_TAIL = OFF_KV + 3 * KV_SIZE;
constexpr uint32_t SMEM_BYTES = OFF_TAIL + 360;
static_assert(SMEM_BYTES <= 232448, "shared memory");

constexpr uint32_t T_FULL = 0;
constexpr uint32_t T_EMPTY = 24;
constexpr uint32_t T_X0FULL = 48;
constexpr uint32_t T_X0FREE = 72;
constexpr uint32_t T_HALO = 88;
constexpr uint32_t T_WG = 160;
constexpr uint32_t B_KVRDY = 0;
constexpr uint32_t B_KVFREE = 8;
constexpr uint32_t B_OUTRDY = 16;
constexpr uint32_t B_OUTFREE = 24;
constexpr uint32_t T_RAW = 256;
constexpr uint32_t T_CLAIM = 264;
constexpr uint32_t T_ZERO = 272;
constexpr uint32_t T_SCALE = 288;
constexpr uint32_t T_ALL = 292;
constexpr uint32_t T_ANY = 296;
constexpr uint32_t T_DUMP = 300;
constexpr uint32_t T_ROW = 304;
constexpr uint32_t T_EXTRA = 352;

__device__ __forceinline__ void hmma_n96_first(uint32_t (&d)[24], uint32_t a0, uint32_t a1, uint32_t a2, uint32_t a3, uint64_t desc) {
  asm volatile("wgmma.mma_async.sync.aligned.m64n96k16.f16.f16.f16 "
               "{%0, %1, %2, %3, %4, %5, %6, %7, %8, %9, %10, %11, %12, %13, %14, %15, "
               "%16, %17, %18, %19, %20, %21, %22, %23}, "
               "{%24, %25, %26, %27}, %28, 0, 1, 1, 0;\n"
               : "=r"(d[0]), "=r"(d[1]), "=r"(d[2]), "=r"(d[3]), "=r"(d[4]), "=r"(d[5]), "=r"(d[6]), "=r"(d[7]),
                 "=r"(d[8]), "=r"(d[9]), "=r"(d[10]), "=r"(d[11]), "=r"(d[12]), "=r"(d[13]), "=r"(d[14]), "=r"(d[15]),
                 "=r"(d[16]), "=r"(d[17]), "=r"(d[18]), "=r"(d[19]), "=r"(d[20]), "=r"(d[21]), "=r"(d[22]), "=r"(d[23])
               : "r"(a0), "r"(a1), "r"(a2), "r"(a3), "l"(desc));
}
__device__ __forceinline__ void hmma_n96(uint32_t (&d)[24], uint32_t a0, uint32_t a1, uint32_t a2, uint32_t a3, uint64_t desc) {
  asm volatile("wgmma.mma_async.sync.aligned.m64n96k16.f16.f16.f16 "
               "{%0, %1, %2, %3, %4, %5, %6, %7, %8, %9, %10, %11, %12, %13, %14, %15, "
               "%16, %17, %18, %19, %20, %21, %22, %23}, "
               "{%24, %25, %26, %27}, %28, 1, 1, 1, 0;\n"
               : "+r"(d[0]), "+r"(d[1]), "+r"(d[2]), "+r"(d[3]), "+r"(d[4]), "+r"(d[5]), "+r"(d[6]), "+r"(d[7]),
                 "+r"(d[8]), "+r"(d[9]), "+r"(d[10]), "+r"(d[11]), "+r"(d[12]), "+r"(d[13]), "+r"(d[14]), "+r"(d[15]),
                 "+r"(d[16]), "+r"(d[17]), "+r"(d[18]), "+r"(d[19]), "+r"(d[20]), "+r"(d[21]), "+r"(d[22]), "+r"(d[23])
               : "r"(a0), "r"(a1), "r"(a2), "r"(a3), "l"(desc));
}
__device__ __forceinline__ void hmma_n96_over(uint32_t (&d)[24], uint32_t a0, uint32_t a1, uint32_t a2, uint32_t a3, uint64_t desc) {
  asm volatile("wgmma.mma_async.sync.aligned.m64n96k16.f16.f16.f16 "
               "{%0, %1, %2, %3, %4, %5, %6, %7, %8, %9, %10, %11, %12, %13, %14, %15, "
               "%16, %17, %18, %19, %20, %21, %22, %23}, "
               "{%24, %25, %26, %27}, %28, 0, 1, 1, 0;\n"
               : "+r"(d[0]), "+r"(d[1]), "+r"(d[2]), "+r"(d[3]), "+r"(d[4]), "+r"(d[5]), "+r"(d[6]), "+r"(d[7]),
                 "+r"(d[8]), "+r"(d[9]), "+r"(d[10]), "+r"(d[11]), "+r"(d[12]), "+r"(d[13]), "+r"(d[14]), "+r"(d[15]),
                 "+r"(d[16]), "+r"(d[17]), "+r"(d[18]), "+r"(d[19]), "+r"(d[20]), "+r"(d[21]), "+r"(d[22]), "+r"(d[23])
               : "r"(a0), "r"(a1), "r"(a2), "r"(a3), "l"(desc));
}
__device__ __forceinline__ void hmma_n56_first(uint32_t (&d)[14], uint32_t a0, uint32_t a1, uint32_t a2, uint32_t a3, uint64_t desc) {
  asm volatile("wgmma.mma_async.sync.aligned.m64n56k16.f16.f16.f16 "
               "{%0, %1, %2, %3, %4, %5, %6, %7, %8, %9, %10, %11, %12, %13}, "
               "{%14, %15, %16, %17}, %18, 0, 1, 1, 0;\n"
               : "=r"(d[0]), "=r"(d[1]), "=r"(d[2]), "=r"(d[3]), "=r"(d[4]), "=r"(d[5]), "=r"(d[6]), "=r"(d[7]),
                 "=r"(d[8]), "=r"(d[9]), "=r"(d[10]), "=r"(d[11]), "=r"(d[12]), "=r"(d[13])
               : "r"(a0), "r"(a1), "r"(a2), "r"(a3), "l"(desc));
}
__device__ __forceinline__ void hmma_n56(uint32_t (&d)[14], uint32_t a0, uint32_t a1, uint32_t a2, uint32_t a3, uint64_t desc) {
  asm volatile("wgmma.mma_async.sync.aligned.m64n56k16.f16.f16.f16 "
               "{%0, %1, %2, %3, %4, %5, %6, %7, %8, %9, %10, %11, %12, %13}, "
               "{%14, %15, %16, %17}, %18, 1, 1, 1, 0;\n"
               : "+r"(d[0]), "+r"(d[1]), "+r"(d[2]), "+r"(d[3]), "+r"(d[4]), "+r"(d[5]), "+r"(d[6]), "+r"(d[7]),
                 "+r"(d[8]), "+r"(d[9]), "+r"(d[10]), "+r"(d[11]), "+r"(d[12]), "+r"(d[13])
               : "r"(a0), "r"(a1), "r"(a2), "r"(a3), "l"(desc));
}
__device__ __forceinline__ void hmma_n192(uint32_t (&d)[48], uint32_t a0, uint32_t a1, uint32_t a2, uint32_t a3, uint64_t desc) {
  asm volatile("wgmma.mma_async.sync.aligned.m64n192k16.f16.f16.f16 "
               "{%0, %1, %2, %3, %4, %5, %6, %7, %8, %9, %10, %11, %12, %13, %14, %15, "
               "%16, %17, %18, %19, %20, %21, %22, %23, %24, %25, %26, %27, %28, %29, %30, %31, "
               "%32, %33, %34, %35, %36, %37, %38, %39, %40, %41, %42, %43, %44, %45, %46, %47}, "
               "{%48, %49, %50, %51}, %52, 1, 1, 1, 0;\n"
               : "+r"(d[0]), "+r"(d[1]), "+r"(d[2]), "+r"(d[3]), "+r"(d[4]), "+r"(d[5]), "+r"(d[6]), "+r"(d[7]),
                 "+r"(d[8]), "+r"(d[9]), "+r"(d[10]), "+r"(d[11]), "+r"(d[12]), "+r"(d[13]), "+r"(d[14]), "+r"(d[15]),
                 "+r"(d[16]), "+r"(d[17]), "+r"(d[18]), "+r"(d[19]), "+r"(d[20]), "+r"(d[21]), "+r"(d[22]), "+r"(d[23]),
                 "+r"(d[24]), "+r"(d[25]), "+r"(d[26]), "+r"(d[27]), "+r"(d[28]), "+r"(d[29]), "+r"(d[30]), "+r"(d[31]),
                 "+r"(d[32]), "+r"(d[33]), "+r"(d[34]), "+r"(d[35]), "+r"(d[36]), "+r"(d[37]), "+r"(d[38]), "+r"(d[39]),
                 "+r"(d[40]), "+r"(d[41]), "+r"(d[42]), "+r"(d[43]), "+r"(d[44]), "+r"(d[45]), "+r"(d[46]), "+r"(d[47])
               : "r"(a0), "r"(a1), "r"(a2), "r"(a3), "l"(desc));
}

__device__ __forceinline__ void wg_fence() { asm volatile("wgmma.fence.sync.aligned;\n" ::: "memory"); }
__device__ __forceinline__ void wg_commit() { asm volatile("wgmma.commit_group.sync.aligned;\n" ::: "memory"); }
template <int N> __device__ __forceinline__ void wg_wait() { asm volatile("wgmma.wait_group.sync.aligned %0;\n" ::"n"(N) : "memory"); }
__device__ __forceinline__ uint64_t make_desc(uint32_t addr, uint32_t lbo, uint32_t sbo) {
  return (uint64_t)((addr & 0x3FFFF) >> 4) | ((uint64_t)(lbo >> 4) << 16) | ((uint64_t)(sbo >> 4) << 32);
}
__device__ __forceinline__ uint64_t desc_add(uint64_t d, uint32_t bytes) { return d + (bytes >> 4); }
__device__ __forceinline__ uint64_t desc_at(uint64_t d, uint32_t bytes) {
  uint64_t r;
  asm volatile("mov.b64 %0, %1;" : "=l"(r) : "l"(d));
  return desc_add(r, bytes);
}

__device__ __forceinline__ void mbar_init(uint32_t bar, uint32_t count) {
  asm volatile("mbarrier.init.shared::cta.b64 [%0], %1;" ::"r"(bar), "r"(count) : "memory");
}
__device__ __forceinline__ void mbar_expect_tx(uint32_t bar, uint32_t bytes) {
  asm volatile("mbarrier.arrive.expect_tx.shared::cta.b64 _, [%0], %1;" ::"r"(bar), "r"(bytes) : "memory");
}
__device__ __forceinline__ void mbar_wait(uint32_t bar, uint32_t parity) {
  asm volatile("{\n.reg .pred p;\n.reg .u32 c;\n"
               "mbarrier.try_wait.parity.shared::cta.b64 p, [%0], %1;\n"
               "@p bra DONE;\n"
               "mov.u32 c, 0;\n"
               "SPIN:\n"
               "mbarrier.try_wait.parity.shared::cta.b64 p, [%0], %1, 4000;\n"
               "@p bra DONE;\n"
               "add.u32 c, c, 1;\n"
               "setp.lt.u32 p, c, 1048576;\n"
               "@!p trap;\n"
               "bra SPIN;\n"
               "DONE:\n}" ::"r"(bar), "r"(parity) : "memory");
}
__device__ __forceinline__ void bar_sync(uint32_t id) { asm volatile("bar.sync %0, 128;" ::"r"(id) : "memory"); }
__device__ __forceinline__ void mbar_arrive(uint32_t bar) { asm volatile("mbarrier.arrive.shared::cta.b64 _, [%0];" ::"r"(bar) : "memory"); }
__device__ __forceinline__ void warp_arrive(uint32_t bar, bool first) {
  __syncwarp();
  if (first) mbar_arrive(bar);
}
__device__ __forceinline__ void arrive_elected(uint32_t bar) {
  asm volatile("{\n.reg .pred p;\nelect.sync _|p, 0xffffffff;\n@p mbarrier.arrive.shared::cta.b64 _, [%0];\n}" ::"r"(bar) : "memory");
}
__device__ __forceinline__ void fence_async() { asm volatile("fence.proxy.async.shared::cta;" ::: "memory"); }
__device__ __forceinline__ uint32_t lds32(uint32_t a) {
  uint32_t v;
  asm volatile("ld.shared.b32 %0, [%1];" : "=r"(v) : "r"(a) : "memory");
  return v;
}
__device__ __forceinline__ void lds64(uint32_t a, uint32_t& v0, uint32_t& v1) {
  asm volatile("ld.shared.v2.b32 {%0, %1}, [%2];" : "=r"(v0), "=r"(v1) : "r"(a) : "memory");
}
__device__ __forceinline__ void sts32(uint32_t a, uint32_t v) { asm volatile("st.shared.b32 [%0], %1;" ::"r"(a), "r"(v) : "memory"); }
__device__ __forceinline__ void sts64(uint32_t a, uint32_t v0, uint32_t v1) {
  asm volatile("st.shared.v2.b32 [%0], {%1, %2};" ::"r"(a), "r"(v0), "r"(v1) : "memory");
}
__device__ __forceinline__ void sts32_if(bool on, uint32_t a, uint32_t v) {
  asm volatile("{\n.reg .pred p;\nsetp.ne.u32 p, %2, 0;\n@p st.shared.b32 [%0], %1;\n}" ::"r"(a), "r"(v), "r"((uint32_t)on) : "memory");
}
__device__ __forceinline__ void ldsm4(uint32_t a, uint32_t& r0, uint32_t& r1, uint32_t& r2, uint32_t& r3) {
  asm volatile("ldmatrix.sync.aligned.m8n8.x4.shared.b16 {%0, %1, %2, %3}, [%4];" : "=r"(r0), "=r"(r1), "=r"(r2), "=r"(r3) : "r"(a) : "memory");
}
__device__ __forceinline__ void stsm4(uint32_t a, uint32_t r0, uint32_t r1, uint32_t r2, uint32_t r3) {
  asm volatile("stmatrix.sync.aligned.m8n8.x4.shared.b16 [%0], {%1, %2, %3, %4};" ::"r"(a), "r"(r0), "r"(r1), "r"(r2), "r"(r3) : "memory");
}
__device__ __forceinline__ void stsm4_t(uint32_t a, uint32_t r0, uint32_t r1, uint32_t r2, uint32_t r3) {
  asm volatile("stmatrix.sync.aligned.m8n8.x4.trans.shared.b16 [%0], {%1, %2, %3, %4};" ::"r"(a), "r"(r0), "r"(r1), "r"(r2), "r"(r3) : "memory");
}
__device__ __forceinline__ uint32_t pack_bf16(float lo, float hi) {
  uint32_t r;
  asm("cvt.rn.bf16x2.f32 %0, %1, %2;" : "=r"(r) : "f"(hi), "f"(lo));
  return r;
}
__device__ __forceinline__ uint32_t pack_f16(float lo, float hi) {
  uint32_t r;
  asm("cvt.rn.f16x2.f32 %0, %1, %2;" : "=r"(r) : "f"(hi), "f"(lo));
  return r;
}
__device__ __forceinline__ float bf_lo(uint32_t v) { return __uint_as_float(v << 16); }
__device__ __forceinline__ float bf_hi(uint32_t v) { return __uint_as_float(v & 0xffff0000u); }
__device__ __forceinline__ float h_lo(uint32_t v) {
  float r;
  asm("{\n.reg .b16 l, h;\nmov.b32 {l, h}, %1;\ncvt.f32.f16 %0, l;\n}" : "=f"(r) : "r"(v));
  return r;
}
__device__ __forceinline__ float h_hi(uint32_t v) {
  float r;
  asm("{\n.reg .b16 l, h;\nmov.b32 {l, h}, %1;\ncvt.f32.f16 %0, h;\n}" : "=f"(r) : "r"(v));
  return r;
}
__device__ __forceinline__ uint32_t bf16x2_to_f16x2(uint32_t v) { return pack_f16(bf_lo(v), bf_hi(v)); }
__device__ __forceinline__ uint32_t f16x2_to_bf16x2(uint32_t v) { return pack_bf16(h_lo(v), h_hi(v)); }
__device__ __forceinline__ uint32_t bmul2(uint32_t a, uint32_t b) {
  uint32_t r;
  asm("mul.rn.bf16x2 %0, %1, %2;" : "=r"(r) : "r"(a), "r"(b));
  return r;
}
__device__ __forceinline__ uint32_t badd2(uint32_t a, uint32_t b) {
  uint32_t r;
  asm("add.rn.bf16x2 %0, %1, %2;" : "=r"(r) : "r"(a), "r"(b));
  return r;
}
__device__ __forceinline__ uint32_t bfma2(uint32_t a, uint32_t b, uint32_t c) {
  uint32_t r;
  asm("fma.rn.bf16x2 %0, %1, %2, %3;" : "=r"(r) : "r"(a), "r"(b), "r"(c));
  return r;
}
__device__ __forceinline__ uint32_t hadd2(uint32_t a, uint32_t b) {
  uint32_t d;
  asm("add.rn.f16x2 %0, %1, %2;" : "=r"(d) : "r"(a), "r"(b));
  return d;
}
__device__ __forceinline__ uint32_t hmax2(uint32_t a, uint32_t b) {
  uint32_t d;
  asm("max.f16x2 %0, %1, %2;" : "=r"(d) : "r"(a), "r"(b));
  return d;
}
__device__ __forceinline__ uint32_t hmul2(uint32_t a, uint32_t b) {
  uint32_t d;
  asm("mul.rn.f16x2 %0, %1, %2;" : "=r"(d) : "r"(a), "r"(b));
  return d;
}
__device__ __forceinline__ uint32_t hmul2_lo(uint32_t a, uint32_t r) {
  uint32_t d;
  asm("{\n.reg .b16 l, h;\n.reg .b32 t;\nmov.b32 {l, h}, %2;\nmov.b32 t, {l, l};\nmul.rn.f16x2 %0, %1, t;\n}" : "=r"(d) : "r"(a), "r"(r));
  return d;
}
__device__ __forceinline__ uint32_t hmul2_hi(uint32_t a, uint32_t r) {
  uint32_t d;
  asm("{\n.reg .b16 l, h;\n.reg .b32 t;\nmov.b32 {l, h}, %2;\nmov.b32 t, {h, h};\nmul.rn.f16x2 %0, %1, t;\n}" : "=r"(d) : "r"(a), "r"(r));
  return d;
}
__device__ __forceinline__ float rcp(float x) {
  float r;
  asm("rcp.approx.ftz.f32 %0, %1;" : "=f"(r) : "f"(x));
  return r;
}
__device__ __forceinline__ float rsqrt_fast(float x) {
  float r;
  asm("rsqrt.approx.ftz.f32 %0, %1;" : "=f"(r) : "f"(x));
  return r;
}
template <int N> __device__ __forceinline__ void fence_regs(uint32_t (&d)[N]) {
#pragma unroll
  for (int i = 0; i < N; i++) asm volatile("" : "+r"(d[i])::"memory");
}

__device__ __forceinline__ void row_stats(const uint32_t (&x)[48], bool odd, float& sum, float& squares) {
  float s0 = 0.f, q0 = 0.f, s1 = 0.f, q1 = 0.f;
#pragma unroll
  for (int i = 0; i < 48; i++) {
    const float lo = h_lo(x[i]), hi = h_hi(x[i]);
    if (i & 1) {
      s1 += lo; q1 = fmaf(lo, lo, q1);
      s1 += hi; q1 = fmaf(hi, hi, q1);
    } else {
      s0 += lo; q0 = fmaf(lo, lo, q0);
      s0 += hi; q0 = fmaf(hi, hi, q0);
    }
  }
  sum = (odd ? s1 : s0) + __shfl_xor_sync(0xffffffffu, odd ? s0 : s1, 1);
  squares = (odd ? q1 : q0) + __shfl_xor_sync(0xffffffffu, odd ? q0 : q1, 1);
  sum += __shfl_xor_sync(0xffffffffu, sum, 2);
  squares += __shfl_xor_sync(0xffffffffu, squares, 2);
}
__device__ __forceinline__ void lane_stats_packed(const uint32_t (&x)[48], uint32_t (&t)[2]) {
  uint32_t s[4] = {x[0], x[1], x[2], x[3]}, q[4];
#pragma unroll
  for (int r = 0; r < 4; r++) q[r] = hmul2(x[r], x[r]);
#pragma unroll
  for (int i = 4; i < 48; i++) {
    asm("add.rn.f16x2 %0, %0, %1;" : "+r"(s[i & 3]) : "r"(x[i]));
    asm("fma.rn.f16x2 %0, %1, %1, %0;" : "+r"(q[i & 3]) : "r"(x[i]));
  }
#pragma unroll
  for (int r = 0; r < 2; r++) {
    const uint32_t a = hadd2(s[r], s[r + 2]), b = hadd2(q[r], q[r + 2]);
    t[r] = hadd2(__byte_perm(a, b, 0x5410), __byte_perm(a, b, 0x7632));
  }
}
__device__ __forceinline__ uint32_t quad_stats_packed(const uint32_t (&t)[2], bool odd) {
  const uint32_t u = hadd2(__shfl_xor_sync(0xffffffffu, odd ? t[0] : t[1], 1), odd ? t[1] : t[0]);
  return hadd2(u, __shfl_xor_sync(0xffffffffu, u, 2));
}

__device__ __forceinline__ void store_k(const uint32_t (&k)[24], uint32_t k_st, bool full, bool first_row, uint32_t r) {
  if (full) {
#pragma unroll
    for (int j = 0; j < 12; j += 2)
      stsm4(k_st + (j / 6) * A_K1 + (j % 6) * K_CHUNK, hmul2_lo(k[2 * j], r), hmul2_hi(k[2 * j + 1], r), hmul2_lo(k[2 * j + 2], r),
            hmul2_hi(k[2 * j + 3], r));
  } else {
#pragma unroll
    for (int j = 0; j < 12; j++) sts32_if(first_row, k_st + (j / 6) * A_K1 + (j % 6) * K_CHUNK, hmul2_lo(k[2 * j], r));
    __syncwarp();
  }
}
template <int HALF> __device__ __forceinline__ uint32_t both(uint32_t v) {
  uint32_t d;
  if (HALF == 0) asm("{\n.reg .b16 l, h;\nmov.b32 {l, h}, %1;\nmov.b32 %0, {l, l};\n}" : "=r"(d) : "r"(v));
  else asm("{\n.reg .b16 l, h;\nmov.b32 {l, h}, %1;\nmov.b32 %0, {h, h};\n}" : "=r"(d) : "r"(v));
  return d;
}
__device__ __forceinline__ uint32_t exp2_scaled(uint32_t s, uint32_t c, uint32_t off) {
  uint32_t d;
  asm("{\n.reg .b32 t;\nfma.rn.f16x2 t, %1, %2, %3;\nex2.approx.f16x2 %0, t;\n}" : "=r"(d) : "r"(s), "r"(c), "r"(off));
  return d;
}
__device__ __forceinline__ uint32_t softmax_top(const uint32_t (&s)[14], uint32_t lane, uint32_t c, uint32_t& last) {
  last = __shfl_sync(0xffffffffu, __byte_perm(s[12], s[13], 0x5410), lane & 28);
  const uint32_t a = hmax2(hmax2(hmax2(s[0], s[2]), s[4]), hmax2(hmax2(s[6], s[8]), s[10]));
  const uint32_t b = hmax2(hmax2(hmax2(s[1], s[3]), s[5]), hmax2(hmax2(s[7], s[9]), s[11]));
  uint32_t m = hmax2(__byte_perm(a, b, 0x5410), __byte_perm(a, b, 0x7632));
  m = hmax2(m, __shfl_xor_sync(0xffffffffu, m, 1));
  m = hmax2(hmax2(m, last), __shfl_xor_sync(0xffffffffu, m, 2));
  return hmul2(m, c);
}
__device__ __forceinline__ void lds128(uint32_t a, uint32_t* v) {
  asm volatile("ld.shared.v4.b32 {%0, %1, %2, %3}, [%4];" : "=r"(v[0]), "=r"(v[1]), "=r"(v[2]), "=r"(v[3]) : "r"(a) : "memory");
}
template <int SUM, int VAL>
__device__ __forceinline__ void softmax_rows(const uint32_t (&s)[14], uint32_t top, uint32_t last, uint32_t c, uint32_t pad,
                                             uint32_t v_last, uint32_t (&pa)[12], uint32_t (&ov)[14]) {
  uint32_t off, v[6];
  lds128(v_last, v);
  lds64(v_last + 16, v[4], v[5]);
  asm("sub.rn.f16x2 %0, %1, %2;" : "=r"(off) : "r"(pad), "r"(top));
#pragma unroll
  for (int j = 0; j < 6; j++) {
    pa[2 * j] = exp2_scaled(s[2 * j], both<0>(c), both<0>(off));
    pa[2 * j + 1] = exp2_scaled(s[2 * j + 1], both<1>(c), both<1>(off));
  }
  const uint32_t p = exp2_scaled(last, c, off);
#pragma unroll
  for (int j = 0; j < 6; j++) {
    ov[VAL + 2 * j] = hmul2_lo(v[j], p);
    ov[VAL + 2 * j + 1] = hmul2_hi(v[j], p);
  }
  ov[SUM] = __byte_perm(p, p, 0x1010);
  ov[SUM + 1] = __byte_perm(p, p, 0x3232);
}
__device__ __forceinline__ void issue_pv(uint32_t (&ov)[14], const uint32_t (&pa)[12], uint64_t v_desc) {
#pragma unroll
  for (int k = 0; k < 3; k++) hmma_n56(ov, pa[4 * k], pa[4 * k + 1], pa[4 * k + 2], pa[4 * k + 3], desc_add(v_desc, k * 256));
}
__device__ __forceinline__ void sts128_if(bool on, uint32_t a, uint32_t v0, uint32_t v1, uint32_t v2, uint32_t v3) {
  asm volatile("{\n.reg .pred p;\nsetp.ne.u32 p, %5, 0;\n@p st.shared.v4.b32 [%0], {%1, %2, %3, %4};\n}"
               ::"r"(a), "r"(v0), "r"(v1), "r"(v2), "r"(v3), "r"((uint32_t)on) : "memory");
}
__device__ __forceinline__ void store_v(const uint32_t (&v)[24], uint32_t v_st, uint32_t v_last, bool full, bool first_row, uint32_t r) {
  if (full) {
#pragma unroll
    for (int j = 0; j < 12; j += 2)
      stsm4_t(v_st + (j / 6) * (A_V1 - A_V0) + (j % 6) * V_GROUP, hmul2_lo(v[2 * j], r), hmul2_hi(v[2 * j + 1], r), hmul2_lo(v[2 * j + 2], r),
              hmul2_hi(v[2 * j + 3], r));
  } else {
#pragma unroll
    for (int h = 0; h < 2; h++) {
      sts128_if(first_row, v_last + h * 128, hmul2_lo(v[12 * h], r), hmul2_lo(v[12 * h + 2], r), hmul2_lo(v[12 * h + 4], r),
                hmul2_lo(v[12 * h + 6], r));
      sts128_if(first_row, v_last + h * 128 + 16, hmul2_lo(v[12 * h + 8], r), hmul2_lo(v[12 * h + 10], r), 0u, 0u);
    }
    __syncwarp();
  }
}
__device__ __forceinline__ void issue_s(uint32_t (&s)[14], const uint32_t* qa, uint64_t k_desc) {
  hmma_n56_first(s, qa[0], qa[1], qa[2], qa[3], k_desc);
#pragma unroll
  for (int k = 1; k < 3; k++) hmma_n56(s, qa[4 * k], qa[4 * k + 1], qa[4 * k + 2], qa[4 * k + 3], desc_add(k_desc, k * 2 * K_CHUNK));
}
template <int SUM, int VAL>
__device__ __forceinline__ void pack_o(const uint32_t (&ov)[14], uint32_t* o) {
  const uint32_t p = pack_f16(rcp(fmaxf(h_lo(ov[SUM]), 0.5f)), rcp(fmaxf(h_lo(ov[SUM + 1]), 0.5f)));
#pragma unroll
  for (int j = 0; j < 6; j++) {
    o[2 * j] = hmul2_lo(ov[VAL + 2 * j], p);
    o[2 * j + 1] = hmul2_hi(ov[VAL + 2 * j + 1], p);
  }
}
template <int FIRST>
__device__ __forceinline__ void issue_half(uint32_t (&d)[24], const uint32_t (&x)[48], uint64_t desc) {
  if (FIRST == 2) hmma_n96_over(d, x[0], x[1], x[2], x[3], desc);
  if (FIRST == 1) hmma_n96_first(d, x[0], x[1], x[2], x[3], desc);
#pragma unroll
  for (int s = FIRST ? 1 : 6; s < (FIRST ? 6 : 12); s++) hmma_n96(d, x[4 * s], x[4 * s + 1], x[4 * s + 2], x[4 * s + 3], desc_add(desc, s * W_STEP));
}
template <int N>
__device__ __forceinline__ void issue_out(uint32_t (&d)[48], const uint32_t* o, uint64_t desc) {
#pragma unroll
  for (int s = 0; s < N; s++) hmma_n192(d, o[4 * s], o[4 * s + 1], o[4 * s + 2], o[4 * s + 3], desc_add(desc, s * WO_STEP));
}

__device__ __forceinline__ void mma_bf16(float (&c)[4], uint32_t a0, uint32_t a1, uint32_t a2, uint32_t a3, uint32_t b0, uint32_t b1) {
  asm("mma.sync.aligned.m16n8k16.row.col.f32.bf16.bf16.f32 {%0, %1, %2, %3}, {%4, %5, %6, %7}, {%8, %9}, {%0, %1, %2, %3};"
      : "+f"(c[0]), "+f"(c[1]), "+f"(c[2]), "+f"(c[3]) : "r"(a0), "r"(a1), "r"(a2), "r"(a3), "r"(b0), "r"(b1));
}
__device__ __forceinline__ void mma_bf16_k8(float (&d)[4], uint32_t a0, uint32_t a1, uint32_t b, const float (&c)[4]) {
  asm("mma.sync.aligned.m16n8k8.row.col.f32.bf16.bf16.f32 {%0, %1, %2, %3}, {%4, %5}, {%6}, {%7, %8, %9, %10};"
      : "=f"(d[0]), "=f"(d[1]), "=f"(d[2]), "=f"(d[3]) : "r"(a0), "r"(a1), "r"(b), "f"(c[0]), "f"(c[1]), "f"(c[2]), "f"(c[3]));
}
__device__ __forceinline__ bool on_diagonal(uint32_t lane) { return (lane & 3) == (lane >> 3); }
__device__ __forceinline__ float column_stats(const uint32_t (&v)[24], uint32_t lane, uint32_t& hi, uint32_t& lo) {
  float sum[2][4] = {}, sq[2][4] = {}, sr[2][4] = {};
#pragma unroll
  for (int c = 0; c < 24; c += 4) mma_bf16(sum[(c >> 2) & 1], v[c], v[c + 1], v[c + 2], v[c + 3], 0x3F803F80u, 0x3F803F80u);
#pragma unroll
  for (int c = 0; c < 24; c += 2) {
    mma_bf16_k8(sq[(c >> 1) & 1], v[c], v[c + 1], v[c], sq[(c >> 1) & 1]);
    mma_bf16_k8(sr[(c >> 1) & 1], v[c], v[c + 1], v[c + 1], sr[(c >> 1) & 1]);
  }
  const float total = (sum[0][0] + sum[0][2]) + (sum[1][0] + sum[1][2]), mean = total * (1.f / 192.f);
  const bool diag = on_diagonal(lane);
  const float n2 = (lane & 4) ? (sq[0][1] + sq[1][1]) + (sr[0][3] + sr[1][3]) : (sq[0][0] + sq[1][0]) + (sr[0][2] + sr[1][2]);
  hi = diag ? __float_as_uint(n2) : 0u;
  lo = __float_as_uint((diag && n2 > 0.f) ? fmaxf(fmaf(-total, mean, n2), 0.f) : INFINITY);
  return mean;
}
__device__ __forceinline__ uint32_t warp_max_abs(const uint32_t (&v)[8]) {
  uint32_t m = v[0];
#pragma unroll
  for (int c = 1; c < 8; c++) asm("max.NaN.xorsign.abs.bf16x2 %0, %0, %1;" : "+r"(m) : "r"(v[c]));
  return __reduce_max_sync(0xffffffffu, max(m & 0x7fffu, (m >> 16) & 0x7fffu));
}
__device__ __forceinline__ bool norms_in_range(uint32_t hi, uint32_t lo) {
  return hi - 0x08800000u <= 0x7B000000u - 0x08800000u && lo >= hi - (12u << 23);
}
__device__ __forceinline__ int norm_exponent(uint32_t n2) { return (int)(0x453B8000u - n2) >> 24; }
__device__ __forceinline__ void scale_to_f16(uint32_t (&v)[8], uint32_t lane, int e, float mean) {
  const uint32_t ident = on_diagonal(lane) ? (uint32_t)(e + 127) << ((lane & 4) ? 23 : 7) : 0u;
  const float c0 = -mean * __uint_as_float((uint32_t)(e + 127) << 23), c[4] = {c0, c0, c0, c0};
#pragma unroll
  for (int i = 0; i < 8; i += 2) {
    float d[4];
    mma_bf16_k8(d, v[i], v[i + 1], ident, c);
    v[i] = bf16x2_to_f16x2(pack_bf16(d[0], d[1]));
    v[i + 1] = bf16x2_to_f16x2(pack_bf16(d[2], d[3]));
  }
}
__device__ __forceinline__ float pow2(int e) { return __uint_as_float((uint32_t)(min(max(e, -126), 127) + 127) << 23); }

constexpr uint32_t kUnits = 24;
constexpr uint32_t RAW_O = W_PART, RAW_RED = RAW_O + 32 * 384;
__device__ __forceinline__ void tile_load(uint32_t dst, const CUtensorMap* tm, uint32_t c0, uint32_t c1, uint32_t bar) {
  asm volatile("{\n.reg .pred p;\nelect.sync _|p, 0xffffffff;\n"
               "@p cp.async.bulk.tensor.2d.shared::cluster.global.tile.mbarrier::complete_tx::bytes [%0], [%1, {%2, %3}], [%4];\n}"
               ::"r"(dst), "l"(tm), "r"(c0), "r"(c1), "r"(bar) : "memory");
}
__device__ __forceinline__ void request_unit(uint32_t u, uint32_t lane, uint32_t raw, uint32_t bar, const CUtensorMap* tmw,
                                             const CUtensorMap* tmwo) {
  const bool is_o = (u & 7) >= 6;
  const uint32_t pair = is_o ? u & 1 : (u & 7) / 3, part = is_o ? 1 : (u & 7) % 3;
#pragma unroll
  for (uint32_t i = 0; i < 3; i++) tile_load(raw + i * (192 * 64), tmw, ((part + 1) % 3) * 192 + pair * 96 + 32 * i, 0, bar);
  if (is_o) {
#pragma unroll
    for (uint32_t i = 0; i < 6; i++) tile_load(raw + RAW_O + i * (32 * 64), tmwo, 32 * i, pair * 96 + (u >> 3) * 32, bar);
  }
  if (lane == 0) mbar_expect_tx(bar, is_o ? W_PART + 32 * 384 : W_PART);
  __syncwarp();
}
__device__ __forceinline__ void ldsm4_t(uint32_t a, uint32_t* v) {
  asm volatile("ldmatrix.sync.aligned.m8n8.x4.trans.shared.b16 {%0, %1, %2, %3}, [%4];" : "=r"(v[0]), "=r"(v[1]), "=r"(v[2]), "=r"(v[3]) : "r"(a) : "memory");
}
__device__ __forceinline__ void prepare_unit(uint32_t u, uint32_t wid, uint32_t lane, uint32_t raw, Scratch* scr) {
  const bool is_o = (u & 7) >= 6;
  const uint32_t third = u >> 3;
  uint32_t v[24], w[8];
  const uint32_t src = raw + (wid >> 2) * (192 * 64) + lane * 64 + (((wid ^ (lane >> 1)) & 3) << 4);
#pragma unroll
  for (int m = 0; m < 6; m++) ldsm4_t(src + m * (32 * 64), &v[4 * m]);
  uint32_t hi, lo, top = 0;
  const float mean = column_stats(v, lane, hi, lo);
  if (is_o) {
#pragma unroll
    for (int m = 0; m < 2; m++)
      ldsm4_t(raw + RAW_O + (wid >> 1) * (32 * 64) + lane * 64 + ((((2 * wid + m) ^ (lane >> 1)) & 3) << 4), &w[4 * m]);
    top = warp_max_abs(w);
  } else {
#pragma unroll
    for (int m = 0; m < 2; m++) ldsm4_t(src + (2 * third + m) * (32 * 64), &w[4 * m]);
  }
  hi = __reduce_max_sync(0xffffffffu, hi);
  lo = __reduce_min_sync(0xffffffffu, lo);
  if (lane == 0) {
    sts64(raw + RAW_RED + wid * 16, hi, lo);
    sts32(raw + RAW_RED + wid * 16 + 8, top);
  }
  asm volatile("bar.sync 4, 384;" ::: "memory");
  lds64(raw + RAW_RED + (lane % 12) * 16, hi, lo);
  top = lds32(raw + RAW_RED + (lane % 12) * 16 + 8);
  hi = __reduce_max_sync(0xffffffffu, hi);
  lo = __reduce_min_sync(0xffffffffu, lo);
  top = __reduce_max_sync(0xffffffffu, top);
  const int e = norm_exponent(hi);
  scale_to_f16(w, lane, is_o ? -e : e - 4, is_o ? 0.f : mean);
  const uint32_t mat = lane >> 3, at = (mat & 1) * 128 + (lane & 7) * 16;
#pragma unroll
  for (int m = 0; m < 2; m++)
    stsm4(raw + at + (is_o ? (mat >> 1) * WO_STEP + (2 * wid + m) * 256 : (2 * m + (mat >> 1)) * W_STEP + wid * 256), w[4 * m], w[4 * m + 1],
          w[4 * m + 2], w[4 * m + 3]);
  fence_async();
  asm volatile("bar.sync 4, 384;" ::: "memory");
  if (wid == 0 && lane == 0) {
    asm volatile("cp.async.bulk.global.shared::cta.bulk_group [%0], [%1], %2;\ncp.async.bulk.commit_group;"
                 ::"l"(scr->weights + (u & 7) * W_PART + third * (W_PART / 3)), "r"(raw), "n"(W_PART / 3) : "memory");
    const bool bad = is_o ? !(__uint_as_float(top << 16) * pow2(-e) <= 0.25f) : !norms_in_range(hi, lo);
    const uint32_t exponent = (!is_o && third == 0 && u % 3 != 1) ? (uint32_t)(e + 64) << (u < 3 ? 10 : 19) : 0u;
    asm volatile("cp.async.bulk.wait_group 0;" ::: "memory");
    asm volatile("red.relaxed.gpu.global.add.u32 [%0], %1;" ::"l"(&scr->ready), "r"(bad ? 33u : 1u + exponent) : "memory");
  }
  __syncwarp();
}

constexpr uint32_t REDO_BYTES = 75776;
static_assert(3 * REDO_BYTES <= OFF_TAIL && (3 * 49 * 192 + 49 * 144) * 2 <= REDO_BYTES, "redo scratch");
__device__ __forceinline__ float round_bf16(float x) { return __bfloat162float(__float2bfloat16(x)); }
__device__ __forceinline__ void redo_window(int c0, int y0, int t, uint32_t bar, uint8_t* scratch, const __nv_bfloat16* x,
                                            const __nv_bfloat16* dw, const __nv_bfloat16* wqkv, const __nv_bfloat16* wo,
                                            __nv_bfloat16* out) {
  __nv_bfloat16* x0 = reinterpret_cast<__nv_bfloat16*>(scratch);
  __nv_bfloat16* h = x0 + 49 * 192;
  __nv_bfloat16* o = h + 49 * 192;
  __nv_bfloat16* qkv = o + 49 * 192;
  bar_sync(bar);
#pragma unroll 1
  for (int i = t; i < 49 * 192; i += 128) {
    const int tok = i / 192, c = i % 192, y = y0 + tok / 7, xx = c0 + tok % 7;
    float pe = 0.f;
#pragma unroll 1
    for (int k = 0; k < 9; k++) {
      const int yy = y + k / 3 - 1, xj = xx + k % 3 - 1;
      const bool in = (uint32_t)yy < kImg && (uint32_t)xj < kImg;
      const float v = in ? __bfloat162float(x[((size_t)yy * kImg + xj) * kCh + c]) : 0.f;
      pe = round_bf16(pe + round_bf16(v * __bfloat162float(dw[k * kCh + c])));
    }
    x0[i] = __float2bfloat16(__bfloat162float(x[((size_t)y * kImg + xx) * kCh + c]) + pe);
  }
  bar_sync(bar);
  if (t < 49) {
    float s = 0.f, v = 0.f;
#pragma unroll 1
    for (int c = 0; c < 192; c++) s += __bfloat162float(x0[t * 192 + c]);
    const float mean = s * (1.f / 192.f);
#pragma unroll 1
    for (int c = 0; c < 192; c++) {
      const float d = __bfloat162float(x0[t * 192 + c]) - mean;
      v = fmaf(d, d, v);
    }
    const float m = round_bf16(mean), sd = round_bf16(sqrtf(round_bf16(round_bf16(v * (1.f / 192.f)) + 1e-5f)));
#pragma unroll 1
    for (int c = 0; c < 192; c++) h[t * 192 + c] = __float2bfloat16(round_bf16(__bfloat162float(x0[t * 192 + c]) - m) / sd);
  }
#pragma unroll 1
  for (int head = 0; head < 4; head++) {
    bar_sync(bar);
#pragma unroll 1
    for (int i = t; i < 49 * 144; i += 128) {
      const int tok = i / 144, n = i % 144, col = (n / 48) * 192 + head * 48 + n % 48;
      float a = 0.f;
#pragma unroll 4
      for (int c = 0; c < 192; c++) a = fmaf(__bfloat162float(h[tok * 192 + c]), __bfloat162float(wqkv[c * 576 + col]), a);
      qkv[i] = __float2bfloat16(a);
    }
    bar_sync(bar);
    if (t < 49) {
      float p[49], m = -INFINITY, s = 0.f;
#pragma unroll
      for (int b = 0; b < 49; b++) {
        float a = 0.f;
#pragma unroll 4
        for (int d = 0; d < 48; d++) a = fmaf(__bfloat162float(qkv[t * 144 + d]), __bfloat162float(qkv[b * 144 + 48 + d]), a);
        p[b] = round_bf16(round_bf16(a) * 0.14433757f);
        m = fmaxf(m, p[b]);
      }
#pragma unroll
      for (int b = 0; b < 49; b++) {
        p[b] = expf(p[b] - m);
        s += p[b];
      }
#pragma unroll
      for (int b = 0; b < 49; b++) p[b] = round_bf16(p[b] / s);
#pragma unroll 1
      for (int d = 0; d < 48; d++) {
        float a = 0.f;
#pragma unroll
        for (int b = 0; b < 49; b++) a = fmaf(p[b], __bfloat162float(qkv[b * 144 + 96 + d]), a);
        o[t * 192 + head * 48 + d] = __float2bfloat16(a);
      }
    }
  }
  bar_sync(bar);
#pragma unroll 1
  for (int i = t; i < 49 * 192; i += 128) {
    const int tok = i / 192, n = i % 192;
    float a = 0.f;
#pragma unroll 4
    for (int c = 0; c < 192; c++) a = fmaf(__bfloat162float(o[tok * 192 + c]), __bfloat162float(wo[c * kCh + n]), a);
    out[((size_t)(y0 + tok / 7) * kImg + c0 + tok % 7) * kCh + n] = __float2bfloat16(__bfloat162float(x0[tok * 192 + n]) + round_bf16(a));
  }
}

__device__ __forceinline__ uint32_t fresh_tid() {
  uint32_t t;
  asm volatile("mov.u32 %0, %%tid.x;" : "=r"(t));
  return t;
}
struct Split {
  uint32_t top, rows, alone, share, pool;
  uint32_t magic[2];
};
struct Windows {
  uint32_t first, count, alone, jump, height, row0, magic;
  __device__ __forceinline__ explicit Windows(const Split& s) {
    uint32_t b;
    asm volatile("mov.u32 %0, %%ctaid.x;" : "=r"(b));
    const bool upper = b < s.top;
    const uint32_t i = upper ? 0 : b - s.top;
    height = upper ? s.rows : kWinPerCol - s.rows;
    row0 = upper ? 0 : s.rows;
    magic = upper ? s.magic[0] : s.magic[1];
    alone = upper ? s.rows : s.alone;
    first = upper ? b * s.rows : i * s.alone;
    count = upper ? s.rows : s.alone + s.share;
    jump = (gridDim.x - s.top - 1 - i) * s.alone + i * s.share;
  }
  __device__ __forceinline__ bool at(uint32_t j, uint32_t& col, uint32_t& row) const {
    const uint32_t v = first + j + (j >= alone ? jump : 0);
    col = (v * magic) >> 20;
    row = v - col * height + row0;
    return row == row0 || j == alone;
  }
  __device__ __forceinline__ void at(uint32_t j, uint32_t& col, uint32_t& row, uint32_t extra) const {
    at(j, col, row);
    if (j == count) {
      col = extra & 255;
      row = extra >> 8;
    }
  }
};
template <uint32_t BYTES>
__device__ __forceinline__ void load_rows(uint32_t dst, const CUtensorMap* tm, uint32_t ch, int x, int y, uint32_t bar) {
  asm volatile("{\n.reg .pred p;\nelect.sync _|p, 0xffffffff;\n"
               "@p mbarrier.arrive.expect_tx.shared::cta.b64 _, [%5], %6;\n"
               "@p cp.async.bulk.tensor.3d.shared::cluster.global.tile.mbarrier::complete_tx::bytes [%0], [%1, {%2, %3, %4}], [%5];\n}"
               ::"r"(dst), "l"(tm), "r"(ch), "r"(x), "r"(y), "r"(bar), "n"(BYTES) : "memory");
}
__device__ __forceinline__ void load_part(uint32_t dst, const void* src, uint32_t bar) {
  asm volatile("{\n.reg .pred p;\nelect.sync _|p, 0xffffffff;\n@p mbarrier.arrive.expect_tx.shared::cta.b64 _, [%3], %2;\n"
               "@p cp.async.bulk.shared::cluster.global.mbarrier::complete_tx::bytes [%0], [%1], %2, [%3];\n}"
               ::"r"(dst), "l"(src), "n"(W_PART), "r"(bar) : "memory");
}
__device__ __forceinline__ void prefetch_box(const CUtensorMap* tm, int x, int y) {
  asm volatile("cp.async.bulk.prefetch.tensor.3d.L2.global.tile [%0, {%1, %2, %3}];" ::"l"(tm), "r"(0), "r"(x), "r"(y) : "memory");
}
__device__ __forceinline__ void prefetch_rows(const CUtensorMap* tm, int x, int y) {
  asm volatile("{\n.reg .pred p;\nelect.sync _|p, 0xffffffff;\n"
               "@p cp.async.bulk.prefetch.tensor.3d.L2.global.tile [%0, {%1, %2, %3}];\n}" ::"l"(tm), "r"(0), "r"(x), "r"(y) : "memory");
}
__device__ __forceinline__ void store_window(const CUtensorMap* tm, uint32_t src, uint32_t x, uint32_t y) {
  asm volatile("{\n.reg .pred p;\n.reg .u32 a;\nelect.sync _|p, 0xffffffff;\n"
               "add.u32 a, %1, 0;\n@p cp.async.bulk.tensor.3d.global.shared::cta.tile.bulk_group [%0, {0, %2, %3}], [a];\n"
               "add.u32 a, %1, 3328;\n@p cp.async.bulk.tensor.3d.global.shared::cta.tile.bulk_group [%0, {32, %2, %3}], [a];\n"
               "add.u32 a, %1, 6656;\n@p cp.async.bulk.tensor.3d.global.shared::cta.tile.bulk_group [%0, {64, %2, %3}], [a];\n"
               "add.u32 a, %1, 9984;\n@p cp.async.bulk.tensor.3d.global.shared::cta.tile.bulk_group [%0, {96, %2, %3}], [a];\n"
               "add.u32 a, %1, 13312;\n@p cp.async.bulk.tensor.3d.global.shared::cta.tile.bulk_group [%0, {128, %2, %3}], [a];\n"
               "add.u32 a, %1, 16640;\n@p cp.async.bulk.tensor.3d.global.shared::cta.tile.bulk_group [%0, {160, %2, %3}], [a];\n"
               "cp.async.bulk.commit_group;\n}" ::"l"(tm), "r"(src), "r"(x), "r"(y) : "memory");
}
static_assert(OUT_GROUP == 3328, "store_window");

template <int N> struct Int { static constexpr int value = N; };
struct Conv {
  uint32_t wt[9], prev[9], acc[7];
  __device__ __forceinline__ void begin(const uint32_t (&cur)[9]) {
#pragma unroll
    for (int x = 0; x < 7; x++) {
      uint32_t a = bmul2(prev[x], wt[0]);
      a = bfma2(prev[x + 1], wt[1], a);
      a = bfma2(prev[x + 2], wt[2], a);
#pragma unroll
      for (int t = 0; t < 3; t++) a = bfma2(cur[x + t], wt[3 + t], a);
      acc[x] = a;
    }
#pragma unroll
    for (int x = 0; x < 9; x++) prev[x] = cur[x];
  }
  __device__ __forceinline__ void start_column(uint32_t slot0, uint32_t bar0, uint32_t parity0, uint32_t slot1, uint32_t bar1,
                                               uint32_t parity1, uint32_t lane, uint32_t dump, bool request, const CUtensorMap* tm,
                                               uint32_t ch, int x, int y) {
    uint32_t cur[9];
    mbar_wait(bar0, parity0);
#pragma unroll
    for (int i = 0; i < 9; i++) prev[i] = lds32(slot0 + lane * 4 + i * 128);
    sts32(dump, prev[0] ^ prev[1] ^ prev[2] ^ prev[3] ^ prev[4] ^ prev[5] ^ prev[6] ^ prev[7] ^ prev[8]);
    if (request) load_rows<HALO_ROW>(slot0, tm, ch, x, y, bar0);
    mbar_wait(bar1, parity1);
#pragma unroll
    for (int i = 0; i < 9; i++) cur[i] = lds32(slot1 + lane * 4 + i * 128);
    begin(cur);
    sts32(dump, acc[0] ^ acc[3] ^ acc[6]);
    if (request) load_rows<HALO_ROW>(slot1, tm, ch, x, y + 1, bar1);
  }
  __device__ __forceinline__ void row_at(uint32_t src, uint32_t dst, uint32_t t) {
    uint32_t cur[9];
#pragma unroll
    for (int x = 0; x < 9; x++) cur[x] = lds32(src + x * 128);
#pragma unroll
    for (int x = 0; x < 7; x++) {
      uint32_t a = acc[x];
#pragma unroll
      for (int i = 0; i < 3; i++) a = bfma2(cur[x + i], wt[6 + i], a);
      sts32((dst ^ (((t + x) & 7) << 4)) + x * 128, bf16x2_to_f16x2(badd2(prev[x + 1], a)));
    }
    begin(cur);
  }
  template <int R>
  __device__ __forceinline__ void row(uint32_t src, uint32_t dst, uint32_t at) {
    uint32_t cur[9];
#pragma unroll
    for (int x = 0; x < 9; x++) cur[x] = lds32(src + x * 128);
#pragma unroll
    for (int x = 0; x < 7; x++) {
      uint32_t a = acc[x];
#pragma unroll
      for (int t = 0; t < 3; t++) a = bfma2(cur[x + t], wt[6 + t], a);
      sts32((dst ^ (((R * 7 + x) & 7) << 4)) + at + x * 128, bf16x2_to_f16x2(badd2(prev[x + 1], a)));
    }
    begin(cur);
  }
};

__global__ void __launch_bounds__(512, 1)
davit_window_attn_kernel(const __grid_constant__ CUtensorMap tm1, const __grid_constant__ CUtensorMap tm7c,
                         const __grid_constant__ CUtensorMap tm7, const __grid_constant__ CUtensorMap tmo,
                         const __grid_constant__ CUtensorMap tmw, const __grid_constant__ CUtensorMap tmwo,
                         const __nv_bfloat16* __restrict__ dw, const __nv_bfloat16* __restrict__ x_raw,
                         const __nv_bfloat16* __restrict__ wqkv_raw, const __nv_bfloat16* __restrict__ wo_raw,
                         __nv_bfloat16* __restrict__ out, Scratch* __restrict__ scr, const Split split) {
  extern __shared__ __align__(1024) uint8_t smem_raw[];
  const uint32_t sb = (uint32_t)__cvta_generic_to_shared(smem_raw);
  const uint32_t tail = sb + OFF_TAIL;
  uint32_t wt[9];
  {
    const uint32_t tid = threadIdx.x;
    const uint32_t wid = __shfl_sync(0xffffffffu, tid >> 5, 0), lane = tid & 31;
    if (wid > 12) {
      const uint32_t chunk = wid - 13, hbar = tail + T_HALO + 24 * chunk, rbar = tail + T_ROW + 16 * chunk;
      if (lane == 0) {
        mbar_init(hbar, 1);
        mbar_init(hbar + 8, 1);
        mbar_init(hbar + 16, 1);
        mbar_init(rbar, 1);
        mbar_init(rbar + 8, 1);
        if (wid == 13) mbar_init(tail + T_RAW, 1);
        if (wid == 14) mbar_init(tail + T_CLAIM, 1);
        fence_async();
      }
      __syncwarp();
      if (blockIdx.x < kUnits) {
        if (wid == 13) request_unit(blockIdx.x, lane, sb + OFF_RING, tail + T_RAW, &tmw, &tmwo);
        asm volatile("bar.sync 5, 96;" ::: "memory");
      }
      uint32_t col, row;
      Windows(split).at(0, col, row);
      const int x = (int)col * 7 - 1, y = (int)row * 7;
      const uint32_t halo = sb + OFF_HALO + chunk * 3 * HALO_ROW;
      load_rows<HALO_ROW>(halo, &tm1, chunk * 64, x, y - 1, hbar);
      load_rows<HALO_ROW>(halo + HALO_ROW, &tm1, chunk * 64, x, y, hbar + 8);
      load_rows<7 * HALO_ROW>(sb + OFF_KV + chunk * 7 * HALO_ROW, &tm7c, chunk * 64, x, y + 1, rbar);
#pragma unroll
      for (int i = 0; i < 9; i++) wt[i] = __ldg(reinterpret_cast<const uint32_t*>(dw) + i * (kCh / 2) + chunk * 32 + lane);
    } else {
      if (lane == 0 && wid < 12) {
        const uint32_t i = 2 * wid, counts = (uint32_t)((wid < 8 ? 0x4144444333CCC111ull >> (8 * wid) : 0x01444144u >> (8 * wid - 64)));
        mbar_init(tail + 8 * (i < 11 ? i : i + 9), counts & 15);
        if (wid < 11) mbar_init(tail + 8 * (i < 10 ? i + 1 : i + 10), (counts >> 4) & 15);
        fence_async();
      }
      if (wid == 12) {
        for (uint32_t line = blockIdx.x + gridDim.x * lane; line < 2304; line += gridDim.x * 32) {
          const uint8_t* p = (line < 1728) ? reinterpret_cast<const uint8_t*>(wqkv_raw) + line * 128
                                           : reinterpret_cast<const uint8_t*>(wo_raw) + (line - 1728) * 128;
          asm volatile("prefetch.global.L2 [%0];" ::"l"(p));
        }
        if (lane < 7) sts32(tail + T_ZERO + 4 * lane, 0u);
      }
    }
    __syncthreads();
    if (wid < 12) {
#pragma unroll 1
      for (uint32_t u = blockIdx.x, i = 0; u < kUnits; u += gridDim.x, i++) {
        if (i) {
          asm volatile("bar.sync 4, 384;" ::: "memory");
          if (wid == 0) request_unit(u, lane, sb + OFF_RING, tail + T_RAW, &tmw, &tmwo);
        }
        mbar_wait(tail + T_RAW, i & 1);
        prepare_unit(u, wid, lane, sb + OFF_RING, scr);
      }
    }
  }

  if (threadIdx.x >= 384) {
    asm volatile("setmaxnreg.dec.sync.aligned.u32 %0;" ::"n"(56));
    const uint32_t tid = fresh_tid();
    const uint32_t warp = __shfl_sync(0xffffffffu, (tid >> 5) & 3, 0), lane = tid & 31;
    if (warp == 0) {
      const Windows win(split);
      uint32_t spins = 0, seen;
      do {
        asm volatile("ld.acquire.gpu.global.u32 %0, [%1];" : "=r"(seen) : "l"(&scr->ready) : "memory");
        seen = __shfl_sync(0xffffffffu, seen, 0);
        if (++spins > (1u << 22)) __trap();
      } while ((seen & 31) != kUnits);
      asm volatile("fence.proxy.async.global;" ::: "memory");
      {
        const int e0 = (int)((seen >> 10) & 511) - 128, e1 = (int)(seen >> 19) - 128;
        sts32(tail + T_SCALE, pack_f16(fmaxf(0.20823509f * pow2(9 - e0), 0x1p-24f), fmaxf(0.20823509f * pow2(9 - e1), 0x1p-24f)));
        if ((seen & 0x3E0u) || e0 < 1 || e1 < 1) sts32(tail + T_ALL, 1u);
        __syncwarp();
      }
#pragma unroll
      for (uint32_t s = 0; s < 3; s++) load_part(sb + OFF_RING + s * W_PART, scr->weights + s * W_PART, tail + T_FULL + 8 * s);
#pragma unroll 1
      for (uint32_t j = 2; j < 4; j++) {
        uint32_t col, row;
        const bool fresh = win.at(j, col, row);
        if (j == 3 || fresh) prefetch_rows(&tm7, 7 * col - 1, 7 * row + 1);
        if (fresh) prefetch_rows(&tm7, 7 * col - 1, 7 * row - 1);
      }
      if (lane == 0 && atomicInc(&scr->passed, gridDim.x - 1) == gridDim.x - 1) scr->ready = 0;
      __syncwarp();
      const uint32_t uses = 8 * (win.count / 3 + 1);
#pragma unroll 1
      for (uint32_t u = 3; u < uses; u++) {
        const uint32_t m = u / 3, s = u - 3 * m;
        mbar_wait(tail + T_EMPTY + 8 * s, (m & 1) ^ 1);
        load_part(sb + OFF_RING + s * W_PART, scr->weights + (u & 7) * W_PART, tail + T_FULL + 8 * s);
      }
#pragma unroll 1
      for (uint32_t u = uses - 3; u < uses; u++) mbar_wait(tail + T_FULL + 8 * (u % 3), (u / 3) & 1);
    } else {
      Conv cv;
#pragma unroll
      for (int i = 0; i < 9; i++) cv.wt[i] = wt[i];
      {
        const uint32_t chunk = warp - 1, halo = sb + OFF_HALO + chunk * 3 * HALO_ROW, hbar = tail + T_HALO + 24 * chunk;
        const Windows win(split);
        uint32_t col, row, cn, rn;
        const uint32_t staged = (win.count > 1 && !win.at(1, col, row)) ? 2 : 1;
        const bool fresh = win.at(staged, cn, rn);
        const int xn = 7 * cn - 1, yn = fresh ? 7 * rn - 1 : 7 * rn + 1;
        if (staged < win.count) load_rows<HALO_ROW>(halo + 2 * HALO_ROW, &tm1, chunk * 64, xn, yn, hbar + 16);
        cv.start_column(halo, hbar, 0, halo + HALO_ROW, hbar + 8, 0, lane, tail + T_DUMP, staged < win.count, &tm1, chunk * 64, xn, yn + 1);
        if (staged == 2)
          load_rows<7 * HALO_ROW>(sb + OFF_KV + (3 + chunk) * 7 * HALO_ROW, &tm7c, chunk * 64, 7 * col - 1, 7 * row + 1,
                                  tail + T_ROW + 16 * chunk + 8);
#pragma unroll 1
        for (uint32_t i = 0; i < staged; i++) {
          mbar_wait(tail + T_ROW + 16 * chunk + 8 * i, 0);
#pragma unroll 1
          for (uint32_t r = 0; r < 7; r++)
            cv.row_at(sb + OFF_KV + ((3 * i + chunk) * 7 + r) * HALO_ROW + lane * 4,
                      sb + OFF_X0 + chunk * X0_CHUNK + lane * 4 + (7 * i + r) * X0_ROW, 7 * r);
          __syncwarp();
          arrive_elected(tail + T_X0FULL + 8 * i);
          if (i == 0 && chunk == 0 && staged < win.count) prefetch_rows(&tm7, xn, yn + 3);
        }
      }
      const uint32_t chunk = __shfl_sync(0xffffffffu, (fresh_tid() >> 5) & 3, 0) - 1, ch = chunk * 64;
      const uint32_t halo = sb + OFF_HALO + chunk * 3 * HALO_ROW, hbar = tail + T_HALO + 24 * chunk;
      const uint32_t src = halo + lane * 4, dst = sb + OFF_X0 + chunk * X0_CHUNK + lane * 4;
      const Windows win(split);
      uint32_t count = win.count;
      uint32_t col, row;
      const uint32_t staged = (count > 1 && !win.at(1, col, row)) ? 2 : 1;
      bool fresh = win.at(staged, col, row);
      uint32_t s0 = 2, p0 = 0;
#pragma unroll 1
      for (uint32_t j = staged; j < count; j++) {
        int x = (int)col * 7 - 1, y = (int)row * 7;
        uint32_t at = 7 * j % kRows * X0_ROW;
        if (fresh) {
          const uint32_t s1 = (s0 == 2) ? 0 : s0 + 1;
          cv.start_column(halo + s0 * HALO_ROW, hbar + 8 * s0, p0, halo + s1 * HALO_ROW, hbar + 8 * s1, p0 ^ (s0 == 2), lane, tail + T_DUMP, true,
                          &tm1, ch, x, y + 2);
          p0 ^= (s0 != 0);
          s0 = (s0 == 0) ? 2 : s0 - 1;
        }
        const uint32_t slot[3] = {s0, (s0 == 2) ? 0 : s0 + 1, (s0 == 0) ? 2 : s0 - 1}, parity[3] = {p0, p0 ^ (s0 == 2), p0 ^ (s0 != 0)};
        if (chunk == 0 && j + 1 == win.count) {
          if (lane == 0) {
            const uint32_t i = atomicInc(&scr->claims, gridDim.x - 1);
            uint32_t extra = ~0u;
            if (i < split.pool) {
              const uint32_t v = kWinPerCol * (kWinPerCol - split.rows) - split.pool + i, c = (v * split.magic[1]) >> 20;
              extra = c + 256 * (v - c * (kWinPerCol - split.rows) + split.rows);
              prefetch_box(&tm7, 7 * c - 1, 7 * (extra >> 8) - 1);
              prefetch_box(&tm7, 7 * c - 1, 7 * (extra >> 8) + 1);
            }
            sts32(tail + T_EXTRA, extra);
            mbar_arrive(tail + T_CLAIM);
          }
          __syncwarp();
        }
        if (chunk == 0 && j + 2 < win.count) {
          if (win.at(j + 2, col, row)) prefetch_rows(&tm7, 7 * col - 1, 7 * row - 1);
          prefetch_rows(&tm7, 7 * col - 1, 7 * row + 1);
        }
        fresh = win.at(j + 1, col, row);
        auto step = [&](auto r) {
          constexpr int R = decltype(r)::value;
          if (R == kRows - 14) {
            mbar_wait(tail + T_X0FREE + 8 * (j & 1), ((j >> 1) & 1) ^ 1);
          }
          if (R == 4) {
            if (j + 1 == win.count) {
              mbar_wait(tail + T_CLAIM, 0);
              const uint32_t extra = __shfl_sync(0xffffffffu, lds32(tail + T_EXTRA), 0);
              count += (extra != ~0u);
              col = extra & 255;
              row = extra >> 8;
              fresh = true;
            }
            x = (int)col * 7 - 1;
            y = (int)row * 7 - (fresh ? 9 : 7);
          }
          mbar_wait(hbar + 8 * slot[R % 3], parity[R % 3] ^ ((R / 3) & 1));
          cv.template row<R>(src + slot[R % 3] * HALO_ROW, dst, at);
          if (R < 4 || j + 1 < count) load_rows<HALO_ROW>(halo + slot[R % 3] * HALO_ROW, &tm1, ch, x, y + R + 4, hbar + 8 * slot[R % 3]);
          at = (at == (kRows - 1) * X0_ROW) ? 0 : at + X0_ROW;
        };
        step(Int<0>()); step(Int<1>()); step(Int<2>()); step(Int<3>()); step(Int<4>()); step(Int<5>()); step(Int<6>());
        __syncwarp();
        arrive_elected(tail + T_X0FULL + 8 * (j % 3));
        s0 = slot[1];
        p0 = parity[1];
      }
    }
    __syncwarp();
    asm volatile("bar.arrive 6, 512;" ::: "memory");
  } else {
    asm volatile("setmaxnreg.inc.sync.aligned.u32 %0;" ::"n"(152));
    const uint32_t wid = __shfl_sync(0xffffffffu, fresh_tid() >> 5, 0);
    const uint32_t wg = wid >> 2, warp = wid & 3;
    uint32_t lane;
    asm volatile("mov.u32 %0, %%laneid;" : "=r"(lane));
    const uint32_t count = Windows(split).count;
    const uint32_t q = lane & 3, mat = lane >> 3, row = lane & 7;
    const uint32_t area = sb + OFF_KV + wg * KV_SIZE;
    const uint32_t bars = tail + T_WG + 32 * wg;
    const bool full = warp < 3;
    const bool valid = full || lane < 4;
    const bool lead = lane == 0;
    uint32_t k_st, v_st, x_ld, x_mask, x_row, o_st;
    {
      const uint32_t rowg = full ? 2 * warp + (mat & 1) : 6, colg = full ? (mat >> 1) : (mat & 1);
      k_st = full ? area + A_K0 + colg * K_CHUNK + rowg * 128 + row * 16 : area + A_K0 + 768 + q * 4;
      v_st = full ? area + A_V0 + colg * V_GROUP + rowg * 128 + row * 16 : area + A_ONES + lane * 16;
      const uint32_t t = 16 * warp + row + 8 * (mat & 1);
      x_ld = (t < 49) ? sb + OFF_X0 + t * 128 + (((mat >> 1) ^ row) << 4) : tail + T_ZERO;
      x_mask = (t < 49) ? ~0u : 0u;
      x_row = t / 7;
      const uint32_t a = area + (full ? t : 48) * 64;
      o_st = a + (((full ? (mat >> 1) : 0) ^ ((a >> 7) & 3)) << 4) + (full ? 0 : 4 * q);
    }
    const uint32_t v_last = area + A_LAST + q * 32;
    const uint32_t pad = (valid ? 0u : 0xFC00u) | (full ? 0u : 0xFC000000u);
    const uint64_t k_desc = make_desc(area + A_K0, K_CHUNK, 128);
    const uint64_t v_desc = make_desc(area + A_V0, 128, V_GROUP);
    const uint64_t w_desc = make_desc(sb + OFF_RING, 128, 256);
    if (wg == 2) asm volatile("bar.arrive 8, 256;" ::: "memory");
    auto send_output = [&](uint32_t j, uint32_t parity, bool last) {
      uint32_t col, row;
      if (last) Windows(split).at(j, col, row, __shfl_sync(0xffffffffu, lds32(tail + T_EXTRA), 0));
      else Windows(split).at(j, col, row);
      mbar_wait(bars + B_OUTRDY, parity);
      store_window(&tmo, area, 7 * col, 7 * row);
    };
    uint32_t round = 0;
#pragma unroll 1
    for (; 3 * round + wg <= count; round++) {
      const uint32_t r = __shfl_sync(0xffffffffu, round, 0), j = 3 * r + wg, ph = r & 1;
      if (j == count) {
        mbar_wait(tail + T_CLAIM, 0);
        if (__shfl_sync(0xffffffffu, lds32(tail + T_EXTRA), 0) == ~0u) break;
      }
      const uint32_t m = 8 * r / 3, rot = 8 * r - 3 * m;
      const uint32_t ra = 8 * rot, rb = (rot == 2) ? 0 : ra + 8, rc = (rot == 0) ? 16 : ra - 8;
      const uint32_t pa = m & 1, pb = pa ^ (rot == 2), pc = pa ^ (rot != 0);
      uint32_t x[48], ka[24], va[24], oa[24], ob[24], rr, scales;
      uint32_t (&qa)[24] = ka;
      uint32_t sc0[14], sc1[14], pa0[12], pa1[12], ov0[14], ov1[14];
      mbar_wait(tail + T_X0FULL + 8 * wg, ph);
      asm volatile("" : "+r"(x_mask));
      const uint32_t x_at = 7 * j % kRows;
      const uint32_t x_a = x_ld + ((x_at * X0_ROW - (x_row >= kRows - x_at ? X0_CHUNK : 0)) & x_mask);
      auto load_x = [&](auto s0, auto s1) {
#pragma unroll
        for (int s = decltype(s0)::value; s < decltype(s1)::value; s++)
          ldsm4((x_a ^ (((s & 3) << 5) & x_mask)) + ((s >> 2) * X0_CHUNK & x_mask), x[4 * s], x[4 * s + 1], x[4 * s + 2], x[4 * s + 3]);
      };
      load_x(Int<0>(), Int<6>());
#pragma unroll
      for (int p = 0; p < 2; p++) {
        asm volatile("bar.sync %0, 256;" ::"r"(8 + wg) : "memory");
        mbar_wait(tail + T_FULL + ra, pa ^ p);
        if (p == 0) {
          load_x(Int<6>(), Int<12>());
          warp_arrive(tail + T_X0FREE + 8 * (j & 1), lead);
        }
        wg_fence();
        {
          const uint64_t d = desc_at(w_desc, ra * (W_PART / 8));
          issue_half<1>(ka, x, d);
          if (p == 0) wg_fence();
          issue_half<0>(ka, x, d);
        }
        wg_commit();
        if (p == 0) {
          if (!full && r > 0) send_output(j - 3, ph ^ 1, false);
        }
        if (p == 1) {
          wg_wait<1>();
          fence_regs(ov1);
          if (lead) mbar_arrive(bars + B_KVFREE);
          pack_o<0, 2>(ov1, &oa[12]);
        }
        mbar_wait(tail + T_FULL + rb, pb ^ p);
        wg_fence();
        {
          const uint64_t d = desc_at(w_desc, rb * (W_PART / 8));
          issue_half<1>(va, x, d);
          wg_commit();
          wg_wait<1>();
          if (lead) mbar_arrive(tail + T_EMPTY + ra);
          __syncwarp();
          issue_half<0>(va, x, d);
          wg_commit();
        }
        asm volatile("bar.arrive %0, 256;" ::"r"(wg == 2 ? 8 : 9 + wg) : "memory");
        if (p == 0) {
          scales = __shfl_sync(0xffffffffu, lds32(tail + T_SCALE), 0);
          const bool odd = q & 1;
          uint32_t lane_sums[2];
          lane_stats_packed(x, lane_sums);
          const uint32_t packed = quad_stats_packed(lane_sums, odd);
          float sum = h_lo(packed), squares = h_hi(packed);
          const bool fine = (squares >= 0.1875f || (pad & (odd ? 0xFC000000u : 0xFC00u))) & (squares <= 65504.f) & (sum * sum <= 96.f * squares);
          const bool exact = !__all_sync(0xffffffffu, fine);
          if (exact) {
            wg_wait<0>();
            row_stats(x, odd, sum, squares);
          }
          const float mean = sum * (1.f / 192.f);
          const float rs = 16.f * rsqrt_fast(fmaxf(fmaf(squares, 1.f / 192.f, -mean * mean), 0.f) + 1e-5f);
          if (exact) {
            const uint32_t range = __reduce_max_sync(0xffffffffu, __float_as_uint(squares * fmaxf(rs * rs, 1.f)));
            if ((range > 0x4D400000u || (range != 0u && range < 0x4585A800u)) && lead) {
              scr->redo[blockIdx.x + gridDim.x * j] = 1;
              sts32(tail + T_ANY, 1u);
            }
          }
          const float o = __shfl_xor_sync(0xffffffffu, rs, 1);
          rr = pack_f16(odd ? o : rs, odd ? rs : o);
          if (!full) {
            asm volatile("cp.async.bulk.wait_group.read 0;" ::: "memory");
            warp_arrive(bars + B_OUTFREE, lead);
          }
          mbar_wait(bars + B_OUTFREE, ph);
        } else {
          mbar_wait(bars + B_KVFREE, 0);
        }
        fence_regs(ka);
        store_k(ka, k_st, full, lane < 4, rr);
        mbar_wait(tail + T_FULL + rc, pc ^ p);
        wg_fence();
        {
          const uint64_t d = desc_at(w_desc, rc * (W_PART / 8));
          issue_half<2>(qa, x, d);
          wg_commit();
          wg_wait<1>();
          if (lead) mbar_arrive(tail + T_EMPTY + rb);
          __syncwarp();
          issue_half<0>(qa, x, d);
          wg_commit();
        }
        fence_regs(va);
        if (p == 0 && !full) {
          sts128_if(true, v_st, 0x3C003C00u, 0x3C003C00u, 0x3C003C00u, 0x3C003C00u);
          sts128_if(lane < 16, v_st + 512, 0x3C003C00u, 0x3C003C00u, 0x3C003C00u, 0x3C003C00u);
        }
        store_v(va, v_st, v_last, full, lane < 4, rr);
        fence_async();
        warp_arrive(bars + B_KVRDY, lead);
        wg_wait<0>();
        fence_regs(qa);
        if (lead) mbar_arrive(tail + T_EMPTY + rc);
        {
          const uint32_t rq = hmul2(rr, 0x18001800u);
#pragma unroll
          for (int i = 0; i < 24; i += 2) {
            qa[i] = hmul2_lo(qa[i], rq);
            qa[i + 1] = hmul2_hi(qa[i + 1], rq);
          }
        }
        const uint32_t cr = (p == 0) ? both<0>(scales) : both<1>(scales);
        mbar_wait(bars + B_KVRDY, p);

        wg_fence();
        issue_s(sc0, &qa[0], desc_at(k_desc, 0));
        wg_commit();
        uint32_t top0, top1, last0, last1;
        if (p == 0) {
          issue_s(sc1, &qa[12], desc_at(k_desc, A_K1));
          wg_commit();
          wg_wait<1>();
          fence_regs(sc0);
          top0 = softmax_top(sc0, lane, cr, last0);
          softmax_rows<12, 0>(sc0, top0, last0, cr, pad, v_last, pa0, ov0);
          wg_fence();
          issue_pv(ov0, pa0, desc_at(v_desc, 0));
          wg_commit();
          wg_wait<1>();
          fence_regs(sc1);
          top1 = softmax_top(sc1, lane, cr, last1);
          softmax_rows<0, 2>(sc1, top1, last1, cr, pad, v_last + 128, pa1, ov1);
        } else {
          wg_wait<0>();
          fence_regs(sc0);
          wg_fence();
          issue_s(sc1, &qa[12], desc_at(k_desc, A_K1));
          wg_commit();
          top0 = softmax_top(sc0, lane, cr, last0);
          wg_wait<0>();
          fence_regs(sc1);
          softmax_rows<12, 0>(sc0, top0, last0, cr, pad, v_last, pa0, ov0);
          mbar_wait(tail + T_FULL + ra, pa);
          wg_fence();
          issue_pv(ov0, pa0, desc_at(v_desc, 0));
          wg_commit();
          issue_out<6>(x, oa, desc_at(w_desc, ra * (W_PART / 8)));
          wg_commit();
          top1 = softmax_top(sc1, lane, cr, last1);
          wg_wait<1>();
          fence_regs(ov0);
          softmax_rows<0, 2>(sc1, top1, last1, cr, pad, v_last + 128, pa1, ov1);
        }
        wg_fence();
        issue_pv(ov1, pa1, desc_at(v_desc, A_ONES - A_V0));
        wg_commit();
        wg_wait<1>();
        if (p == 0) fence_regs(ov0);
        else if (lead) mbar_arrive(tail + T_EMPTY + ra);
        {
          uint32_t big;
          asm("{\n.reg .pred p, q;\n.reg .b32 t;\nmax.xorsign.abs.f16x2 t, %1, %2;\nabs.f16x2 t, t;\nsetp.gt.f16x2 p|q, t, %3;\n"
              "or.pred p, p, q;\nselp.u32 %0, 1, 0, p;\n}" : "=r"(big) : "r"(top0), "r"(top1), "r"(0x60006000u));
          if (__any_sync(0xffffffffu, big) && lead) {
            scr->redo[blockIdx.x + gridDim.x * j] = 1;
            sts32(tail + T_ANY, 1u);
          }
          __syncwarp();
        }
        uint32_t (&o)[24] = (p == 0) ? oa : ob;
        pack_o<12, 0>(ov0, &o[0]);
        if (p == 1) {
          mbar_wait(tail + T_FULL + rb, pb);
          wg_fence();
          issue_out<3>(x, &ob[0], desc_at(w_desc, rb * (W_PART / 8)));
          wg_commit();
          wg_wait<1>();
          fence_regs(ov1);
          if (lead) mbar_arrive(bars + B_KVFREE);
          pack_o<0, 2>(ov1, &o[12]);
        }
      }
      wg_fence();
      issue_out<3>(x, &ob[12], desc_at(w_desc, rb * (W_PART / 8) + 3 * WO_STEP));
      wg_commit();
      mbar_wait(bars + B_KVFREE, 1);
      wg_wait<0>();
      fence_regs(x);
      if (lead) mbar_arrive(tail + T_EMPTY + rb);
      asm volatile("" : "+r"(o_st));
      if (full) {
#pragma unroll
        for (int s = 0; s < 12; s++)
          stsm4((o_st ^ (((s ^ (s >> 1)) & 1) << 5)) + (s >> 1) * OUT_GROUP, f16x2_to_bf16x2(x[4 * s]), f16x2_to_bf16x2(x[4 * s + 1]),
                f16x2_to_bf16x2(x[4 * s + 2]), f16x2_to_bf16x2(x[4 * s + 3]));
        fence_async();
        warp_arrive(bars + B_OUTRDY, lead);
      } else {
#pragma unroll
        for (int i = 0; i < 24; i++)
          sts32_if(lane < 4, (o_st ^ (((i ^ ((i >> 1) & 2)) & 3) << 4)) + (i >> 2) * OUT_GROUP, f16x2_to_bf16x2(x[2 * i]));
        fence_async();
        warp_arrive(bars + B_OUTRDY, lead);
      }
    }
    if (!full && round > 0) send_output(3 * round + wg - 3, (round & 1) ^ 1, true);
    if (3 * round <= count) {
#pragma unroll 1
      for (uint32_t i = 0; i < 5; i++) {
        if (i % 3 == 0) {
          asm volatile("bar.sync %0, 256;" ::"r"(8 + wg) : "memory");
          asm volatile("bar.arrive %0, 256;" ::"r"(wg == 2 ? 8 : 9 + wg) : "memory");
        }
        const uint32_t u = 8 * round + i;
        mbar_wait(tail + T_FULL + 8 * (u % 3), (u / 3) & 1);
        if (lead) mbar_arrive(tail + T_EMPTY + 8 * (u % 3));
        __syncwarp();
      }
    }
    asm volatile("cp.async.bulk.wait_group.read 0;" ::: "memory");
    __syncwarp();
    asm volatile("bar.sync 6, 512;" ::: "memory");
    const uint32_t redo_all = lds32(tail + T_ALL);
    if (redo_all | lds32(tail + T_ANY)) {
      const uint32_t t = fresh_tid(), c = t >> 7;
      asm volatile("cp.async.bulk.wait_group 0;\nfence.proxy.async.global;" ::: "memory");
      const Windows win(split);
      const uint32_t extra = lds32(tail + T_EXTRA);
      for (uint32_t j = c; j < win.count + (extra != ~0u); j += 3) {
        uint8_t* flag = &scr->redo[blockIdx.x + gridDim.x * j];
        if (!redo_all && !*reinterpret_cast<volatile uint8_t*>(flag)) continue;
        uint32_t col, row;
        win.at(j, col, row, extra);
        redo_window(7 * col, 7 * row, t & 127, 1 + c, smem_raw + c * REDO_BYTES, x_raw, dw, wqkv_raw, wo_raw, out);
        if ((t & 127) == 0) *flag = 0;
      }
    }
  }
}

typedef CUresult (*EncodeTiledFn)(CUtensorMap*, CUtensorMapDataType, cuuint32_t, void*, const cuuint64_t*, const cuuint64_t*,
                                  const cuuint32_t*, const cuuint32_t*, CUtensorMapInterleave, CUtensorMapSwizzle,
                                  CUtensorMapL2promotion, CUtensorMapFloatOOBfill);

}

extern "C" void kernel_launch(void* const* d_in, const int* in_sizes, int n_in, void* d_out, int out_size) {
  (void)in_sizes; (void)n_in; (void)out_size;
  static EncodeTiledFn encode = nullptr;
  static int grid = 0;
  static void* scratch = nullptr;
  if (!encode) {
    void* fn = nullptr;
    cudaDriverEntryPointQueryResult st;
    cudaGetDriverEntryPoint("cuTensorMapEncodeTiled", &fn, cudaEnableDefault, &st);
    encode = (EncodeTiledFn)fn;
    cudaFuncSetAttribute(davit_window_attn_kernel, cudaFuncAttributeMaxDynamicSharedMemorySize, SMEM_BYTES);
    cudaGetSymbolAddress(&scratch, g_scratch);
    int dev = 0;
    cudaGetDevice(&dev);
    cudaDeviceGetAttribute(&grid, cudaDevAttrMultiProcessorCount, dev);
    if (grid > 1024) grid = 1024;
  }
  Split split = {};
  {
    const uint32_t g = grid, n = kNumWin / g;
    if (g > kWinPerCol && g <= 2 * kWinPerCol && kWinPerCol - n <= n) {
      const uint32_t below = (kWinPerCol - n) * kWinPerCol;
      split.top = kWinPerCol;
      split.rows = (below > (n + 1) * (g - kWinPerCol) && n + 1 < kWinPerCol) ? n + 1 : n;
      split.alone = kWinPerCol - split.rows;
    }
    const uint32_t others = g - split.top, rest = kNumWin - split.top * split.rows - others * split.alone;
    split.share = rest / others;
    split.pool = rest % others;
    split.magic[0] = split.rows ? ((1u << 20) + split.rows - 1) / split.rows : 0;
    split.magic[1] = ((1u << 20) + kWinPerCol - split.rows - 1) / (kWinPerCol - split.rows);
  }
  auto image_map = [&](void* base, cuuint32_t c, cuuint32_t w, cuuint32_t h, CUtensorMapSwizzle swizzle) {
    CUtensorMap tm;
    const cuuint64_t dims[3] = {(cuuint64_t)kCh, (cuuint64_t)kImg, (cuuint64_t)kImg};
    const cuuint64_t strides[2] = {(cuuint64_t)kCh * 2, (cuuint64_t)kCh * 2 * kImg};
    const cuuint32_t box[3] = {c, w, h};
    const cuuint32_t estr[3] = {1, 1, 1};
    encode(&tm, CU_TENSOR_MAP_DATA_TYPE_BFLOAT16, 3, base, dims, strides, box, estr, CU_TENSOR_MAP_INTERLEAVE_NONE, swizzle,
           CU_TENSOR_MAP_L2_PROMOTION_L2_128B, CU_TENSOR_MAP_FLOAT_OOB_FILL_NONE);
    return tm;
  };
  auto weight_map = [&](void* base, cuuint64_t cols, cuuint32_t rows) {
    CUtensorMap tm;
    const cuuint64_t dims[2] = {cols, (cuuint64_t)kCh};
    const cuuint64_t strides[1] = {cols * 2};
    const cuuint32_t box[2] = {32, rows};
    const cuuint32_t estr[2] = {1, 1};
    encode(&tm, CU_TENSOR_MAP_DATA_TYPE_BFLOAT16, 2, base, dims, strides, box, estr, CU_TENSOR_MAP_INTERLEAVE_NONE,
           CU_TENSOR_MAP_SWIZZLE_64B, CU_TENSOR_MAP_L2_PROMOTION_L2_128B, CU_TENSOR_MAP_FLOAT_OOB_FILL_NONE);
    return tm;
  };
  davit_window_attn_kernel<<<grid, 512, SMEM_BYTES, cudaStreamPerThread>>>(
      image_map(d_in[0], 64, 9, 1, CU_TENSOR_MAP_SWIZZLE_NONE), image_map(d_in[0], 64, 9, 7, CU_TENSOR_MAP_SWIZZLE_NONE),
      image_map(d_in[0], 192, 9, 7, CU_TENSOR_MAP_SWIZZLE_NONE), image_map(d_out, 32, 7, 7, CU_TENSOR_MAP_SWIZZLE_64B),
      weight_map(d_in[2], 576, 192), weight_map(d_in[3], 192, 32),
      (const __nv_bfloat16*)d_in[1], (const __nv_bfloat16*)d_in[0], (const __nv_bfloat16*)d_in[2], (const __nv_bfloat16*)d_in[3],
      (__nv_bfloat16*)d_out, (Scratch*)scratch, split);
}
```
